```python
import torch

def _softmax(x, axis=-1):
    return torch.softmax(x, dim=axis)

def _gelu(x):
    return torch.nn.functional.gelu(x, approximate='tanh')

def _silu(x):
    return torch.nn.functional.silu(x)

def _sigmoid(x):
    return torch.sigmoid(x)

def _layernorm(x, axis=-1, eps=1e-05):
    m = x.mean(dim=axis, keepdim=True)
    v = x.var(dim=axis, keepdim=True, unbiased=False)
    return (x - m) / torch.sqrt(v + eps)

def _scatter_add(tgt, idx, src, axis=0):
    return tgt.clone().index_add_(axis, idx, src)

def _segment_sum(src, seg, n):
    out = torch.zeros((n,) + src.shape[1:], dtype=src.dtype)
    return out.index_add_(0, seg, src)

def _pad(x, pw):
    flat = tuple((v for pair in reversed(pw) for v in pair))
    return torch.nn.functional.pad(x, flat)
kernel_name = 'standalone__video_video_swin__vision'

def setup_inputs():

    _w = lambda a: (lambda t: t.to(torch.bfloat16) if t.is_floating_point() else t)(torch.as_tensor(a))
    T = 4
    H = W = 512 // 7 * 7
    C, win = (96, 7)
    return {'x': _w((lambda *s: torch.randn(*s, dtype=torch.bfloat16) * 0.1)(1, T, H, W, C)), 'wqkv_t': _w((lambda *s: torch.randn(*s, dtype=torch.bfloat16) * 0.1)(C, 3 * C)), 'wo_t': _w((lambda *s: torch.randn(*s, dtype=torch.bfloat16) * 0.1)(C, C)), 'wqkv_s': _w((lambda *s: torch.randn(*s, dtype=torch.bfloat16) * 0.1)(C, 3 * C)), 'wo_s': _w((lambda *s: torch.randn(*s, dtype=torch.bfloat16) * 0.05)(C, C))}

def reference(x, wqkv_t, wo_t, wqkv_s, wo_s):
    B, T, H, W, C = x.shape
    win = 7
    scale = C ** (-0.5)
    h = _layernorm(x, axis=-1)
    ht = (lambda x, *d: x.permute(*d))(h, 0, 2, 3, 1, 4).reshape(B * H * W, T, C)
    qkv = ht @ wqkv_t
    q, k, v = (qkv[..., :C].clone(), qkv[..., C:2 * C].clone(), qkv[..., 2 * C:].clone())
    p = _softmax(torch.einsum('btc,bsc->bts', q, k) * scale, axis=-1)
    ot = torch.einsum('bts,bsc->btc', p, v) @ wo_t
    ot = (lambda x, *d: x.permute(*d))(ot.reshape(B, H, W, T, C), 0, 3, 1, 2, 4)
    x = x + ot
    h = _layernorm(x, axis=-1)
    nh, nw = (H // win, W // win)
    hs = h.reshape(B * T, nh, win, nw, win, C)
    hw = (lambda x, *d: x.permute(*d))(hs, 0, 1, 3, 2, 4, 5).reshape(B * T * nh * nw, win * win, C)
    qkv = hw @ wqkv_s
    q, k, v = (qkv[..., :C].clone(), qkv[..., C:2 * C].clone(), qkv[..., 2 * C:].clone())
    p = _softmax(torch.einsum('bqc,bkc->bqk', q, k) * scale, axis=-1)
    os = torch.einsum('bqk,bkc->bqc', p, v) @ wo_s
    os = (lambda x, *d: x.permute(*d))(os.reshape(B * T, nh, nw, win, win, C), 0, 1, 3, 2, 4, 5)
    os = os.reshape(B, T, H, W, C)
    return x + os
```

```cpp
#include <cuda_runtime.h>
#include <cuda.h>
#include <cuda_bf16.h>
#include <cuda_fp16.h>
#include <stdint.h>

namespace {

constexpr int kH = 511, kW = 511, kT = 4;
constexpr int kNWX = 73, kNWIN = 73 * 73;
constexpr int kChunk = 12544;
constexpr int kPlane = 3136;
constexpr int kXBytes = 37632;
constexpr int kBufStride = 38912;
constexpr int kWMat = 18432;
constexpr int kAtChunk = 104 * 64;
constexpr int kOffWt = 3 * kAtChunk;
constexpr int kOffAs = kOffWt + kWMat, kOffWs = kOffAs + kWMat;
constexpr int kWBytes = kOffWs + kWMat;
constexpr int kOffBuf = kWBytes;
constexpr int kOffBar = kOffBuf + 4 * kBufStride;
constexpr int kOffFlag = kOffBar + 96;
constexpr int kSmemBytes = kOffBar + 128;
constexpr int kNWG = 4;

struct Params {
  float cS_t, cS_s;
  float kt;
  float kappa;
  float kb;
};

__device__ uint4 g_wimg[kWBytes / 16];
__device__ __align__(16) Params g_par;
#define TR(i, k)

__device__ __forceinline__ uint32_t smem_u32(const void* p) { return (uint32_t)__cvta_generic_to_shared(p); }
__device__ __forceinline__ void mbar_init(uint32_t a, int c) { asm volatile("mbarrier.init.shared::cta.b64 [%0], %1;" ::"r"(a), "r"(c)); }
__device__ __forceinline__ void mbar_expect(uint32_t a, int bytes) {
  asm volatile("mbarrier.arrive.expect_tx.shared::cta.b64 _, [%0], %1;" ::"r"(a), "r"(bytes) : "memory");
}
__device__ __forceinline__ void mbar_arrive(uint32_t a) {
  asm volatile("mbarrier.arrive.shared::cta.b64 _, [%0];" ::"r"(a) : "memory");
}
__device__ __forceinline__ void mbar_wait(uint32_t a, uint32_t par) {
  asm volatile(
      "{\n.reg .pred p;\n.reg .u32 n;\n"
      "mbarrier.try_wait.parity.shared::cta.b64 p, [%0], %1;\n"
      "@p bra.uni WDONE;\n"
      "mov.u32 n, 0;\n"
      "WLOOP:\n"
      "mbarrier.try_wait.parity.shared::cta.b64 p, [%0], %1;\n"
      "@p bra.uni WDONE;\n"
      "add.u32 n, n, 1;\n"
      "setp.lt.u32 p, n, 0x1000000;\n"
      "@p bra.uni WLOOP;\n"
      "trap;\n"
      "WDONE:\n}" ::"r"(a), "r"(par) : "memory");
}
__device__ __forceinline__ void mbar_arrive_n(uint32_t a, uint32_t n, uint32_t doit) {
  asm volatile("{\n.reg .pred p;\nsetp.ne.u32 p, %2, 0;\n@p mbarrier.arrive.shared::cta.b64 _, [%0], %1;\n}" ::"r"(a), "r"(n), "r"(doit) : "memory");
}
__device__ __forceinline__ void tma_load_win(uint32_t dst, const CUtensorMap* m, uint32_t bar, uint32_t w) {
  const uint32_t wy = (w * 57457u) >> 22, wx = w - wy * kNWX;
  asm volatile(
      "cp.async.bulk.tensor.5d.shared::cluster.global.mbarrier::complete_tx::bytes [%0], [%1, {%3,%4,%5,%3,%3}], [%2];" ::"r"(dst),
      "l"(m), "r"(bar), "r"(0), "r"(wx * 7), "r"(wy * 7)
      : "memory");
}
__device__ __forceinline__ void wg_fence() { asm volatile("wgmma.fence.sync.aligned;" ::: "memory"); }
__device__ __forceinline__ void wg_commit() { asm volatile("wgmma.commit_group.sync.aligned;" ::: "memory"); }
template <int N>
__device__ __forceinline__ void wg_wait() { asm volatile("wgmma.wait_group.sync.aligned %0;" ::"n"(N) : "memory"); }
template <int N>
__device__ __forceinline__ void pin(uint32_t* d) {
#pragma unroll
  for (int i = 0; i < N; i++) asm volatile("" : "+r"(d[i])::"memory");
}
__device__ __forceinline__ void sched_fence(uint32_t a, uint32_t b, uint32_t c) {
  asm volatile("{\n.reg .pred p;\n.reg .b32 t;\nsetp.ne.u32 p, %0, 0x7fffffff;\n@p bra.uni SFD;\n"
               "add.u32 t, %1, %2;\nadd.u32 t, t, %3;\nst.volatile.shared.b32 [t], t;\nSFD:\n}" ::"r"(gridDim.x), "r"(a), "r"(b), "r"(c) : "memory");
}
__device__ __forceinline__ uint64_t mk_desc(uint32_t addr, uint32_t lbo16) {
  return ((uint64_t)0x80000020u << 32) | ((addr >> 4) & 0x3fff) | (lbo16 << 16);
}

#define R4(d, i) "+r"(d[i]), "+r"(d[i + 1]), "+r"(d[i + 2]), "+r"(d[i + 3])
#define O4(d, i) "=r"(d[i]), "=r"(d[i + 1]), "=r"(d[i + 2]), "=r"(d[i + 3])
#define D24 "{%0,%1,%2,%3,%4,%5,%6,%7,%8,%9,%10,%11,%12,%13,%14,%15,%16,%17,%18,%19,%20,%21,%22,%23},"
#define D14 "{%0,%1,%2,%3,%4,%5,%6,%7,%8,%9,%10,%11,%12,%13},"

template <int SC, int TB>
__device__ __forceinline__ void wg96h(uint32_t (&d)[24], const uint32_t* a, uint64_t db) {
  if (SC)
    asm volatile("wgmma.mma_async.sync.aligned.m64n96k16.f16.f16.f16 " D24 "{%24,%25,%26,%27}, %28, 1, 1, 1, %29;"
                 : R4(d, 0), R4(d, 4), R4(d, 8), R4(d, 12), R4(d, 16), R4(d, 20)
                 : "r"(a[0]), "r"(a[1]), "r"(a[2]), "r"(a[3]), "l"(db), "n"(TB));
  else
    asm volatile("wgmma.mma_async.sync.aligned.m64n96k16.f16.f16.f16 " D24 "{%24,%25,%26,%27}, %28, 0, 1, 1, %29;"
                 : O4(d, 0), O4(d, 4), O4(d, 8), O4(d, 12), O4(d, 16), O4(d, 20)
                 : "r"(a[0]), "r"(a[1]), "r"(a[2]), "r"(a[3]), "l"(db), "n"(TB));
}
template <int SC>
__device__ __forceinline__ void wg104h(uint32_t (&d)[26], const uint32_t* a, uint64_t db) {
  if (SC)
    asm volatile("wgmma.mma_async.sync.aligned.m64n104k16.f16.f16.f16 "
                 "{%0,%1,%2,%3,%4,%5,%6,%7,%8,%9,%10,%11,%12,%13,%14,%15,%16,%17,%18,%19,%20,%21,%22,%23,%24,%25},"
                 "{%26,%27,%28,%29}, %30, 1, 1, 1, 0;"
                 : R4(d, 0), R4(d, 4), R4(d, 8), R4(d, 12), R4(d, 16), R4(d, 20), "+r"(d[24]), "+r"(d[25])
                 : "r"(a[0]), "r"(a[1]), "r"(a[2]), "r"(a[3]), "l"(db));
  else
    asm volatile("wgmma.mma_async.sync.aligned.m64n104k16.f16.f16.f16 "
                 "{%0,%1,%2,%3,%4,%5,%6,%7,%8,%9,%10,%11,%12,%13,%14,%15,%16,%17,%18,%19,%20,%21,%22,%23,%24,%25},"
                 "{%26,%27,%28,%29}, %30, 0, 1, 1, 0;"
                 : O4(d, 0), O4(d, 4), O4(d, 8), O4(d, 12), O4(d, 16), O4(d, 20), "=r"(d[24]), "=r"(d[25])
                 : "r"(a[0]), "r"(a[1]), "r"(a[2]), "r"(a[3]), "l"(db));
}
template <int SC>
__device__ __forceinline__ void wg56h(uint32_t (&d)[16], const uint32_t* a, uint64_t db) {
  if (SC)
    asm volatile("wgmma.mma_async.sync.aligned.m64n56k16.f16.f16.f16 " D14 "{%14,%15,%16,%17}, %18, 1, 1, 1, 0;"
                 : R4(d, 0), R4(d, 4), R4(d, 8), "+r"(d[12]), "+r"(d[13])
                 : "r"(a[0]), "r"(a[1]), "r"(a[2]), "r"(a[3]), "l"(db));
  else
    asm volatile("wgmma.mma_async.sync.aligned.m64n56k16.f16.f16.f16 " D14 "{%14,%15,%16,%17}, %18, 0, 1, 1, 0;"
                 : O4(d, 0), O4(d, 4), O4(d, 8), "=r"(d[12]), "=r"(d[13])
                 : "r"(a[0]), "r"(a[1]), "r"(a[2]), "r"(a[3]), "l"(db));
}
template <int SC>
__device__ __forceinline__ void gemm_w(uint32_t (&d)[24], const uint32_t* a, uint64_t dw) {
  wg_fence();
  wg96h<SC, 0>(d, a, dw); wg96h<1, 0>(d, a + 4, dw + 2);
  wg96h<1, 0>(d, a + 8, dw + 384); wg96h<1, 0>(d, a + 12, dw + 386);
  wg96h<1, 0>(d, a + 16, dw + 768); wg96h<1, 0>(d, a + 20, dw + 770);
  wg_commit();
}
__device__ __forceinline__ void lds128(uint32_t* r, uint32_t a) {
  asm volatile("ld.shared.v4.b32 {%0,%1,%2,%3}, [%4];" : "=r"(r[0]), "=r"(r[1]), "=r"(r[2]), "=r"(r[3]) : "r"(a) : "memory");
}
__device__ __forceinline__ void ldsm4(uint32_t* r, uint32_t a) {
  asm volatile("ldmatrix.sync.aligned.m8n8.x4.shared.b16 {%0,%1,%2,%3}, [%4];"
               : "=r"(r[0]), "=r"(r[1]), "=r"(r[2]), "=r"(r[3]) : "r"(a) : "memory");
}
__device__ __forceinline__ void stsm4(uint32_t a, const uint32_t* r) {
  asm volatile("stmatrix.sync.aligned.m8n8.x4.shared.b16 [%0], {%1,%2,%3,%4};" ::"r"(a), "r"(r[0]), "r"(r[1]), "r"(r[2]), "r"(r[3])
               : "memory");
}
__device__ __forceinline__ uint32_t pack_h2(float lo, float hi) {
  uint32_t r; asm("cvt.rn.f16x2.f32 %0, %1, %2;" : "=r"(r) : "f"(hi), "f"(lo)); return r;
}
__device__ __forceinline__ uint32_t pack_h2_sat(float lo, float hi) {
  uint32_t r; asm("cvt.rn.satfinite.f16x2.f32 %0, %1, %2;" : "=r"(r) : "f"(hi), "f"(lo)); return r;
}
__device__ __forceinline__ uint32_t pack_bf2(float lo, float hi) {
  uint32_t r; asm("cvt.rn.bf16x2.f32 %0, %1, %2;" : "=r"(r) : "f"(hi), "f"(lo)); return r;
}
__device__ __forceinline__ __half2 as_h2(uint32_t v) { return *reinterpret_cast<__half2*>(&v); }
__device__ __forceinline__ uint32_t as_u(__half2 v) { return *reinterpret_cast<uint32_t*>(&v); }
__device__ __forceinline__ float2 unpack_h2(uint32_t v) { return __half22float2(as_h2(v)); }
__device__ __forceinline__ uint32_t h2ex2(uint32_t v) { uint32_t r; asm("ex2.approx.f16x2 %0, %1;" : "=r"(r) : "r"(v)); return r; }
__device__ __forceinline__ uint32_t h2max(uint32_t a, uint32_t b) { return as_u(__hmax2(as_h2(a), as_h2(b))); }
__device__ __forceinline__ uint32_t h2add(uint32_t a, uint32_t b) { return as_u(__hadd2(as_h2(a), as_h2(b))); }
__device__ __forceinline__ uint32_t h2sub(uint32_t a, uint32_t b) { return as_u(__hsub2(as_h2(a), as_h2(b))); }
__device__ __forceinline__ uint32_t h2mul(uint32_t a, uint32_t b) { return as_u(__hmul2(as_h2(a), as_h2(b))); }
__device__ __forceinline__ uint32_t h2fma(uint32_t a, uint32_t b, uint32_t c) { return as_u(__hfma2(as_h2(a), as_h2(b), as_h2(c))); }
__device__ __forceinline__ uint32_t lo2(uint32_t v) { return as_u(__low2half2(as_h2(v))); }
__device__ __forceinline__ uint32_t hi2(uint32_t v) { return as_u(__high2half2(as_h2(v))); }
__device__ __forceinline__ uint32_t fold_add(uint32_t a, uint32_t b) { return h2add(__byte_perm(a, b, 0x5410), __byte_perm(a, b, 0x7632)); }
__device__ __forceinline__ uint32_t bitsel(uint32_t a, uint32_t m, uint32_t c) {
  uint32_t r; asm("lop3.b32 %0, %1, %2, %3, 0xe2;" : "=r"(r) : "r"(a), "r"(m), "r"(c)); return r;
}
__device__ __forceinline__ uint32_t sel(bool p, uint32_t a, uint32_t b) {
  uint32_t r; asm("{\n.reg .pred p;\nsetp.ne.u32 p, %3, 0;\nselp.b32 %0, %1, %2, p;\n}" : "=r"(r) : "r"(a), "r"(b), "r"((uint32_t)p)); return r;
}
__device__ __forceinline__ float sel4(bool odd, bool up, float a, float b, float c, float d) {
  return __uint_as_float(sel(up, sel(odd, __float_as_uint(d), __float_as_uint(c)), sel(odd, __float_as_uint(b), __float_as_uint(a))));
}
__device__ __forceinline__ float rcp_fast(float v) { float r; asm("rcp.approx.ftz.f32 %0, %1;" : "=f"(r) : "f"(v)); return r; }
__device__ __forceinline__ float rsq_fast(float v) { float r; asm("rsqrt.approx.ftz.f32 %0, %1;" : "=f"(r) : "f"(v)); return r; }
__device__ __forceinline__ float quad_sum(float v) {
  v += __shfl_xor_sync(0xffffffffu, v, 1);
  return v + __shfl_xor_sync(0xffffffffu, v, 2);
}
__device__ __forceinline__ uint32_t quad_h2add(uint32_t v) {
  v = h2add(v, __shfl_xor_sync(0xffffffffu, v, 1));
  return h2add(v, __shfl_xor_sync(0xffffffffu, v, 2));
}
__device__ __forceinline__ uint32_t score_scale(const float* p) { const float v = __ldcg(p); return pack_h2(v, v); }

constexpr float kEps96 = 1e-5f * 96.f * 96.f;
__device__ __forceinline__ float2 stat_f32(uint32_t e) {
  const float2 h = unpack_h2(e);
  const bool w = e & 0x8000u;
  return make_float2(__uint_as_float(sel(w, (e << 16) & 0x7fff0000u, __float_as_uint(h.x))), __uint_as_float(sel(w, e & 0xffff0000u, __float_as_uint(h.y))));
}
__device__ __forceinline__ void stg128(uint8_t* p, const uint32_t* r, uint32_t off) {
  asm volatile("{\n.reg .pred p;\nsetp.eq.u32 p, %5, 0;\n@p st.global.v4.b32 [%0], {%1,%2,%3,%4};\n}" ::"l"(p), "r"(r[0]), "r"(r[1]), "r"(r[2]), "r"(r[3]),
               "r"(off) : "memory");
}
template <int N>
__device__ __forceinline__ void launder(uint32_t* q) {
#pragma unroll
  for (int j = 0; j < N; j++) { uint32_t t; asm volatile("mov.b32 %0, %1;" : "=r"(t) : "r"(q[j])); q[j] = t; }
}

#define LB 512
#define LAU 1
#define NOWIDE 0
#define LAV 4
#define X 0
#define SMODE 2
#define RT 128
#define TM 4
#define TROLE 0
#define SF 0
#define SG 0
__device__ __forceinline__ void sfence(uint32_t& v) {
  asm volatile("{\n.reg .pred p;\nsetp.eq.u32 p, %1, 0x7fffffff;\n@p mov.u32 %0, %%clock;\n}" : "+r"(v) : "r"(gridDim.x) : "memory");
}
#define sf() sfence(tid)
#define FG(m, b) do { if ((m) & (b)) sf(); } while (0)
__device__ __forceinline__ uint32_t fresh(uint32_t v) { asm volatile("" : "+r"(v)); return v; }
#define V1 1
#define EA 1
#define CB 0
#define ET 1
#define HELP 3
#define PRE 2
#define RB 1
#define QS 2
#define GT 255
#define HT 255
#define GS 168
#define HS 255
__device__ __forceinline__ void gemm_at(uint32_t (&d)[26], const uint32_t* a, uint64_t da) {
  wg_fence();
  wg104h<0>(d, a, da); wg104h<1>(d, a + 4, da + 2);
  wg104h<1>(d, a + 8, da + 416); wg104h<1>(d, a + 12, da + 418);
  wg104h<1>(d, a + 16, da + 832); wg104h<1>(d, a + 20, da + 834);
  wg_commit();
}
__device__ __forceinline__ void load_rows(uint32_t* x0, uint32_t* x1, uint32_t a0, uint32_t a1) {
  a0 ^= (a0 >> 3) & 0x30; a1 ^= (a1 >> 3) & 0x30;
  lds128(x0, a0); lds128(x1, a1);
  lds128(x0 + 4, (a0 ^ 32) + kChunk); lds128(x1 + 4, (a1 ^ 32) + kChunk);
  lds128(x0 + 8, a0 + 2 * kChunk); lds128(x1 + 8, a1 + 2 * kChunk);
}
__device__ __forceinline__ uint32_t sumsq2(const uint32_t* z) {
  uint32_t q0, q1;
#pragma unroll
  for (int j = 0; j < 12; j++) {
    const uint32_t u = z[2 * j], v = z[2 * j + 1];
    q0 = j ? h2fma(u, u, q0) : h2mul(u, u); q1 = j ? h2fma(v, v, q1) : h2mul(v, v);
  }
  return fold_add(q0, q1);
}
__device__ __forceinline__ void to_half(uint32_t (&z)[24], const uint32_t* x) {
#pragma unroll
  for (int j = 0; j < 12; j++) {
    z[2 * j] = pack_h2(__uint_as_float(x[j] << 16), __uint_as_float(x[j] & 0xffff0000u));
    z[2 * j + 1] = pack_h2(__uint_as_float(x[12 + j] << 16), __uint_as_float(x[12 + j] & 0xffff0000u));
  }
}
__device__ __forceinline__ void load_general(uint32_t (&z)[24], uint32_t a0, float& ie0, float& ie1, float& m0, float& m1) {
  float acc[48];
  uint32_t x0[12], x1[12];
  load_rows(x0, x1, a0, a0 + kPlane);
#pragma unroll
  for (int j = 0; j < 12; j++) {
    acc[4 * j] = __uint_as_float(x0[j] << 16); acc[4 * j + 1] = __uint_as_float(x0[j] & 0xffff0000u);
    acc[4 * j + 2] = __uint_as_float(x1[j] << 16); acc[4 * j + 3] = __uint_as_float(x1[j] & 0xffff0000u);
  }
  float s[4], q[4];
#pragma unroll
  for (int e = 0; e < 4; e++) { s[e] = acc[e]; q[e] = acc[e] * acc[e]; }
#pragma unroll
  for (int j = 4; j < 48; j++) { s[j & 3] += acc[j]; q[j & 3] = fmaf(acc[j], acc[j], q[j & 3]); }
  const float s0 = quad_sum(s[0] + s[1]), s1 = quad_sum(s[2] + s[3]), q0 = quad_sum(q[0] + q[1]), q1 = quad_sum(q[2] + q[3]);
  const float u0 = rsq_fast(fmaxf(fmaf(-s0, s0, fmaf(q0, 96.f, kEps96)), kEps96));
  const float u1 = rsq_fast(fmaxf(fmaf(-s1, s1, fmaf(q1, 96.f, kEps96)), kEps96));
  const float n0 = -s0 * u0, n1 = -s1 * u1;
  ie0 = 96.f * u0; ie1 = 96.f * u1;
  m0 = s0 * (1.f / 96.f); m1 = s1 * (1.f / 96.f);
#pragma unroll
  for (int j = 0; j < 12; j++) {
    z[2 * j] = pack_h2(fmaf(acc[4 * j], ie0, n0), fmaf(acc[4 * j + 1], ie0, n0));
    z[2 * j + 1] = pack_h2(fmaf(acc[4 * j + 2], ie1, n1), fmaf(acc[4 * j + 3], ie1, n1));
  }
}
__device__ __forceinline__ float2 sumsq2f(const uint32_t* z) {
  float2 r = make_float2(0.f, 0.f);
#pragma unroll
  for (int j = 0; j < 12; j++) {
    const float2 u = unpack_h2(z[2 * j]), v = unpack_h2(z[2 * j + 1]);
    r.x = fmaf(u.x, u.x, fmaf(u.y, u.y, r.x)); r.y = fmaf(v.x, v.x, fmaf(v.y, v.y, r.y));
  }
  return make_float2(quad_sum(r.x), quad_sum(r.y));
}
__device__ __forceinline__ uint32_t quad_scatter(uint32_t a, uint32_t b, bool up) {
  const uint32_t t = h2add(sel(up, b, a), __shfl_xor_sync(0xffffffffu, sel(up, a, b), 2));
  return h2add(t, __shfl_xor_sync(0xffffffffu, t, 1));
}
__device__ __forceinline__ void scores2(const uint32_t* q, const uint32_t* z0, const uint32_t* z1, uint32_t* f) {
  uint32_t d[8];
#pragma unroll
  for (int j = 0; j < 12; j++) {
    const uint32_t kk[4] = {z0[2 * j], z0[2 * j + 1], z1[2 * j], z1[2 * j + 1]};
#pragma unroll
    for (int e = 0; e < 4; e++) {
      d[e] = j ? h2fma(q[2 * j], kk[e], d[e]) : h2mul(q[2 * j], kk[e]);
      d[4 + e] = j ? h2fma(q[2 * j + 1], kk[e], d[4 + e]) : h2mul(q[2 * j + 1], kk[e]);
    }
  }
#pragma unroll
  for (int e = 0; e < 4; e++) f[e] = fold_add(d[2 * e], d[2 * e + 1]);
}
__device__ __forceinline__ void pair_scatter(uint32_t* k, const uint32_t* a, const uint32_t* b, bool up, int m) {
#pragma unroll
  for (int e = 0; e < 2; e++) k[e] = h2add(sel(up, b[e], a[e]), __shfl_xor_sync(0xffffffffu, sel(up, a[e], b[e]), m));
}
__device__ __forceinline__ void mix2(uint32_t* y, const uint32_t* v, uint32_t c0, uint32_t c1) {
#pragma unroll
  for (int j = 0; j < 12; j++) {
    y[2 * j] = h2fma(v[2 * j + 1], hi2(c0), h2fma(v[2 * j], lo2(c0), y[2 * j]));
    y[2 * j + 1] = h2fma(v[2 * j + 1], hi2(c1), h2fma(v[2 * j], lo2(c1), y[2 * j + 1]));
  }
}
__device__ __forceinline__ void norm_store(uint32_t* y, uint32_t r0, uint32_t r1, uint32_t ma) {
#pragma unroll
  for (int j = 0; j < 12; j++) { y[2 * j] = h2fma(y[2 * j], lo2(r0), hi2(r0)); y[2 * j + 1] = h2fma(y[2 * j + 1], lo2(r1), hi2(r1)); }
  ma ^= (ma >> 3) & 0x30;
  const uint32_t mb = ma ^ 32;
  stsm4(ma, y); stsm4(mb, y + 4);
  stsm4(mb + kChunk, y + 8); stsm4(ma + kChunk, y + 12);
  stsm4(ma + 2 * kChunk, y + 16); stsm4(mb + 2 * kChunk, y + 20);
}

template <bool kDirect>
__device__ __forceinline__ bool temporal(uint32_t sb, uint32_t bufA, uint32_t dB, int ow, int live, const Params& P, bool scaled, uint32_t flag, uint32_t& tid) {
  uint32_t lane = tid & 31;
  const bool odd = lane & 1, up = lane & 2;
  uint32_t a0 = bufA + ow * 64 + lane * 16 + ((int)(lane >> 2) >= 49 - ow ? dB - kPlane : 0);
  const uint64_t da = mk_desc(sb, 1), dv = mk_desc(sb + kOffWt, 1);
  uint32_t z0[24], z1[24], q0[26], q1[26], v0[24], v1[24], nn = 0, ca0 = 0, ca1 = 0;
  float ie = 1.f, mm = 0.f;
  bool tiny = false;
  if (kDirect) {
    uint32_t x[48];
    load_rows(x, x + 12, a0, a0 + kPlane);
    if (ET) { load_rows(x + 24, x + 36, a0 + 2 * kPlane, a0 + 3 * kPlane); sf(); }
    to_half(z0, x);
    gemm_at(q0, z0, da);
    FG(GT, 1);
    if (!ET) load_rows(x + 24, x + 36, a0 + 2 * kPlane, a0 + 3 * kPlane);
    to_half(z1, x + 24);
    pin<24>(z1); FG(HT, 1);
  } else {
    float e[4], m[4];
    load_general(z0, a0, e[0], e[1], m[0], m[1]);
    pin<24>(z0); sf();
    load_general(z1, a0 + 2 * kPlane, e[2], e[3], m[2], m[3]);
    tiny = __any_sync(0xffffffffu, fmaxf(fmaxf(e[0], e[1]), fmaxf(e[2], e[3])) * P.kt > 400.f);
    if (tiny) {
      const float2 u = sumsq2f(z0), w = sumsq2f(z1);
      const float ik = 9.8f * rsq_fast(fmaxf(fmaxf(fmaxf(u.x, u.y), fmaxf(w.x, w.y)), 2e-7f)) * rcp_fast(__uint_as_float(fresh(__float_as_uint(P.kt))));
      ca0 = pack_h2(__fdividef(fminf(e[0], ik), e[0]), __fdividef(fminf(e[1], ik), e[1]));
      ca1 = pack_h2(__fdividef(fminf(e[2], ik), e[2]), __fdividef(fminf(e[3], ik), e[3]));
#pragma unroll
      for (int j = 0; j < 4; j++) e[j] = fminf(e[j], ik);
    }
    ie = sel4(odd, up, e[0], e[1], e[2], e[3]);
    mm = sel4(odd, up, m[0], m[1], m[2], m[3]);
    gemm_at(q0, z0, da);
  }
  uint32_t f[4], k0[2], k1[2], sk[2];
  wg_wait<0>(); pin<26>(q0);
  gemm_w<0>(v0, z0, dv);
  FG(GT, 2);
  scores2(q0, z0, z1, f);
  const uint32_t nu0 = fresh(__byte_perm(q0[24], q0[25], 0x7632)), mp0 = fresh(__byte_perm(q0[24], q0[25], 0x5410));
  pin<4>(f); sf();
  wg_wait<0>(); pin<24>(v0);
  gemm_at(q1, z1, da);
  FG(GT, 4);
  pair_scatter(k0, f, f + 2, odd, 1);
  if (kDirect) nn = fresh(quad_scatter(sumsq2(z0), sumsq2(z1), up));
  pin<2>(k0); FG(HT, 4);
  wg_wait<0>(); pin<26>(q1);
  const uint32_t nu1 = fresh(__byte_perm(q1[24], q1[25], 0x7632));
  uint32_t rc = 0, r0 = 0, r1 = 0;
  float mz = 0.f;
  if (kDirect) {
    const uint32_t mp = sel(up, __byte_perm(q1[24], q1[25], 0x5410), mp0);
    const float2 t = unpack_h2(__byte_perm(nn, mp, odd ? 0x7632 : 0x5410));
    mz = t.y;
    const float e = fmaf(t.x, 1.f / 96.f, 1e-5f), d = fmaf(-mz, mz, e);
    const bool fine = (d >= fmaxf(0.8f * e, 4e-4f)) & (e <= 4.f);
    const float r = rsq_fast(d);
    rc = pack_h2(r, r);
    const uint32_t p = __byte_perm(rc, __shfl_xor_sync(0xffffffffu, rc, 1), odd ? 0x1054 : 0x5410);
    const uint32_t o = __shfl_xor_sync(0xffffffffu, p, 2);
    r0 = sel(up, o, p); r1 = sel(up, p, o);
    asm volatile("{\n.reg .pred p;\nsetp.ne.u32 p, %1, 0;\n@p st.volatile.shared.b32 [%0], %1;\n}" ::"r"(flag),
                 "r"((uint32_t)(!fine & ((int)(tid & 31) < 4 * live))) : "memory");
  }
  scores2(q1, z0, z1, f);
  pin<4>(f); sf();
  gemm_w<0>(v1, z1, dv);
  FG(GT, 8);
  pair_scatter(k1, f, f + 2, odd, 1);
  pair_scatter(sk, k0, k1, up, 2);
  uint32_t cw[8], mu;
  {
    if (kDirect) { sk[0] = h2mul(sk[0], r0); sk[1] = h2mul(sk[1], r1); }
    uint32_t mx = h2max(sk[0], sk[1]);
    mx = h2max(lo2(mx), hi2(mx));
    if (kDirect) {
      const uint32_t nm = h2mul(mx, rc) ^ 0x80008000u;
      sk[0] = h2fma(sk[0], rc, nm); sk[1] = h2fma(sk[1], rc, nm);
    } else {
      sk[0] = h2sub(sk[0], mx); sk[1] = h2sub(sk[1], mx);
      if (scaled) {
        const uint32_t cs = score_scale(&g_par.cS_t);
        sk[0] = h2mul(sk[0], cs); sk[1] = h2mul(sk[1], cs);
      }
    }
    sk[0] = h2ex2(sk[0]); sk[1] = h2ex2(sk[1]);
    const float2 sf = unpack_h2(h2add(sk[0], sk[1]));
    const float iv = (kDirect ? P.kt : P.kt * ie) * rcp_fast(sf.x + sf.y);
    const uint32_t inv = pack_h2(iv, iv);
    sk[0] = h2mul(sk[0], inv); sk[1] = h2mul(sk[1], inv);
    if (kDirect) { sk[0] = h2mul(sk[0], r0); sk[1] = h2mul(sk[1], r1); }
#pragma unroll
    for (int i = 0; i < 4; i++) { cw[2 * i] = __shfl_sync(0xffffffffu, sk[0], i, 4); cw[2 * i + 1] = __shfl_sync(0xffffffffu, sk[1], i, 4); }
    mu = h2fma(sk[1], nu1, h2mul(sk[0], nu0));
  }
  uint32_t bad = 0;
  if (kDirect) {
    mix2(z0, v0, cw[0], cw[2]);
    pin<24>(z0); FG(HT, 8);
    wg_wait<0>(); pin<24>(v1);
    asm volatile("ld.shared.b32 %0, [%1];" : "=r"(bad) : "r"(flag + (v1[0] & (gridDim.x == 0x7fffffffu))) : "memory");
  } else {
    wg_wait<0>(); pin<24>(v1);
    if (tiny) {
#pragma unroll
      for (int j = 0; j < 12; j++) {
        z0[2 * j] = h2mul(z0[2 * j], lo2(ca0)); z0[2 * j + 1] = h2mul(z0[2 * j + 1], hi2(ca0));
        z1[2 * j] = h2mul(z1[2 * j], lo2(ca1)); z1[2 * j + 1] = h2mul(z1[2 * j + 1], hi2(ca1));
      }
    }
    mix2(z0, v0, cw[0], cw[2]);
  }
  mix2(z0, v1, cw[1], cw[3]);
  mix2(z1, v0, cw[4], cw[6]);
  mix2(z1, v1, cw[5], cw[7]);
  const uint32_t t2 = quad_scatter(sumsq2(z0), sumsq2(z1), up);
  float qq = __low2float(as_h2(__byte_perm(t2, t2, odd ? 0x7632 : 0x5410)));
  if (__any_sync(0xffffffffu, !(qq < 65000.f) || bad != 0)) {
    if (kDirect && __any_sync(0xffffffffu, bad != 0)) return false;
    const float2 u = sumsq2f(z0), w = sumsq2f(z1);
    qq = sel4(odd, up, u.x, u.y, w.x, w.y);
  }
  const float rf = kDirect ? rsq_fast(fmaxf(fmaf(-mz, mz, fmaf(qq, 1.f / 96.f, 1e-5f)), 1e-5f)) : rsq_fast(fmaf(qq, 1.f / 96.f, 1e-5f * ie * ie));
  const uint32_t rn = pack_h2_sat(rf, -mz * rf);
  uint32_t rr[4];
#pragma unroll
  for (int i = 0; i < 4; i++) rr[i] = __shfl_sync(0xffffffffu, rn, i, 4);
  lane = tid & 31;
  const uint32_t ma = bufA + ow * 64 + (lane & 7) * 64 + (lane & 8) * (kPlane / 8) + (lane & 16) + ((int)(lane & 7) >= 49 - ow ? dB - kPlane : 0);
  norm_store(z0, rr[0], rr[1], ma);
  norm_store(z1, rr[2], rr[3], ma + 2 * kPlane);
  const float2 rm = unpack_h2(rn), mf = unpack_h2(mu);
  const float sg = rcp_fast(kDirect ? rm.x : rm.x * ie);
  mm = kDirect ? fmaf(-rm.y, sg, mf.x + mf.y) : fmaf((mf.x + mf.y) * rm.x, sg, mm);
  const float kap = __uint_as_float(fresh(__float_as_uint(P.kb)));
  const bool ok = (sg >= fmaxf(0.0045f, kap * 0.011f)) & (fmaf(sg, 9.8f, fabsf(mm)) < fmaf(kap, -627.2f, 60000.f));
  const uint32_t sa = bufA + kXBytes + ow * 4 + (lane & 0x1c) + (lane & 3) * 196 + ((int)(lane >> 2) >= 49 - ow ? dB - 196 : 0);
  asm volatile("st.shared.b32 [%0], %1;" ::"r"(sa), "r"(sel(ok, pack_h2(sg, mm), pack_bf2(-sg, mm))) : "memory");
  return true;
}

__device__ __forceinline__ void run_T(uint32_t sb, int nw, uint32_t pbeg, uint32_t pend, int tg, int wp, uint32_t tid, const Params& P, bool scaled, bool direct) {
  const uint32_t flag = sb + kOffFlag + tg * 4;
  const uint32_t barF = sb + kOffBar, barD = sb + kOffBar + 32;
  pend += 8 * wp;
  for (uint32_t p0 = pbeg + 8 * wp; p0 < pend;) {
    const uint32_t iw = (p0 * 21400u) >> 20;
    const int ow = p0 - 49 * iw;
    const uint32_t ia = iw & 3, ib = (iw + 1) & 3;
    const bool strad = ow > 41;
    const uint32_t bufA = sb + kOffBuf + ia * kBufStride, dB = (ib - ia) * kBufStride;
    if (wp == 3) TR(p0 >> 5, 1);
    mbar_wait(barF + ia * 8, (iw >> 2) & 1);
    if (strad) mbar_wait(barF + ib * 8, ((iw + 1) >> 2) & 1);
    if (wp == 3) TR(p0 >> 5, 2);
    bool done = false;
    if (direct) done = temporal<true>(sb, bufA, dB, ow, 49 * nw - p0, P, false, flag, tid);
    if (!done) {
      if (direct) {
        asm volatile("barrier.cta.sync.aligned %0, 128;" ::"r"(tg + 1) : "memory");
        asm volatile("st.shared.b32 [%0], %1;\nfence.acq_rel.cta;" ::"r"(flag), "r"(0) : "memory");
      }
      temporal<false>(sb, bufA, dB, ow, 0, P, scaled, flag, tid);
    }
    asm volatile("fence.proxy.async.shared::cta;" ::: "memory");
    __syncwarp();
    const bool l0 = (tid & 31) == 0;
    mbar_arrive_n(barD + ia * 8, strad ? 49 - ow : 8, l0);
    mbar_arrive_n(barD + ib * 8, ow - 41, l0 && strad);
    __syncwarp();
    if (wp == 3) TR(p0 >> 5, 3);
    p0 = __shfl_sync(0xffffffffu, p0 + 64, 0);
  }
}

struct Frame {
  bool light;
  uint32_t sta;
  uint32_t oo;
  uint32_t e0, e1;
};
__device__ __forceinline__ uint32_t frame_init(Frame& F, uint32_t t, int wp, int lane) {
  wp = (wp + t) & 3;
  F.light = wp == 3;
  F.sta = kXBytes + (49 * t + 16 * wp) * 4;
  const uint32_t r = 16 * wp + (lane >> 2);
  F.oo = ((r / 7) * (kW - 7) + r) * 12u + (lane & 3) + (((((r + 8) / 7) * (kW - 7) + r + 8) * 12u + (lane & 3)) << 16);
  F.e0 = F.e1 = 0x8000u;
  const uint32_t am = t * kPlane + wp * 1024 + ((lane * 65) & 0x3d0);
  return F.light && (lane & 15) ? kXBytes + 896 : am ^ ((am >> 3) & 0x30);
}
__device__ __forceinline__ uint32_t is_wide(const Frame& F) { return __ballot_sync(0xffffffffu, (F.e0 | F.e1) & 0x8000u); }
__device__ __forceinline__ void load_frame(uint32_t (&v)[24], uint32_t ma, uint32_t buf) {
  const uint32_t st = ma < kXBytes ? kChunk : 0, mb = ma ^ 32;
  ldsm4(v, buf + ma); ldsm4(v + 4, buf + mb);
  ldsm4(v + 8, buf + (mb + st)); ldsm4(v + 12, buf + (ma + st));
  ldsm4(v + 16, buf + (ma + 2 * st)); ldsm4(v + 20, buf + (mb + 2 * st));
}
__device__ __forceinline__ void load_stats(Frame& F, uint32_t a) {
  asm volatile("ld.shared.b32 %0, [%1];" : "=r"(F.e0) : "r"(a + F.sta) : "memory");
  asm volatile("ld.shared.b32 %0, [%1];" : "=r"(F.e1) : "r"(a + F.sta + 32) : "memory");
}
__device__ __forceinline__ void hand_over(uint32_t (&q)[24]) {
  pin<24>(q);
  launder<24>(q);
  if (gridDim.x == 0x7fffffffu) {
#pragma unroll
    for (int j = 0; j < 24; j++) asm volatile("not.b32 %0, %0;" : "+r"(q[j]));
  }
}
__device__ __forceinline__ void gemm_s(uint32_t (&s)[16], const uint32_t* q, uint32_t pl) {
  const uint64_t dA = mk_desc(pl, 1);
  wg_fence();
  wg56h<0>(s, q, dA); wg56h<1>(s, q + 4, dA + 2);
  wg56h<1>(s, q + 8, dA + 784); wg56h<1>(s, q + 12, dA + 786);
  wg56h<1>(s, q + 16, dA + 1568); wg56h<1>(s, q + 20, dA + 1570);
  wg_commit();
}
__device__ __forceinline__ void gemm_u(uint32_t (&u)[24], const uint32_t* s, uint32_t pl) {
  const uint64_t mn = mk_desc(pl, kChunk >> 4);
  wg_fence();
  wg96h<0, 1>(u, s, mn); wg96h<1, 1>(u, s + 4, mn + 64); wg96h<1, 1>(u, s + 8, mn + 128); wg96h<1, 1>(u, s + 12, mn + 192);
  wg_commit();
}
__device__ __forceinline__ uint32_t key48(uint32_t (&s)[16], uint32_t tid) {
  pin<14>(s);
  return fresh(sel(tid & 3, 0xfc00fc00u, __byte_perm(s[12], s[13], 0x5410)));
}
__device__ __forceinline__ uint32_t amax3(uint32_t a, uint32_t b, uint32_t c) {
  return as_u(__hmax2(__hmax2(__habs2(as_h2(a)), __habs2(as_h2(b))), __habs2(as_h2(c))));
}
__device__ __forceinline__ uint32_t soft_exp(uint32_t (&s)[16], uint32_t& t, uint32_t (&v)[24], Frame& F, float2& e) {
  const uint32_t am = h2max(h2max(h2max(amax3(s[0], s[1], s[2]), amax3(s[3], s[4], s[5])), amax3(s[6], s[7], s[8])), h2max(amax3(s[9], s[10], s[11]), t));
  const uint32_t al = __byte_perm(F.e0, F.e1, 0x5410);
  e = unpack_h2(al);
  uint32_t rare;
  asm("{\n.reg .pred p, q;\nsetp.eq.u32 q, %3, 0;\nsetp.le.and.f16x2 p|q, %1, %2, q;\nand.pred p, p, q;\nselp.b32 %0, 0, 1, p;\n}"
      : "=r"(rare) : "r"(am), "r"(0x47004700u), "r"(al & 0x80008000u));
  if (__any_sync(0xffffffffu, rare)) {
    const uint32_t x0 = h2max(h2max(h2max(s[0], s[2]), h2max(s[4], s[6])), h2max(s[8], s[10]));
    const uint32_t x1 = h2max(h2max(h2max(s[1], s[3]), h2max(s[5], s[7])), h2max(s[9], s[11]));
    uint32_t mx = h2max(h2max(__byte_perm(x0, x1, 0x5410), __byte_perm(x0, x1, 0x7632)), t);
    mx = h2max(mx, __shfl_xor_sync(0xffffffffu, mx, 1));
    mx = h2max(mx, __shfl_xor_sync(0xffffffffu, mx, 2));
    const uint32_t cs = score_scale(&g_par.cS_s);
#pragma unroll
    for (int j = 0; j < 6; j++) { s[2 * j] = h2mul(h2sub(s[2 * j], lo2(mx)), cs); s[2 * j + 1] = h2mul(h2sub(s[2 * j + 1], hi2(mx)), cs); }
    t = h2mul(h2sub(t, mx), cs);
    if (is_wide(F)) {
      const float s0 = stat_f32(F.e0).x, s1 = stat_f32(F.e1).x;
      const float kb = __ldcg(&g_par.kb), ik = rcp_fast(__ldcg(&g_par.kappa));
      e.x = fmaxf(s0, kb); e.y = fmaxf(s1, kb);
      const uint32_t aw = pack_h2(__fdividef(s0, e.x), __fdividef(s1, e.y));
      e.x *= ik; e.y *= ik;
#pragma unroll
      for (int j = 0; j < 12; j++) { v[2 * j] = h2mul(v[2 * j], lo2(aw)); v[2 * j + 1] = h2mul(v[2 * j + 1], hi2(aw)); }
    }
  }
#pragma unroll
  for (int j = 0; j < 12; j++) s[j] = h2ex2(s[j]);
  t = h2ex2(t);
  return fresh(h2add(t, fold_add(h2add(h2add(h2add(s[0], s[2]), h2add(s[4], s[6])), h2add(s[8], s[10])),
                                 h2add(h2add(h2add(s[1], s[3]), h2add(s[5], s[7])), h2add(s[9], s[11])))));
}
struct Quad { uint32_t v[4]; };
__device__ __forceinline__ Quad quad_send(uint32_t a) {
  Quad q;
  q.v[0] = a;
#pragma unroll
  for (int i = 1; i < (QS == 2 ? 4 : QS == 1 ? 2 : 1); i++) q.v[i] = __shfl_xor_sync(0xffffffffu, a, i);
  return q;
}
__device__ __forceinline__ uint32_t quad_recv(const Quad& q) {
  if (QS == 2) return h2add(h2add(q.v[0], q.v[1]), h2add(q.v[2], q.v[3]));
  if (QS == 0) return quad_h2add(q.v[0]);
  const uint32_t t = h2add(q.v[0], q.v[1]);
  return h2add(t, __shfl_xor_sync(0xffffffffu, t, 2));
}
__device__ __forceinline__ void soft_norm(uint32_t (&s)[16], uint32_t& t, const Quad& rsum, const Frame& F, float2 e, uint32_t tid) {
  const uint32_t kk2 = F.light ? ((tid & 28) == 0 ? 0xffffu : 0u) : 0xffffffffu;
  const float2 d = unpack_h2(quad_recv(rsum));
  const uint32_t cb = pack_h2(rcp_fast(d.x * e.x), rcp_fast(d.y * e.y)) & kk2;
#pragma unroll
  for (int j = 0; j < 6; j++) { s[2 * j] = h2mul(s[2 * j], lo2(cb)); s[2 * j + 1] = h2mul(s[2 * j + 1], hi2(cb)); }
  t = fresh(h2mul(t, cb));
  pin<12>(s);
}
__device__ __forceinline__ void soft_tail(uint32_t (&s)[16], uint32_t t) {
  s[12] = t & 0xffffu; s[13] = t >> 16;
  asm volatile("mov.b32 %0, 0;\nmov.b32 %1, 0;" : "=r"(s[14]), "=r"(s[15]));
}
template <int H>
__device__ __forceinline__ void store_rows(const uint32_t* r, const Frame& F, uint8_t* ob, uint32_t off) {
  const uint32_t oo = fresh(F.oo);
  uint8_t* o = ob + (size_t)(H ? oo >> 16 : oo & 0xffffu) * 16;
#pragma unroll
  for (int i = 0; i < 3; i++) stg128(o + 64 * i, r + 4 * i, off);
}
template <int H>
__device__ __forceinline__ void affine(uint32_t* r, const uint32_t (&v)[24], const Frame& F) {
  const uint32_t e = H ? F.e1 : F.e0;
#pragma unroll
  for (int j = 0; j < 12; j++) r[j] = h2fma(v[2 * j + H], lo2(e), hi2(e));
  pin<12>(r);
}
template <int H>
__device__ __forceinline__ void finish(uint32_t* r, const Frame& F, uint8_t* ob, uint32_t off) {
#pragma unroll
  for (int j = 0; j < 12; j++) { const float2 f = unpack_h2(r[j]); r[j] = pack_bf2(f.x, f.y); }
  store_rows<H>(r, F, ob, off);
}
template <int H>
__device__ __forceinline__ void finish_wide(const uint32_t (&v)[24], const Frame& F, uint8_t* ob, uint32_t tid) {
  const float2 z = stat_f32(H ? F.e1 : F.e0);
  const float w = fmaxf(z.x, __ldcg(&g_par.kb));
  uint32_t r[12];
#pragma unroll
  for (int j = 0; j < 12; j++) { const float2 f = unpack_h2(v[2 * j + H]); r[j] = pack_bf2(fmaf(f.x, w, z.y), fmaf(f.y, w, z.y)); }
  store_rows<H>(r, F, ob, F.light ? (H ? 1 : tid & 28) : 0);
}

__device__ __forceinline__ void release_slot(uint32_t sb, uint32_t i, int nw, uint32_t w, uint32_t wlast, int lane, const CUtensorMap* tm) {
  const uint32_t ia = i & 3;
  uint32_t old = 0;
  asm volatile("{\n.reg .pred p;\nsetp.eq.u32 p, %2, 0;\n@p atom.relaxed.cta.shared::cta.inc.u32 %0, [%1], 1;\n}"
               : "+r"(old) : "r"(sb + kOffBar + 80 + ia * 4), "r"(lane) : "memory");
  if (old == 1) {
    const uint32_t bar = sb + kOffBar + ia * 8;
    if (i + 4 < nw) {
      mbar_expect(bar, kXBytes);
      tma_load_win(sb + kOffBuf + ia * kBufStride, tm, bar, i + 5 == nw ? wlast : w + 4 * gridDim.x);
    } else if (i + 4 == nw) {
      mbar_arrive(bar);
    }
  }
  __syncwarp();
}
__device__ __forceinline__ void run_S(uint32_t sb, int nw, int i0, int nwS, uint32_t wlast, int sg, int wp, int lane,
                                      const CUtensorMap* tm, uint8_t* __restrict__ out) {
  constexpr size_t kFrame = (size_t)kH * kW * 192;
  Frame A, B;
  const uint32_t ld = frame_init(A, 2 * sg, wp, lane) + (frame_init(B, 2 * sg + 1, wp, lane) << 16);
  const uint64_t dQ = mk_desc(sb + kOffAs, 1), dO = mk_desc(sb + kOffWs, 1);
  uint32_t va[24], vb[24], x[24], sa[16], sc[16], r0[12], r1[12], ta, tb, wd;
  Quad rs;
  float2 e;
#pragma unroll
  for (int j = 0; j < 24; j++) vb[j] = 0;
  uint8_t* ob = out;
  uint32_t tid = lane;
  if (EA) { mbar_wait(sb + kOffBar + 32 + (i0 & 3) * 8, (i0 >> 2) & 1); load_frame(va, fresh(ld) & 0xffffu, sb + kOffBuf + (i0 & 3) * kBufStride); }
  int i = i0;
  do {
    const uint32_t ia = i & 3;
    const uint32_t buf = sb + kOffBuf + ia * kBufStride, pa = buf + 2 * sg * kPlane, pb = pa + kPlane;
    if (!EA) {
      mbar_wait(sb + kOffBar + 32 + ia * 8, (i >> 2) & 1);
      load_frame(va, fresh(ld) & 0xffffu, buf);
      sf();
      affine<0>(r0, vb, B); affine<1>(r1, vb, B);
      sf();
    }
    if (LAV & 8) launder<24>(va);
    gemm_w<0>(x, va, dQ);
    FG(GS, 1);
    wd = is_wide(B);
    if (EA) { affine<0>(r0, vb, B); affine<1>(r1, vb, B); sf(); }
    load_frame(vb, fresh(ld) >> 16, buf);
    load_stats(A, buf + (tid & 0x1c));
    FG(HS, 1);
    finish<0>(r0, B, ob + kFrame, (tid & (B.light ? 28 : 0)) | wd);
    if (!RB && !B.light) finish<1>(r1, B, ob + kFrame, wd);
    if (RB) sf();
    wg_wait<0>(); hand_over(x);
    gemm_s(sa, x, pa);
    FG(GS, 2);
    if (RB && !B.light) finish<1>(r1, B, ob + kFrame, wd);
    const uint32_t w = i + 1 == nw ? wlast : blockIdx.x + i * gridDim.x;
    ob = out + (size_t)((((w * 57457u) >> 22) * (7 * kW - 7 * kNWX) + w * 7 + sg * (2 * kH * kW)) * 192u);
    FG(HS, 2);
    wg_wait<0>(); pin<14>(sa);
    gemm_w<0>(x, vb, dQ);
    FG(GS, 4);
    ta = key48(sa, tid);
    rs = quad_send(soft_exp(sa, ta, va, A, e));
    FG(HS, 4);
    wg_wait<0>(); hand_over(x);
    gemm_s(sc, x, pb);
    FG(GS, 8);
    load_stats(B, buf + (tid & 0x1c));
    soft_norm(sa, ta, rs, A, e, tid);
    FG(HS, 8);
    wg_wait<0>();
    tb = key48(sc, tid);
    sf();
    soft_tail(sa, ta);
    gemm_u(x, sa, pa);
    FG(GS, 16);
    rs = quad_send(soft_exp(sc, tb, vb, B, e));
    FG(HS, 16);
    wg_wait<0>(); hand_over(x);
    if (LAV & 1) launder<24>(va);
    gemm_w<1>(va, x, dO);
    FG(GS, 32);
    soft_norm(sc, tb, rs, B, e, tid);
    soft_tail(sc, tb);
    FG(HS, 32);
    wg_wait<0>(); pin<24>(va);
    if (LAV & 16) launder<24>(va);
    gemm_u(x, sc, pb);
    FG(GS, 64);
    wd = is_wide(A);
    if (wd) { finish_wide<0>(va, A, ob, tid); finish_wide<1>(va, A, ob, tid); }
    affine<0>(r0, va, A);
    finish<0>(r0, A, ob, (tid & (A.light ? 28 : 0)) | wd);
    FG(HS, 64);
    wg_wait<0>(); hand_over(x);
    if (LAV & 2) launder<24>(vb);
    gemm_w<1>(vb, x, dO);
    FG(GS, 128);
    if (EA) {
      if (A.light) release_slot(sb, i, nw, w, wlast, tid & 31, tm);
      affine<1>(r1, va, A);
      if (wp == 2) TR(i + 1, 4 + 2 * sg);
      if (i + 1 < nwS) mbar_wait(sb + kOffBar + 32 + ((i + 1) & 3) * 8, ((i + 1) >> 2) & 1);
      if (wp == 2) TR(i + 1, 5 + 2 * sg);
      load_frame(va, fresh(ld) & 0xffffu, sb + kOffBuf + ((i + 1) & 3) * kBufStride);
      if (!A.light) finish<1>(r1, A, ob, wd);
    } else {
      if (A.light) release_slot(sb, i, nw, w, wlast, tid & 31, tm);
      else { affine<1>(r1, va, A); finish<1>(r1, A, ob, wd); }
    }
    wg_wait<0>(); pin<24>(vb);
    if (LAU) launder<24>(vb);
    if (LAV & 4) launder<24>(va);
    if (is_wide(B)) { finish_wide<0>(vb, B, ob + kFrame, tid); finish_wide<1>(vb, B, ob + kFrame, tid); }
  } while (++i < nwS);
  wd = is_wide(B);
  affine<0>(r0, vb, B); finish<0>(r0, B, ob + kFrame, (tid & (B.light ? 28 : 0)) | wd);
  affine<1>(r1, vb, B); finish<1>(r1, B, ob + kFrame, B.light | wd);
}

__global__ void __launch_bounds__(LB, 1) swin_main(const __grid_constant__ CUtensorMap tm, uint8_t* __restrict__ out) {
  extern __shared__ __align__(1024) uint8_t smem[];
  const uint32_t sb = CB ? 1024u : smem_u32(smem);
  const int tid = threadIdx.x;
  const int wg = __shfl_sync(0xffffffffu, tid >> 7, 0);
  const int wp = __shfl_sync(0xffffffffu, (tid >> 5) & 3, 0);
  const int lane = tid & 31;
  const int b = blockIdx.x, nb = gridDim.x;
  const int nfull = kNWIN / nb, nrem = kNWIN - nfull * nb;
  const bool share = 2 * nrem <= nb;
  const int nw = nfull + (b < (share ? 2 * nrem : nrem));
  const bool half = share && nw > nfull;
  const uint32_t wlast = half && b >= nrem ? b - nrem + nfull * nb : b + (nw - 1) * nb;
  if (tid == 0) {
    if (sb != smem_u32(smem) || (sb & 1023) || nw > 700 || nw < 5) __trap();
#pragma unroll
    for (int i = 0; i < 4; i++) {
      mbar_init(sb + kOffBar + i * 8, 1);
      mbar_init(sb + kOffBar + 32 + i * 8, 49);
      asm volatile("st.shared.b32 [%0], %1;" ::"r"(sb + kOffBar + 80 + i * 4), "r"(0) : "memory");
    }
    for (int i = 0; i < 4; i++) asm volatile("st.shared.b32 [%0], %1;" ::"r"(sb + kOffFlag + i * 4), "r"(0) : "memory");
    asm volatile("fence.mbarrier_init.release.cluster;" ::: "memory");
    for (int i = 0; i < PRE; i++) {
      mbar_expect(sb + kOffBar + i * 8, kXBytes);
      tma_load_win(sb + kOffBuf + i * kBufStride, &tm, sb + kOffBar + i * 8, b + i * nb);
    }
  }
  __syncwarp();
  if (wg == 1 || wg == 2)
    asm volatile("st.shared.v4.b32 [%0], {%1,%1,%1,%1};" ::"r"(sb + kOffBuf + ((tid - 128) >> 6) * kBufStride + kXBytes + (tid & 63) * 16), "r"(0) : "memory");
  __syncthreads();
  asm volatile("griddepcontrol.wait;" ::: "memory");
#pragma unroll
  for (int q = 0; q < kWBytes / 16 / 512; q++)
    asm volatile("cp.async.cg.shared.global [%0], [%1], 16;" ::"r"(sb + (tid + q * 512) * 16), "l"(g_wimg + tid + q * 512) : "memory");
  if (wg == 0 && wp < 3) {
    static_assert(kWBytes / 16 == 9 * 512 + 96, "weight copy split");
    const int e = tid + 9 * 512;
    asm volatile("cp.async.cg.shared.global [%0], [%1], 16;" ::"r"(sb + e * 16), "l"(g_wimg + e) : "memory");
  }
  Params P;
  {
    const float4 p0 = __ldcg(reinterpret_cast<const float4*>(&g_par));
    P.cS_t = p0.x; P.cS_s = p0.y; P.kt = p0.z; P.kappa = p0.w;
    const float kb = __ldcg(&g_par.kb);
    P.kb = P.cS_s != 1.f || P.kappa != 1.f ? 1e30f : kb;
  }
  const bool scaled = __any_sync(0xffffffffu, P.cS_t != 1.f);
  const bool direct = __all_sync(0xffffffffu, !scaled && P.kt <= 256.f);
  asm volatile("cp.async.wait_all;\nfence.proxy.async.shared::cta;" ::: "memory");
  if (tid == 0) {
    for (int i = PRE; i < 4; i++) {
      mbar_expect(sb + kOffBar + i * 8, kXBytes);
      tma_load_win(sb + kOffBuf + i * kBufStride, &tm, sb + kOffBar + i * 8, b + i * nb);
    }
  }
  __syncthreads();
  const bool isT = (wg >> 1) == TROLE;
  const int g2 = wg & 1;
  run_T(sb, nw, 32 * g2 + (isT && HELP & 1 ? 64 : 0), isT ? 49 * nw : HELP & 1 ? 64 : 0, wg, wp, tid, P, scaled, direct);
  const int skip = half && (b >= nrem) != g2;
  const int i0 = isT ? (HELP & 2 ? nw - 1 : nw) : 0, i1 = isT || !(HELP & 2) ? nw - skip : nw - 1;
  if (i0 < i1) run_S(sb, nw, i0, i1, wlast, g2, wp, lane, &tm, out);
}

__device__ __forceinline__ int ch_pos(int ch) { return 32 * (ch >> 5) + 8 * ((ch >> 1) & 3) + 2 * ((ch >> 3) & 3) + (ch & 1); }
__device__ __forceinline__ float pow2_ceil(float v) {
  return __uint_as_float((__float_as_uint(v) + 0x7fffffu) & 0x7f800000u);
}

constexpr int kPrepSplit = 12;
constexpr int kPrepThreads = 384;
__global__ void __launch_bounds__(kPrepThreads) swin_prep(const __nv_bfloat16* __restrict__ wqkv_t, const __nv_bfloat16* __restrict__ wo_t,
                                                          const __nv_bfloat16* __restrict__ wqkv_s, const __nv_bfloat16* __restrict__ wo_s) {
  asm volatile("griddepcontrol.launch_dependents;");
  __shared__ __align__(16) uint32_t raw[2][96][52];
  __shared__ __align__(16) uint32_t mu[3][52];
  __shared__ float nrm[12], nrm2[6], csum[6][9];
  const int mat = blockIdx.x / kPrepSplit, blk = blockIdx.x % kPrepSplit;
  const int tid = threadIdx.x, lane = tid & 31, warp = tid >> 5, g = lane >> 2, c = lane & 3;
  const __nv_bfloat16* wqkv = mat < 2 ? wqkv_t : wqkv_s;
  const __nv_bfloat16* wo = mat < 2 ? wo_t : wo_s;
  const bool isA = (mat & 1) == 0;
  {
    uint4 v[3], u[3];
#pragma unroll
    for (int q = 0; q < 3; q++) {
      const int e = tid + q * kPrepThreads, i = e / 12, c8 = (e % 12) * 8;
      v[q] = __ldg(reinterpret_cast<const uint4*>(wqkv + i * 288 + (isA ? 0 : 192) + c8));
      u[q] = __ldg(reinterpret_cast<const uint4*>(isA ? wqkv + i * 288 + 96 + c8 : wo + i * 96 + c8));
    }
#pragma unroll
    for (int q = 0; q < 3; q++) {
      const int e = tid + q * kPrepThreads, i = e / 12, c4 = (e % 12) * 4;
      *reinterpret_cast<uint4*>(&raw[0][i][c4]) = v[q];
      *reinterpret_cast<uint4*>(&raw[1][i][c4]) = u[q];
    }
  }
  __syncthreads();
  {
    const int m = warp / 6, cp = (warp % 6) * 8 + g;
    float s0 = 0.f, s1 = 0.f, q0 = 0.f, q1 = 0.f;
#pragma unroll
    for (int i = 0; i < 24; i++) {
      const uint32_t w = raw[m][4 * i + c][cp];
      const float lo = __uint_as_float(w << 16), hi = __uint_as_float(w & 0xffff0000u);
      s0 += lo; s1 += hi; q0 = fmaf(lo, lo, q0); q1 = fmaf(hi, hi, q1);
    }
    s0 = quad_sum(s0) * (1.f / 96.f); s1 = quad_sum(s1) * (1.f / 96.f); q0 = quad_sum(q0); q1 = quad_sum(q1);
    if (mat == 1 && m == 1) {
      float r0 = 0.f, r1 = 0.f;
#pragma unroll
      for (int i = 0; i < 12; i++) {
        const uint32_t w0 = raw[1][2 * cp][4 * i + c], w1 = raw[1][2 * cp + 1][4 * i + c];
        r0 += __uint_as_float(w0 << 16) + __uint_as_float(w0 & 0xffff0000u);
        r1 += __uint_as_float(w1 << 16) + __uint_as_float(w1 & 0xffff0000u);
      }
      r0 = quad_sum(r0) * (1.f / 96.f); r1 = quad_sum(r1) * (1.f / 96.f);
      s0 = r0; s1 = r1;
    }
    if (m == 1 && c == 0) {
      const uint32_t hi = mat == 3 ? 0u : pack_bf2(s0, s1);
      mu[0][cp] = hi;
      mu[1][cp] = mat == 3 ? 0u : pack_bf2(s0 - __uint_as_float(hi << 16), s1 - __uint_as_float(hi & 0xffff0000u));
      mu[2][cp] = 0u;
    }
    if (m == 0 || isA) {
      q0 = fmaxf(fmaf(-96.f * s0, s0, q0), 0.f) + q0 * 1e-6f;
      q1 = fmaxf(fmaf(-96.f * s1, s1, q1), 0.f) + q1 * 1e-6f;
    }
    const bool usemax = m == 1 && mat == 3;
    float t = usemax ? fmaxf(q0, q1) : q0 + q1;
#pragma unroll
    for (int o = 4; o < 32; o <<= 1) { const float z = __shfl_xor_sync(0xffffffffu, t, o); t = usemax ? fmaxf(t, z) : t + z; }
    if (lane == 0) nrm[warp] = t;
  }
  __syncthreads();
  if (warp >= 6) return;
  float d[4] = {0.f, 0.f, 0.f, 0.f}, e[4] = {0.f, 0.f, 0.f, 0.f}, v0, v1;
  {
    const uint32_t arow = smem_u32(&raw[0][16 * warp + (lane & 15)][(lane >> 4) * 4]);
    const uint32_t brow = isA ? smem_u32(&raw[1][blk * 8 + (lane & 7)][(lane >> 3) * 4]) : smem_u32(&raw[1][lane][blk * 4]);
    const uint32_t mrow = smem_u32(&mu[min(lane & 7, 2)][(lane >> 3) * 4]);
#pragma unroll
    for (int k2 = 0; k2 < 3; k2++) {
      uint32_t b[4], m[4];
      if (isA) ldsm4(b, brow + k2 * 64);
      else asm volatile("ldmatrix.sync.aligned.m8n8.x4.trans.shared.b16 {%0,%1,%2,%3}, [%4];"
                        : "=r"(b[0]), "=r"(b[1]), "=r"(b[2]), "=r"(b[3]) : "r"(brow + k2 * (32 * 208)) : "memory");
      ldsm4(m, mrow + k2 * 64);
#pragma unroll
      for (int hf = 0; hf < 2; hf++) {
        uint32_t a[4];
        ldsm4(a, arow + (2 * k2 + hf) * 32);
        asm volatile("mma.sync.aligned.m16n8k16.row.col.f32.bf16.bf16.f32 {%0,%1,%2,%3},{%4,%5,%6,%7},{%8,%9},{%0,%1,%2,%3};"
                     : "+f"(d[0]), "+f"(d[1]), "+f"(d[2]), "+f"(d[3])
                     : "r"(a[0]), "r"(a[1]), "r"(a[2]), "r"(a[3]), "r"(b[2 * hf]), "r"(b[2 * hf + 1]));
        asm volatile("mma.sync.aligned.m16n8k16.row.col.f32.bf16.bf16.f32 {%0,%1,%2,%3},{%4,%5,%6,%7},{%8,%9},{%0,%1,%2,%3};"
                     : "+f"(e[0]), "+f"(e[1]), "+f"(e[2]), "+f"(e[3])
                     : "r"(a[0]), "r"(a[1]), "r"(a[2]), "r"(a[3]), "r"(m[2 * hf]), "r"(m[2 * hf + 1]));
      }
    }
    v0 = __shfl_sync(0xffffffffu, e[0] + e[1], lane & ~3); v1 = __shfl_sync(0xffffffffu, e[2] + e[3], lane & ~3);
    d[0] -= v0; d[1] -= v0; d[2] -= v1; d[3] -= v1;
    float t0 = d[0] + d[2], t1 = d[1] + d[3], t2 = v0 + v1;
#pragma unroll
    for (int o = 4; o < 32; o <<= 1) {
      t0 += __shfl_xor_sync(0xffffffffu, t0, o); t1 += __shfl_xor_sync(0xffffffffu, t1, o); t2 += __shfl_xor_sync(0xffffffffu, t2, o);
    }
    if (g == 0) { csum[warp][2 * c] = t0; csum[warp][2 * c + 1] = t1; csum[warp][8] = t2; }
  }
  const float nl = nrm[0] + nrm[1] + nrm[2] + nrm[3] + nrm[4] + nrm[5];
  const float nr = mat == 3 ? fmaxf(fmaxf(fmaxf(nrm[6], nrm[7]), fmaxf(nrm[8], nrm[9])), fmaxf(nrm[10], nrm[11]))
                            : nrm[6] + nrm[7] + nrm[8] + nrm[9] + nrm[10] + nrm[11];
  const float bound = __fsqrt_rn(nl) * __fsqrt_rn(nr) * 1.01f;
  const float f = isA ? 0.14724448f : 1.f;
  float sc = pow2_ceil(fmaxf(bound * (isA ? 0.14724448f / 160.f : mat == 1 ? 1.f / 16.f : 1.f / 64.f), 1e-30f));
  if (isA) sc = fminf(fmaxf(sc, 1.f), 32768.f);
  if (mat == 3) {
    if (blk == 0 && tid == 0) g_par.kb = sc;
    if (sc <= 1.f && sc >= 1.f / 1024.f) sc = 1.f;
  }
  const float mul = f * __uint_as_float(0x7f000000u - __float_as_uint(sc));
  if (blk == 0 && tid == 0) (mat == 0 ? g_par.cS_t : mat == 1 ? g_par.kt : mat == 2 ? g_par.cS_s : g_par.kappa) = sc;
  asm volatile("bar.sync 1, 192;" ::: "memory");
  float mean[2];
#pragma unroll
  for (int b = 0; b < 2; b++)
    mean[b] = (csum[0][2 * c + b] + csum[1][2 * c + b] + csum[2][2 * c + b] + csum[3][2 * c + b] + csum[4][2 * c + b] + csum[5][2 * c + b]) *
              (1.f / 96.f);
  uint8_t* img = reinterpret_cast<uint8_t*>(g_wimg) + (mat == 0 ? 0 : mat == 1 ? kOffWt : mat == 2 ? kOffAs : kOffWs);
  const float vmean = (csum[0][8] + csum[1][8] + csum[2][8] + csum[3][8] + csum[4][8] + csum[5][8]) * (1.f / 96.f);
  float off = 0.f;
  if (mat == 2) {
    float q2 = 0.f;
#pragma unroll
    for (int q = 0; q < 4; q++) q2 = fmaf(d[q] - mean[q & 1], d[q] - mean[q & 1], q2);
#pragma unroll
    for (int o = 16; o; o >>= 1) q2 += __shfl_xor_sync(0xffffffffu, q2, o);
    if (lane == 0) nrm2[warp] = q2;
    asm volatile("bar.sync 1, 192;" ::: "memory");
    q2 = nrm2[0] + nrm2[1] + nrm2[2] + nrm2[3] + nrm2[4] + nrm2[5];
    off = 1.5f * pow2_ceil(fmaxf(__fsqrt_rn(q2 * (1.f / 768.f)) * mul * 3.f, 1e-4f));
  }
#pragma unroll
  for (int q = 0; q < 4; q++) {
    const int kp = ch_pos(16 * warp + g + 8 * (q >> 1)), np = ch_pos(blk * 8 + 2 * c + (q & 1));
    const uint32_t ko = (kp >> 5) * (mat == 0 ? kAtChunk : 6144) + (kp & 31) * 2;
    uint32_t a = ko + np * 64;
    a ^= ((a >> 7) & 3) << 4;
    float o = (d[q] - mean[q & 1]) * mul;
    o = mat == 2 ? o + off : __uint_as_float((__float_as_uint(o) + 0x8000u) & 0xffff0000u);
    *reinterpret_cast<__half*>(img + a) = __float2half_rn(o);
    if (mat == 1 && blk == 0) {
      a = (kp >> 5) * kAtChunk + (kp & 31) * 2 + (96 + 2 * c + (q & 1)) * 64;
      a ^= ((a >> 7) & 3) << 4;
      *reinterpret_cast<__half*>(reinterpret_cast<uint8_t*>(g_wimg) + a) = __float2half_rn((q & 1) ? ((q >> 1 ? v1 : v0) - vmean) * mul : 1.f / 96.f);
    }
  }
}

typedef CUresult (*EncodeFn)(CUtensorMap*, CUtensorMapDataType, cuuint32_t, void*, const cuuint64_t*, const cuuint64_t*,
                             const cuuint32_t*, const cuuint32_t*, CUtensorMapInterleave, CUtensorMapSwizzle,
                             CUtensorMapL2promotion, CUtensorMapFloatOOBfill);

}

extern "C" void kernel_launch(void* const* d_in, const int* in_sizes, int n_in, void* d_out, int out_size) {
  (void)in_sizes; (void)n_in; (void)out_size;
  static EncodeFn enc = nullptr;
  static int nsm = 0;
  if (!enc) {
    void* fn = nullptr;
    cudaDriverEntryPointQueryResult qr;
    cudaGetDriverEntryPoint("cuTensorMapEncodeTiled", &fn, cudaEnableDefault, &qr);
    enc = reinterpret_cast<EncodeFn>(fn);
    int dev = 0;
    cudaGetDevice(&dev);
    cudaDeviceGetAttribute(&nsm, cudaDevAttrMultiProcessorCount, dev);
    cudaFuncSetAttribute(swin_main, cudaFuncAttributeMaxDynamicSharedMemorySize, kSmemBytes);
  }
  CUtensorMap tm;
  const cuuint64_t dims[5] = {32, kW, kH, kT, 3};
  const cuuint64_t strides[4] = {192, 192ull * kW, 192ull * kW * kH, 64};
  const cuuint32_t box[5] = {32, 7, 7, 4, 3};
  const cuuint32_t es[5] = {1, 1, 1, 1, 1};
  enc(&tm, CU_TENSOR_MAP_DATA_TYPE_BFLOAT16, 5, d_in[0], dims, strides, box, es, CU_TENSOR_MAP_INTERLEAVE_NONE,
      CU_TENSOR_MAP_SWIZZLE_64B, CU_TENSOR_MAP_L2_PROMOTION_L2_128B, CU_TENSOR_MAP_FLOAT_OOB_FILL_NONE);

  cudaStream_t st = cudaStreamPerThread;
  swin_prep<<<4 * kPrepSplit, kPrepThreads, 0, st>>>(
      static_cast<const __nv_bfloat16*>(d_in[1]), static_cast<const __nv_bfloat16*>(d_in[2]),
      static_cast<const __nv_bfloat16*>(d_in[3]), static_cast<const __nv_bfloat16*>(d_in[4]));

  cudaLaunchConfig_t cfg = {};
  cfg.gridDim = dim3(nsm);
  cfg.blockDim = dim3(kNWG * 128);
  cfg.dynamicSmemBytes = kSmemBytes;
  cfg.stream = st;
  cudaLaunchAttribute at[1];
  at[0].id = cudaLaunchAttributeProgrammaticStreamSerialization;
  at[0].val.programmaticStreamSerializationAllowed = 1;
  cfg.attrs = at;
  cfg.numAttrs = 1;
  cudaLaunchKernelEx(&cfg, swin_main, tm, static_cast<uint8_t*>(d_out));
}
```

```cpp
#include <cuda_runtime.h>
#include <cuda.h>
#include <cuda_bf16.h>
#include <cuda_fp16.h>
#include <stdint.h>

namespace {

constexpr int kH = 511, kW = 511, kT = 4;
constexpr int kNWX = 73, kNWIN = 73 * 73;
constexpr int kChunk = 12544;
constexpr int kPlane = 3136;
constexpr int kXBytes = 37632;
constexpr int kBufStride = 38912;
constexpr int kWMat = 18432;
constexpr int kAtChunk = 200 * 64;
constexpr int kOffWt = 104 * 64;
constexpr int kOffAs = 3 * kAtChunk, kOffWs = kOffAs + kWMat;
constexpr int kWBytes = kOffWs + kWMat;
constexpr int kOffBuf = kWBytes;
constexpr int kOffBar = kOffBuf + 4 * kBufStride;
constexpr int kOffFlag = kOffBar + 96;
constexpr int kSmemBytes = kOffBar + 128;
constexpr int kNWG = 4;

struct Params {
  float cS_t, cS_s;
  float kt;
  float kappa;
  float kb;
};

__device__ uint4 g_wimg[kWBytes / 16];
__device__ __align__(16) Params g_par;
#define TR(i, k)

__device__ __forceinline__ uint32_t smem_u32(const void* p) { return (uint32_t)__cvta_generic_to_shared(p); }
__device__ __forceinline__ void mbar_init(uint32_t a, int c) { asm volatile("mbarrier.init.shared::cta.b64 [%0], %1;" ::"r"(a), "r"(c)); }
__device__ __forceinline__ void mbar_expect(uint32_t a, int bytes) {
  asm volatile("mbarrier.arrive.expect_tx.shared::cta.b64 _, [%0], %1;" ::"r"(a), "r"(bytes) : "memory");
}
__device__ __forceinline__ void mbar_arrive(uint32_t a) {
  asm volatile("mbarrier.arrive.shared::cta.b64 _, [%0];" ::"r"(a) : "memory");
}
__device__ __forceinline__ void mbar_wait(uint32_t a, uint32_t par) {
  asm volatile(
      "{\n.reg .pred p;\n.reg .u32 n;\n"
      "mbarrier.try_wait.parity.shared::cta.b64 p, [%0], %1;\n"
      "@p bra.uni WDONE;\n"
      "mov.u32 n, 0;\n"
      "WLOOP:\n"
      "mbarrier.try_wait.parity.shared::cta.b64 p, [%0], %1;\n"
      "@p bra.uni WDONE;\n"
      "add.u32 n, n, 1;\n"
      "setp.lt.u32 p, n, 0x1000000;\n"
      "@p bra.uni WLOOP;\n"
      "trap;\n"
      "WDONE:\n}" ::"r"(a), "r"(par) : "memory");
}
__device__ __forceinline__ void mbar_arrive_n(uint32_t a, uint32_t n, uint32_t doit) {
  asm volatile("{\n.reg .pred p;\nsetp.ne.u32 p, %2, 0;\n@p mbarrier.arrive.shared::cta.b64 _, [%0], %1;\n}" ::"r"(a), "r"(n), "r"(doit) : "memory");
}
__device__ __forceinline__ void tma_load_win(uint32_t dst, const CUtensorMap* m, uint32_t bar, uint32_t w) {
  const uint32_t wy = (w * 57457u) >> 22, wx = w - wy * kNWX;
  asm volatile(
      "cp.async.bulk.tensor.5d.shared::cluster.global.mbarrier::complete_tx::bytes [%0], [%1, {%3,%4,%5,%3,%3}], [%2];" ::"r"(dst),
      "l"(m), "r"(bar), "r"(0), "r"(wx * 7), "r"(wy * 7)
      : "memory");
}
__device__ __forceinline__ void tma_prefetch_win(const CUtensorMap* m, uint32_t w) {
  const uint32_t wy = (w * 57457u) >> 22, wx = w - wy * kNWX;
  asm volatile("cp.async.bulk.prefetch.tensor.5d.L2.global [%0, {%1,%2,%3,%1,%1}];" ::"l"(m), "r"(0), "r"(wx * 7), "r"(wy * 7) : "memory");
}
__device__ __forceinline__ void wg_fence() { asm volatile("wgmma.fence.sync.aligned;" ::: "memory"); }
__device__ __forceinline__ void wg_commit() { asm volatile("wgmma.commit_group.sync.aligned;" ::: "memory"); }
template <int N>
__device__ __forceinline__ void wg_wait() { asm volatile("wgmma.wait_group.sync.aligned %0;" ::"n"(N) : "memory"); }
template <int N>
__device__ __forceinline__ void pin(uint32_t* d) {
#pragma unroll
  for (int i = 0; i < N; i++) asm volatile("" : "+r"(d[i])::"memory");
}
__device__ __forceinline__ void sched_fence(uint32_t a, uint32_t b, uint32_t c) {
  asm volatile("{\n.reg .pred p;\n.reg .b32 t;\nsetp.ne.u32 p, %0, 0x7fffffff;\n@p bra.uni SFD;\n"
               "add.u32 t, %1, %2;\nadd.u32 t, t, %3;\nst.volatile.shared.b32 [t], t;\nSFD:\n}" ::"r"(gridDim.x), "r"(a), "r"(b), "r"(c) : "memory");
}
__host__ __device__ constexpr uint64_t mk_desc(uint32_t addr, uint32_t lbo16) {
  return ((uint64_t)0x80000020u << 32) | ((addr >> 4) & 0x3fff) | (lbo16 << 16);
}

#define R4(d, i) "+r"(d[i]), "+r"(d[i + 1]), "+r"(d[i + 2]), "+r"(d[i + 3])
#define O4(d, i) "=r"(d[i]), "=r"(d[i + 1]), "=r"(d[i + 2]), "=r"(d[i + 3])
#define D24 "{%0,%1,%2,%3,%4,%5,%6,%7,%8,%9,%10,%11,%12,%13,%14,%15,%16,%17,%18,%19,%20,%21,%22,%23},"
#define D14 "{%0,%1,%2,%3,%4,%5,%6,%7,%8,%9,%10,%11,%12,%13},"

template <int SC, int TB>
__device__ __forceinline__ void wg96h(uint32_t (&d)[24], const uint32_t* a, uint64_t db) {
  if (SC == 2)
    asm volatile("{\n.reg .pred p;\nsetp.eq.u32 p, %30, 0x7fffffff;\nwgmma.mma_async.sync.aligned.m64n96k16.f16.f16.f16 " D24 "{%24,%25,%26,%27}, %28, p, 1, 1, %29;\n}"
                 : R4(d, 0), R4(d, 4), R4(d, 8), R4(d, 12), R4(d, 16), R4(d, 20)
                 : "r"(a[0]), "r"(a[1]), "r"(a[2]), "r"(a[3]), "l"(db), "n"(TB), "r"(gridDim.x));
  else if (SC)
    asm volatile("wgmma.mma_async.sync.aligned.m64n96k16.f16.f16.f16 " D24 "{%24,%25,%26,%27}, %28, 1, 1, 1, %29;"
                 : R4(d, 0), R4(d, 4), R4(d, 8), R4(d, 12), R4(d, 16), R4(d, 20)
                 : "r"(a[0]), "r"(a[1]), "r"(a[2]), "r"(a[3]), "l"(db), "n"(TB));
  else
    asm volatile("wgmma.mma_async.sync.aligned.m64n96k16.f16.f16.f16 " D24 "{%24,%25,%26,%27}, %28, 0, 1, 1, %29;"
                 : O4(d, 0), O4(d, 4), O4(d, 8), O4(d, 12), O4(d, 16), O4(d, 20)
                 : "r"(a[0]), "r"(a[1]), "r"(a[2]), "r"(a[3]), "l"(db), "n"(TB));
}
template <int SC>
__device__ __forceinline__ void wg104h(uint32_t (&d)[26], const uint32_t* a, uint64_t db) {
  if (SC)
    asm volatile("wgmma.mma_async.sync.aligned.m64n104k16.f16.f16.f16 "
                 "{%0,%1,%2,%3,%4,%5,%6,%7,%8,%9,%10,%11,%12,%13,%14,%15,%16,%17,%18,%19,%20,%21,%22,%23,%24,%25},"
                 "{%26,%27,%28,%29}, %30, 1, 1, 1, 0;"
                 : R4(d, 0), R4(d, 4), R4(d, 8), R4(d, 12), R4(d, 16), R4(d, 20), "+r"(d[24]), "+r"(d[25])
                 : "r"(a[0]), "r"(a[1]), "r"(a[2]), "r"(a[3]), "l"(db));
  else
    asm volatile("wgmma.mma_async.sync.aligned.m64n104k16.f16.f16.f16 "
                 "{%0,%1,%2,%3,%4,%5,%6,%7,%8,%9,%10,%11,%12,%13,%14,%15,%16,%17,%18,%19,%20,%21,%22,%23,%24,%25},"
                 "{%26,%27,%28,%29}, %30, 0, 1, 1, 0;"
                 : O4(d, 0), O4(d, 4), O4(d, 8), O4(d, 12), O4(d, 16), O4(d, 20), "=r"(d[24]), "=r"(d[25])
                 : "r"(a[0]), "r"(a[1]), "r"(a[2]), "r"(a[3]), "l"(db));
}
template <int SC>
__device__ __forceinline__ void wg56h(uint32_t (&d)[16], const uint32_t* a, uint64_t db) {
  if (SC)
    asm volatile("wgmma.mma_async.sync.aligned.m64n56k16.f16.f16.f16 " D14 "{%14,%15,%16,%17}, %18, 1, 1, 1, 0;"
                 : R4(d, 0), R4(d, 4), R4(d, 8), "+r"(d[12]), "+r"(d[13])
                 : "r"(a[0]), "r"(a[1]), "r"(a[2]), "r"(a[3]), "l"(db));
  else
    asm volatile("wgmma.mma_async.sync.aligned.m64n56k16.f16.f16.f16 " D14 "{%14,%15,%16,%17}, %18, 0, 1, 1, 0;"
                 : O4(d, 0), O4(d, 4), O4(d, 8), "=r"(d[12]), "=r"(d[13])
                 : "r"(a[0]), "r"(a[1]), "r"(a[2]), "r"(a[3]), "l"(db));
}
template <int SC, int CH = 384>
__device__ __forceinline__ void gemm_w(uint32_t (&d)[24], const uint32_t* a, uint64_t dw) {
  asm volatile("" : "+l"(dw));
  wg_fence();
  wg96h<SC, 0>(d, a, dw); wg96h<1, 0>(d, a + 4, dw + 2);
  wg96h<1, 0>(d, a + 8, dw + CH); wg96h<1, 0>(d, a + 12, dw + CH + 2);
  wg96h<1, 0>(d, a + 16, dw + 2 * CH); wg96h<1, 0>(d, a + 20, dw + 2 * CH + 2);
  wg_commit();
}
__device__ __forceinline__ void lds128(uint32_t* r, uint32_t a) {
  asm volatile("ld.shared.v4.b32 {%0,%1,%2,%3}, [%4];" : "=r"(r[0]), "=r"(r[1]), "=r"(r[2]), "=r"(r[3]) : "r"(a) : "memory");
}
__device__ __forceinline__ void ldsm4(uint32_t* r, uint32_t a) {
  asm volatile("ldmatrix.sync.aligned.m8n8.x4.shared.b16 {%0,%1,%2,%3}, [%4];"
               : "=r"(r[0]), "=r"(r[1]), "=r"(r[2]), "=r"(r[3]) : "r"(a) : "memory");
}
__device__ __forceinline__ void stsm4(uint32_t a, const uint32_t* r) {
  asm volatile("stmatrix.sync.aligned.m8n8.x4.shared.b16 [%0], {%1,%2,%3,%4};" ::"r"(a), "r"(r[0]), "r"(r[1]), "r"(r[2]), "r"(r[3])
               : "memory");
}
__device__ __forceinline__ uint32_t pack_h2(float lo, float hi) {
  uint32_t r; asm("cvt.rn.f16x2.f32 %0, %1, %2;" : "=r"(r) : "f"(hi), "f"(lo)); return r;
}
__device__ __forceinline__ uint32_t pack_h2_sat(float lo, float hi) {
  uint32_t r; asm("cvt.rn.satfinite.f16x2.f32 %0, %1, %2;" : "=r"(r) : "f"(hi), "f"(lo)); return r;
}
__device__ __forceinline__ uint32_t pack_bf2(float lo, float hi) {
  uint32_t r; asm("cvt.rn.bf16x2.f32 %0, %1, %2;" : "=r"(r) : "f"(hi), "f"(lo)); return r;
}
__device__ __forceinline__ __half2 as_h2(uint32_t v) { return *reinterpret_cast<__half2*>(&v); }
__device__ __forceinline__ uint32_t as_u(__half2 v) { return *reinterpret_cast<uint32_t*>(&v); }
__device__ __forceinline__ float2 unpack_h2(uint32_t v) { return __half22float2(as_h2(v)); }
__device__ __forceinline__ uint32_t h2ex2(uint32_t v) { uint32_t r; asm("ex2.approx.f16x2 %0, %1;" : "=r"(r) : "r"(v)); return r; }
__device__ __forceinline__ uint32_t h2max(uint32_t a, uint32_t b) { return as_u(__hmax2(as_h2(a), as_h2(b))); }
__device__ __forceinline__ uint32_t h2add(uint32_t a, uint32_t b) { return as_u(__hadd2(as_h2(a), as_h2(b))); }
__device__ __forceinline__ uint32_t h2sub(uint32_t a, uint32_t b) { return as_u(__hsub2(as_h2(a), as_h2(b))); }
__device__ __forceinline__ uint32_t h2mul(uint32_t a, uint32_t b) { return as_u(__hmul2(as_h2(a), as_h2(b))); }
__device__ __forceinline__ uint32_t h2fma(uint32_t a, uint32_t b, uint32_t c) { return as_u(__hfma2(as_h2(a), as_h2(b), as_h2(c))); }
__device__ __forceinline__ uint32_t lo2(uint32_t v) { return as_u(__low2half2(as_h2(v))); }
__device__ __forceinline__ uint32_t hi2(uint32_t v) { return as_u(__high2half2(as_h2(v))); }
__device__ __forceinline__ uint32_t fold_add(uint32_t a, uint32_t b) { return h2add(__byte_perm(a, b, 0x5410), __byte_perm(a, b, 0x7632)); }
__device__ __forceinline__ uint32_t bitsel(uint32_t a, uint32_t m, uint32_t c) {
  uint32_t r; asm("lop3.b32 %0, %1, %2, %3, 0xe2;" : "=r"(r) : "r"(a), "r"(m), "r"(c)); return r;
}
__device__ __forceinline__ uint32_t sel(bool p, uint32_t a, uint32_t b) {
  uint32_t r; asm("{\n.reg .pred p;\nsetp.ne.u32 p, %3, 0;\nselp.b32 %0, %1, %2, p;\n}" : "=r"(r) : "r"(a), "r"(b), "r"((uint32_t)p)); return r;
}
__device__ __forceinline__ float sel4(bool odd, bool up, float a, float b, float c, float d) {
  return __uint_as_float(sel(up, sel(odd, __float_as_uint(d), __float_as_uint(c)), sel(odd, __float_as_uint(b), __float_as_uint(a))));
}
__device__ __forceinline__ float rcp_fast(float v) { float r; asm("rcp.approx.ftz.f32 %0, %1;" : "=f"(r) : "f"(v)); return r; }
__device__ __forceinline__ float rsq_fast(float v) { float r; asm("rsqrt.approx.ftz.f32 %0, %1;" : "=f"(r) : "f"(v)); return r; }
__device__ __forceinline__ float quad_sum(float v) {
  v += __shfl_xor_sync(0xffffffffu, v, 1);
  return v + __shfl_xor_sync(0xffffffffu, v, 2);
}
__device__ __forceinline__ uint32_t quad_h2add(uint32_t v) {
  v = h2add(v, __shfl_xor_sync(0xffffffffu, v, 1));
  return h2add(v, __shfl_xor_sync(0xffffffffu, v, 2));
}
__device__ __forceinline__ uint32_t score_scale(const float* p) { const float v = __ldcg(p); return pack_h2(v, v); }

constexpr float kEps96 = 1e-5f * 96.f * 96.f;
__device__ __forceinline__ float2 stat_f32(uint32_t e) {
  const float2 h = unpack_h2(e);
  const bool w = e & 0x8000u;
  return make_float2(__uint_as_float(sel(w, (e << 16) & 0x7fff0000u, __float_as_uint(h.x))), __uint_as_float(sel(w, e & 0xffff0000u, __float_as_uint(h.y))));
}
__device__ __forceinline__ void stg3(uint8_t* p, const uint32_t* r, uint32_t off) {
  asm volatile("{\n.reg .pred p;\nsetp.eq.u32 p, %13, 0;\n@p st.global.v4.b32 [%0], {%1,%2,%3,%4};\n"
               "@p st.global.v4.b32 [%0+64], {%5,%6,%7,%8};\n@p st.global.v4.b32 [%0+128], {%9,%10,%11,%12};\n}" ::"l"(p),
               "r"(r[0]), "r"(r[1]), "r"(r[2]), "r"(r[3]), "r"(r[4]), "r"(r[5]), "r"(r[6]), "r"(r[7]), "r"(r[8]), "r"(r[9]), "r"(r[10]), "r"(r[11]),
               "r"(off) : "memory");
}
__device__ __forceinline__ uint32_t mbar_test(uint32_t a, uint32_t par) {
  uint32_t r;
  asm volatile("{\n.reg .pred p;\nmbarrier.test_wait.parity.shared::cta.b64 p, [%1], %2;\nselp.b32 %0, 1, 0, p;\n}" : "=r"(r) : "r"(a), "r"(par) : "memory");
  return r;
}
template <int N>
__device__ __forceinline__ void launder(uint32_t* q) {
#pragma unroll
  for (int j = 0; j < N; j++) { uint32_t t; asm volatile("mov.b32 %0, %1;" : "=r"(t) : "r"(q[j])); q[j] = t; }
}

#define LB 512
#define LAU 1
#define NOWIDE 0
#define LAV 4
#define X 0
#define SMODE 2
#define RT 128
#define TM 0
#define TROLE 0
#define SF 0
__device__ __forceinline__ void sfence(uint32_t& v) {
  asm volatile("{\n.reg .pred p;\nsetp.eq.u32 p, %1, 0x7fffffff;\n@p mov.u32 %0, %%clock;\n}" : "+r"(v) : "r"(gridDim.x) : "memory");
}
#define sf() sfence(tid)
#define FG(m, b) do { if ((m) & (b)) sf(); } while (0)
__device__ __forceinline__ uint32_t fresh(uint32_t v) { asm volatile("" : "+r"(v)); return v; }
#define V1 1
#define EA 1
#define CB 0
#define ET 1
#define HELP 3
#define PRE 2
#define RB 1
#define QS 2
#define A7 0
#define TW 1
#define SE 1
#define MG 1
#define XL 2
#define PF 2
#define MX 1
#define TRN 0
#define FEN 0
#define CV 1
#define RG 1
#define O1 0
#define O7 0
#define XS 0
#define XA 0
#define SP 0
#define S1 4
#define S2 3
#define NA 4
#define NB 4
#define LR 0
#define SG 2
#define G1 0
#define GT 255
#define HT 255
#define GS 232
#define HS 255
__device__ __forceinline__ void gemm_at(uint32_t (&d)[26], const uint32_t* a, uint64_t da) {
  asm volatile("" : "+l"(da));
  wg_fence();
  wg104h<0>(d, a, da); wg104h<1>(d, a + 4, da + 2);
  wg104h<1>(d, a + 8, da + 800); wg104h<1>(d, a + 12, da + 802);
  wg104h<1>(d, a + 16, da + 1600); wg104h<1>(d, a + 20, da + 1602);
  wg_commit();
}
template <int ND, class W>
__device__ __forceinline__ void gemm_spread(uint32_t (&d)[ND], const uint32_t* a, uint64_t da, uint32_t& tid, W work) {
  asm volatile("" : "+l"(da));
  wg_fence();
#pragma unroll
  for (int k = 0; k < 6; k++) {
    const uint64_t dk = da + (k >> 1) * 800 + (k & 1) * 2;
    if constexpr (ND == 26) { if (k) wg104h<1>(d, a + 4 * k, dk); else wg104h<0>(d, a, dk); }
    else { if (k) wg96h<1, 0>(d, a + 4 * k, dk); else wg96h<0, 0>(d, a, dk); }
    if (k == 5) wg_commit();
    work(k);
    if (k < 5) sf();
  }
}
__device__ __forceinline__ void load_rows(uint32_t* x0, uint32_t* x1, uint32_t a0, uint32_t a1) {
  a0 ^= (a0 >> 3) & 0x30; a1 ^= (a1 >> 3) & 0x30;
  lds128(x0, a0); lds128(x1, a1);
  lds128(x0 + 4, (a0 ^ 32) + kChunk); lds128(x1 + 4, (a1 ^ 32) + kChunk);
  lds128(x0 + 8, a0 + 2 * kChunk); lds128(x1 + 8, a1 + 2 * kChunk);
}
__device__ __forceinline__ uint32_t sumsq2(const uint32_t* z) {
  uint32_t q0, q1;
#pragma unroll
  for (int j = 0; j < 12; j++) {
    const uint32_t u = z[2 * j], v = z[2 * j + 1];
    q0 = j ? h2fma(u, u, q0) : h2mul(u, u); q1 = j ? h2fma(v, v, q1) : h2mul(v, v);
  }
  return fold_add(q0, q1);
}
__device__ __forceinline__ void to_half(uint32_t (&z)[24], const uint32_t* x, int j0 = 0, int j1 = 24) {
#pragma unroll
  for (int j = 0; j < 24; j += 2) {
    if (j < j0 || j >= j1) continue;
    const int o = j < 12 ? 2 * j : 2 * j - 23;
    if (CV) {
      uint32_t t;
      asm("cvt.rz.f16x2.f32 %0, %1, %2;" : "=r"(t) : "f"(__uint_as_float(x[j + 1])), "f"(__uint_as_float(x[j])));
      z[o] = pack_h2(__uint_as_float(x[j] << 16), __uint_as_float(x[j + 1] << 16));
      z[o + 2] = t & 0xfff8fff8u;
      pin<1>(z + o); pin<1>(z + o + 2);
    } else {
      z[o] = pack_h2(__uint_as_float(x[j] << 16), __uint_as_float(x[j + 1] << 16));
      z[o + 2] = pack_h2(__uint_as_float(x[j] & 0xffff0000u), __uint_as_float(x[j + 1] & 0xffff0000u));
    }
  }
}
__device__ __forceinline__ void load_general(uint32_t (&z)[24], uint32_t a0, float& ie0, float& ie1, float& m0, float& m1) {
  float acc[48];
  uint32_t x0[12], x1[12];
  load_rows(x0, x1, a0, a0 + kPlane);
#pragma unroll
  for (int j = 0; j < 12; j++) {
    acc[4 * j] = __uint_as_float(x0[j] << 16); acc[4 * j + 1] = __uint_as_float(x0[j] & 0xffff0000u);
    acc[4 * j + 2] = __uint_as_float(x1[j] << 16); acc[4 * j + 3] = __uint_as_float(x1[j] & 0xffff0000u);
  }
  float s[4], q[4];
#pragma unroll
  for (int e = 0; e < 4; e++) { s[e] = acc[e]; q[e] = acc[e] * acc[e]; }
#pragma unroll
  for (int j = 4; j < 48; j++) { s[j & 3] += acc[j]; q[j & 3] = fmaf(acc[j], acc[j], q[j & 3]); }
  const float s0 = quad_sum(s[0] + s[1]), s1 = quad_sum(s[2] + s[3]), q0 = quad_sum(q[0] + q[1]), q1 = quad_sum(q[2] + q[3]);
  const float u0 = rsq_fast(fmaxf(fmaf(-s0, s0, fmaf(q0, 96.f, kEps96)), kEps96));
  const float u1 = rsq_fast(fmaxf(fmaf(-s1, s1, fmaf(q1, 96.f, kEps96)), kEps96));
  const float n0 = -s0 * u0, n1 = -s1 * u1;
  ie0 = 96.f * u0; ie1 = 96.f * u1;
  m0 = s0 * (1.f / 96.f); m1 = s1 * (1.f / 96.f);
#pragma unroll
  for (int j = 0; j < 12; j++) {
    const int o = 8 * (j >> 1) + (j & 1);
    z[2 * j] = pack_h2(fmaf(acc[o], ie0, n0), fmaf(acc[o + 4], ie0, n0));
    z[2 * j + 1] = pack_h2(fmaf(acc[o + 2], ie1, n1), fmaf(acc[o + 6], ie1, n1));
  }
}
__device__ __forceinline__ float2 sumsq2f(const uint32_t* z) {
  float2 r = make_float2(0.f, 0.f);
#pragma unroll
  for (int j = 0; j < 12; j++) {
    const float2 u = unpack_h2(z[2 * j]), v = unpack_h2(z[2 * j + 1]);
    r.x = fmaf(u.x, u.x, fmaf(u.y, u.y, r.x)); r.y = fmaf(v.x, v.x, fmaf(v.y, v.y, r.y));
  }
  return make_float2(quad_sum(r.x), quad_sum(r.y));
}
__device__ __forceinline__ uint32_t quad_scatter(uint32_t a, uint32_t b, bool up) {
  const uint32_t t = h2add(sel(up, b, a), __shfl_xor_sync(0xffffffffu, sel(up, a, b), 2));
  return h2add(t, __shfl_xor_sync(0xffffffffu, t, 1));
}
__device__ __forceinline__ void scores_part(uint32_t* d, int j0, int j1, const uint32_t* q, const uint32_t* z0, const uint32_t* z1) {
#pragma unroll
  for (int j = 0; j < 12; j++) {
    if (j < j0 || j >= j1) continue;
    const uint32_t kk[4] = {z0[2 * j], z0[2 * j + 1], z1[2 * j], z1[2 * j + 1]};
#pragma unroll
    for (int e = 0; e < 4; e++) {
      d[e] = j ? h2fma(q[2 * j], kk[e], d[e]) : h2mul(q[2 * j], kk[e]);
      d[4 + e] = j ? h2fma(q[2 * j + 1], kk[e], d[4 + e]) : h2mul(q[2 * j + 1], kk[e]);
    }
  }
  if (j1 > j0) pin<8>(d);
}
__device__ __forceinline__ void scores_fold(uint32_t* f, const uint32_t* d) {
#pragma unroll
  for (int e = 0; e < 4; e++) f[e] = fold_add(d[2 * e], d[2 * e + 1]);
}
__device__ __forceinline__ void scores2(const uint32_t* q, const uint32_t* z0, const uint32_t* z1, uint32_t* f) {
  uint32_t d[8];
  scores_part(d, 0, 12, q, z0, z1);
  scores_fold(f, d);
}
__device__ __forceinline__ void pair_scatter(uint32_t* k, const uint32_t* a, const uint32_t* b, bool up, int m) {
#pragma unroll
  for (int e = 0; e < 2; e++) k[e] = h2add(sel(up, b[e], a[e]), __shfl_xor_sync(0xffffffffu, sel(up, a[e], b[e]), m));
}
struct Xch { uint32_t keep[2], got[2]; };
__device__ __forceinline__ Xch pair_send(const uint32_t* a, const uint32_t* b, bool up, int m) {
  Xch x;
#pragma unroll
  for (int e = 0; e < 2; e++) { x.keep[e] = fresh(sel(up, b[e], a[e])); x.got[e] = __shfl_xor_sync(0xffffffffu, sel(up, a[e], b[e]), m); }
  return x;
}
__device__ __forceinline__ void pair_recv(uint32_t* k, const Xch& x) { k[0] = h2add(x.keep[0], x.got[0]); k[1] = h2add(x.keep[1], x.got[1]); }
__device__ __forceinline__ void mix2(uint32_t* y, const uint32_t* v, uint32_t c0, uint32_t c1) {
#pragma unroll
  for (int j = 0; j < 12; j++) {
    y[2 * j] = h2fma(v[2 * j + 1], hi2(c0), h2fma(v[2 * j], lo2(c0), y[2 * j]));
    y[2 * j + 1] = h2fma(v[2 * j + 1], hi2(c1), h2fma(v[2 * j], lo2(c1), y[2 * j + 1]));
  }
}
__device__ __forceinline__ void norm_store(uint32_t* y, uint32_t r0, uint32_t r1, uint32_t ma) {
#pragma unroll
  for (int j = 0; j < 12; j++) { y[2 * j] = h2fma(y[2 * j], lo2(r0), hi2(r0)); y[2 * j + 1] = h2fma(y[2 * j + 1], lo2(r1), hi2(r1)); }
  ma ^= (ma >> 3) & 0x30;
  const uint32_t mb = ma ^ 32;
  stsm4(ma, y); stsm4(mb, y + 4);
  stsm4(mb + kChunk, y + 8); stsm4(ma + kChunk, y + 12);
  stsm4(ma + 2 * kChunk, y + 16); stsm4(mb + 2 * kChunk, y + 20);
}

template <bool kDirect>
__device__ __forceinline__ bool temporal(uint64_t da, uint32_t bufA, uint32_t dB, int ow, int live, const Params& P, bool scaled, uint32_t flag, uint32_t gate, uint32_t& tid) {
  uint32_t lane = tid & 31;
  const bool odd = lane & 1, up = lane & 2;
  uint32_t a0 = bufA + ow * 64 + lane * 16 + ((int)(lane >> 2) >= 49 - ow ? dB - kPlane : 0);
  const uint64_t dv = da + (kOffWt >> 4);
  uint32_t z0[24], z1[24], q0[26], q1[24], v0[24], w1[26], nn = 0, ng = 0, ca0 = 0, ca1 = 0;
  uint32_t* const v1 = w1 + 2;
  float ie = 1.f, mm = 0.f;
  bool tiny = false;
  if (kDirect) {
    uint32_t x[48];
    load_rows(x, x + 12, a0, a0 + kPlane);
    if (ET) { load_rows(x + 24, x + 36, a0 + 2 * kPlane, a0 + 3 * kPlane); sf(); }
    to_half(z0, x);
    if (SP & 1) gemm_spread(q0, z0, da, tid, [&](int k) { to_half(z1, x + 24, S1 * k, k < 5 ? S1 * k + S1 : 24); });
    else { gemm_at(q0, z0, da); FG(GT, 1); to_half(z1, x + 24); }
    const uint32_t n0 = sumsq2(z0), n1 = sumsq2(z1);
    nn = fresh(sel(up, n1, n0)); ng = __shfl_xor_sync(0xffffffffu, sel(up, n0, n1), 2);
    pin<24>(z1); FG(HT, 1);
  } else {
    float e[4], m[4];
    load_general(z0, a0, e[0], e[1], m[0], m[1]);
    pin<24>(z0); sf();
    load_general(z1, a0 + 2 * kPlane, e[2], e[3], m[2], m[3]);
    tiny = __any_sync(0xffffffffu, fmaxf(fmaxf(e[0], e[1]), fmaxf(e[2], e[3])) * P.kt > 400.f);
    if (tiny) {
      const float2 u = sumsq2f(z0), w = sumsq2f(z1);
      const float ik = 9.8f * rsq_fast(fmaxf(fmaxf(fmaxf(u.x, u.y), fmaxf(w.x, w.y)), 2e-7f)) * rcp_fast(__uint_as_float(fresh(__float_as_uint(P.kt))));
      ca0 = pack_h2(__fdividef(fminf(e[0], ik), e[0]), __fdividef(fminf(e[1], ik), e[1]));
      ca1 = pack_h2(__fdividef(fminf(e[2], ik), e[2]), __fdividef(fminf(e[3], ik), e[3]));
#pragma unroll
      for (int j = 0; j < 4; j++) e[j] = fminf(e[j], ik);
    }
    ie = sel4(odd, up, e[0], e[1], e[2], e[3]);
    mm = sel4(odd, up, m[0], m[1], m[2], m[3]);
    gemm_at(q0, z0, da);
  }
  uint32_t f[4], k0[2], k1[2], sk[2];
  wg_wait<0>(); pin<26>(q0);
  if (SG == 1) mbar_arrive_n(gate, 1, gate && (tid & 127) == 0);
  uint32_t dd[8];
  if (kDirect && (SP & 2)) {
    gemm_spread(q1, z1, da, tid, [&](int k) {
      if (k == 1) { nn = h2add(nn, ng); ng = __shfl_xor_sync(0xffffffffu, nn, 1); }
      scores_part(dd, S2 * k / 2, k < 5 ? S2 * (k + 1) / 2 : 12, q0, z0, z1);
    });
    scores_fold(f, dd);
  } else {
    gemm_w<0, 800>(q1, z1, da);
    FG(GT, 2);
    if (kDirect) { nn = h2add(nn, ng); ng = __shfl_xor_sync(0xffffffffu, nn, 1); FG(GT, 16); }
    scores2(q0, z0, z1, f);
  }
  const uint32_t nu0 = fresh(__byte_perm(q0[24], q0[25], 0x7632)), mp0 = fresh(__byte_perm(q0[24], q0[25], 0x5410));
  Xch xc = pair_send(f, f + 2, odd, 1);
  sf();
  wg_wait<0>(); pin<24>(q1);
  if (SG == 2) mbar_arrive_n(gate, 1, gate && (tid & 127) == 0);
  float e2 = 0.f;
  if (kDirect && (SP & 4)) {
    gemm_spread(w1, z1, dv - 32, tid, [&](int k) {
      if (k == 2) { pair_recv(k0, xc); pin<2>(k0); }
      scores_part(dd, S2 * k / 2, k < 5 ? S2 * (k + 1) / 2 : 12, q1, z0, z1);
    });
    scores_fold(f, dd);
  } else {
    gemm_at(w1, z1, dv - 32);
    FG(GT, 4);
    pair_recv(k0, xc);
    scores2(q1, z0, z1, f);
  }
  if (kDirect) e2 = fmaf(__low2float(as_h2(__byte_perm(h2add(nn, ng), 0, odd ? 0x3232 : 0x1010))), 1.f / 96.f, 1e-5f);
  e2 = __uint_as_float(fresh(__float_as_uint(e2)));
  xc = pair_send(f, f + 2, odd, 1);
  pin<2>(k0); sf();
  wg_wait<0>(); pin<26>(w1);
  if (SG == 3) mbar_arrive_n(gate, 1, gate && (tid & 127) == 0);
  uint32_t rc = 0, r0 = 0, r1 = 0;
  float mz = 0.f, d2 = 0.f;
  if (kDirect) {
    mz = __low2float(as_h2(sel(up, sel(odd, w1[1], w1[0]), __byte_perm(mp0, 0, odd ? 0x3232 : 0x1010))));
    d2 = fmaf(-mz, mz, e2);
    const bool fine = (d2 >= fmaxf(0.5f * e2, 4e-4f)) & (e2 <= 4.f);
    asm volatile("{\n.reg .pred p;\nsetp.ne.u32 p, %1, 0;\n@p st.volatile.shared.b32 [%0], %1;\n}" ::"r"(flag),
                 "r"((uint32_t)(!fine & ((int)(tid & 31) < 4 * live))) : "memory");
  }
  gemm_w<0, 800>(v0, z0, dv);
  FG(GT, 8);
  const uint32_t nu1 = __byte_perm(w1[0], w1[1], 0x7632);
  if (kDirect) {
    const float r = rsq_fast(d2);
    rc = pack_h2(r, r);
    if (RG) {
      r0 = __byte_perm(__shfl_sync(0xffffffffu, rc, 0, 4), __shfl_sync(0xffffffffu, rc, 1, 4), 0x5410);
      r1 = __byte_perm(__shfl_sync(0xffffffffu, rc, 2, 4), __shfl_sync(0xffffffffu, rc, 3, 4), 0x5410);
    } else {
      const uint32_t p = __byte_perm(rc, __shfl_xor_sync(0xffffffffu, rc, 1), odd ? 0x1054 : 0x5410);
      const uint32_t o = __shfl_xor_sync(0xffffffffu, p, 2);
      r0 = sel(up, o, p); r1 = sel(up, p, o);
    }
  }
  pair_recv(k1, xc);
  pair_scatter(sk, k0, k1, up, 2);
  uint32_t cw[8], mu;
  {
    if (kDirect) { sk[0] = h2mul(sk[0], r0); sk[1] = h2mul(sk[1], r1); }
    uint32_t mx = h2max(sk[0], sk[1]);
    mx = h2max(lo2(mx), hi2(mx));
    if (kDirect) {
      const uint32_t nm = h2mul(mx, rc) ^ 0x80008000u;
      sk[0] = h2fma(sk[0], rc, nm); sk[1] = h2fma(sk[1], rc, nm);
    } else {
      sk[0] = h2sub(sk[0], mx); sk[1] = h2sub(sk[1], mx);
      if (scaled) {
        const uint32_t cs = score_scale(&g_par.cS_t);
        sk[0] = h2mul(sk[0], cs); sk[1] = h2mul(sk[1], cs);
      }
    }
    sk[0] = h2ex2(sk[0]); sk[1] = h2ex2(sk[1]);
    const float2 sf = unpack_h2(h2add(sk[0], sk[1]));
    const float iv = (kDirect ? P.kt : P.kt * ie) * rcp_fast(sf.x + sf.y);
    const uint32_t inv = pack_h2(iv, iv);
    sk[0] = h2mul(sk[0], inv); sk[1] = h2mul(sk[1], inv);
    if (kDirect) { sk[0] = h2mul(sk[0], r0); sk[1] = h2mul(sk[1], r1); }
#pragma unroll
    for (int i = 0; i < 4; i++) { cw[2 * i] = __shfl_sync(0xffffffffu, sk[0], i, 4); cw[2 * i + 1] = __shfl_sync(0xffffffffu, sk[1], i, 4); }
    mu = h2fma(sk[1], nu1, h2mul(sk[0], nu0));
  }
  uint32_t bad = 0;
  if (kDirect) {
    mix2(z1, v1, cw[5], cw[7]);
    pin<24>(z1); FG(HT, 8);
    wg_wait<0>(); pin<24>(v0);
    asm volatile("ld.shared.b32 %0, [%1];" : "=r"(bad) : "r"(flag + (v0[0] & (gridDim.x == 0x7fffffffu))) : "memory");
  } else {
    wg_wait<0>(); pin<24>(v0);
    if (tiny) {
#pragma unroll
      for (int j = 0; j < 12; j++) {
        z0[2 * j] = h2mul(z0[2 * j], lo2(ca0)); z0[2 * j + 1] = h2mul(z0[2 * j + 1], hi2(ca0));
        z1[2 * j] = h2mul(z1[2 * j], lo2(ca1)); z1[2 * j + 1] = h2mul(z1[2 * j + 1], hi2(ca1));
      }
    }
    mix2(z1, v1, cw[5], cw[7]);
  }
  mix2(z1, v0, cw[4], cw[6]);
  if (MX & 1) { pin<24>(z1); sf(); }
  mix2(z0, v1, cw[1], cw[3]);
  if (MX & 2) { pin<24>(z0); sf(); }
  mix2(z0, v0, cw[0], cw[2]);
  if (MX & 4) { pin<24>(z0); sf(); }
  const uint32_t t2 = quad_scatter(sumsq2(z0), sumsq2(z1), up);
  float qq = __low2float(as_h2(__byte_perm(t2, t2, odd ? 0x7632 : 0x5410)));
  if (__any_sync(0xffffffffu, (!(qq < 65000.f) & ((int)(tid & 31) < 4 * live)) | (bad != 0))) {
    if (kDirect && __any_sync(0xffffffffu, bad != 0)) return false;
    const float2 u = sumsq2f(z0), w = sumsq2f(z1);
    qq = sel4(odd, up, u.x, u.y, w.x, w.y);
  }
  const float rf = kDirect ? rsq_fast(fmaxf(fmaf(-mz, mz, fmaf(qq, 1.f / 96.f, 1e-5f)), 1e-5f)) : rsq_fast(fmaf(qq, 1.f / 96.f, 1e-5f * ie * ie));
  const uint32_t rn = pack_h2_sat(rf, -mz * rf);
  uint32_t rr[4];
#pragma unroll
  for (int i = 0; i < 4; i++) rr[i] = __shfl_sync(0xffffffffu, rn, i, 4);
  lane = tid & 31;
  const uint32_t ma = bufA + ow * 64 + (lane & 7) * 64 + (lane & 8) * (kPlane / 8) + (lane & 16) + ((int)(lane & 7) >= 49 - ow ? dB - kPlane : 0);
  norm_store(z0, rr[0], rr[1], ma);
  norm_store(z1, rr[2], rr[3], ma + 2 * kPlane);
  const float2 rm = unpack_h2(rn), mf = unpack_h2(mu);
  const float sg = rcp_fast(kDirect ? rm.x : rm.x * ie);
  mm = kDirect ? fmaf(-rm.y, sg, mf.x + mf.y) : fmaf((mf.x + mf.y) * rm.x, sg, mm);
  const float kap = __uint_as_float(fresh(__float_as_uint(P.kb)));
  const bool ok = (sg >= fmaxf(0.0045f, kap * 0.011f)) & (fmaf(sg, 9.8f, fabsf(mm)) < fmaf(kap, -627.2f, 60000.f));
  const uint32_t sa = bufA + kXBytes + ow * 4 + (lane & 0x1c) + (lane & 3) * 196 + ((int)(lane >> 2) >= 49 - ow ? dB - 196 : 0);
  asm volatile("st.shared.b32 [%0], %1;" ::"r"(sa), "r"(sel(ok, pack_h2(sg, mm), pack_bf2(-sg, mm))) : "memory");
  return true;
}

__device__ __forceinline__ void run_T(uint32_t sb, uint64_t d0, int nw, uint32_t pbeg, uint32_t pend, int tg, int wp, uint32_t tid, const Params& P, bool scaled, bool direct) {
  const uint32_t flag = sb + kOffFlag + tg * 4;
  const uint32_t barF = sb + kOffBar, barD = sb + kOffBar + 32;
  pend += 8 * wp;
  for (uint32_t p0 = pbeg + 8 * wp; p0 < pend;) {
    const uint32_t iw = (p0 * 21400u) >> 20;
    const int ow = p0 - 49 * iw;
    const uint32_t ia = iw & 3, ib = (iw + 1) & 3;
    const bool strad = ow > 41;
    const uint32_t bufA = sb + kOffBuf + ia * kBufStride, dB = (ib - ia) * kBufStride;
    if (wp == 3) TR(p0 >> 5, 1);
    mbar_wait(barF + ia * 8, (iw >> 2) & 1);
    if (strad) mbar_wait(barF + ib * 8, ((iw + 1) >> 2) & 1);
    const uint32_t gate = p0 >= 64 ? sb + kOffBar + 64 + ((p0 >> 2) & 8) : 0;
    if (SG && p0 >= 96 && (!G1 || wp == 0)) mbar_wait(gate ^ 8, ((p0 - 96) >> 6) & 1);
    if (wp == 3) TR(p0 >> 5, 2);
    bool done = false;
    if (direct) done = temporal<true>(d0, bufA, dB, ow, 49 * nw - p0, P, false, flag, gate, tid);
    if (!done) {
      if (direct) {
        asm volatile("barrier.cta.sync.aligned %0, 128;" ::"r"(tg + 1) : "memory");
        asm volatile("st.shared.b32 [%0], %1;\nfence.acq_rel.cta;" ::"r"(flag), "r"(0) : "memory");
      }
      temporal<false>(d0, bufA, dB, ow, 49 * nw - p0, P, scaled, flag, direct ? 0u : gate, tid);
    }
    if (!FEN) asm volatile("fence.proxy.async.shared::cta;" ::: "memory");
    __syncwarp();
    const bool l0 = (tid & 31) == 0;
    mbar_arrive_n(barD + ia * 8, strad ? 49 - ow : 8, l0);
    mbar_arrive_n(barD + ib * 8, ow - 41, l0 && strad);
    __syncwarp();
    if (wp == 3) TR(p0 >> 5, 3);
    p0 = __shfl_sync(0xffffffffu, p0 + 64, 0);
  }
}

struct Frame {
  bool light;
  uint32_t sta;
  uint32_t oo;
  uint32_t e0, e1;
};
__device__ __forceinline__ uint32_t frame_init(Frame& F, uint32_t t, int wp, int lane) {
  wp = (wp + t) & 3;
  F.light = wp == 3;
  F.sta = kXBytes + (49 * t + 16 * wp) * 4;
  const uint32_t r = 16 * wp + (lane >> 2);
  F.oo = ((r / 7) * (kW - 7) + r) * 12u + (lane & 3) + (((((r + 8) / 7 - r / 7) * (kW - 7) + 8) * 12u) << 16);
  F.e0 = F.e1 = 0x8000u;
  const uint32_t am = t * kPlane + wp * 1024 + ((lane * 65) & 0x3d0);
  return F.light && (lane & 15) ? kXBytes + 896 : am ^ ((am >> 3) & 0x30);
}
__device__ __forceinline__ uint32_t is_wide(const Frame& F) { return __ballot_sync(0xffffffffu, (F.e0 | F.e1) & 0x8000u); }
__device__ __forceinline__ void load_frame(uint32_t (&v)[24], uint32_t ma, uint32_t buf) {
  const uint32_t st = ma < kXBytes ? kChunk : 0, mb = ma ^ 32;
  ldsm4(v, buf + ma); ldsm4(v + 4, buf + mb);
  ldsm4(v + 8, buf + (mb + st)); ldsm4(v + 12, buf + (ma + st));
  ldsm4(v + 16, buf + (ma + 2 * st)); ldsm4(v + 20, buf + (mb + 2 * st));
}
__device__ __forceinline__ void load_stats(Frame& F, uint32_t a) {
  asm volatile("ld.shared.b32 %0, [%1];" : "=r"(F.e0) : "r"(a + F.sta) : "memory");
  asm volatile("ld.shared.b32 %0, [%1];" : "=r"(F.e1) : "r"(a + F.sta + 32) : "memory");
}
template <int M>
__device__ __forceinline__ void hand_over(uint32_t (&q)[24]) {
  pin<24>(q);
  if (M) launder<24>(q);
  if (M == 4 && gridDim.x == 0x7fffffffu) {
#pragma unroll
    for (int j = 0; j < 24; j++) asm volatile("not.b32 %0, %0;" : "+r"(q[j]));
  }
  if (M == 8) {
#pragma unroll
    for (int j = 0; j < 24; j += 4)
      asm volatile("{\n.reg .pred p;\nsetp.eq.u32 p, %1, 0x7fffffff;\n@p not.b32 %0, %0;\n}" : "+r"(q[j]) : "r"(gridDim.x));
  }
}
__device__ __forceinline__ void gemm_s(uint32_t (&s)[16], const uint32_t* q, uint64_t dA) {
  asm volatile("" : "+l"(dA));
  wg_fence();
  wg56h<0>(s, q, dA); wg56h<1>(s, q + 4, dA + 2);
  wg56h<1>(s, q + 8, dA + 784); wg56h<1>(s, q + 12, dA + 786);
  wg56h<1>(s, q + 16, dA + 1568); wg56h<1>(s, q + 20, dA + 1570);
  wg_commit();
}
__device__ __forceinline__ void gemm_u(uint32_t (&u)[24], const uint32_t* s, uint64_t dA) {
  asm volatile("" : "+l"(dA));
  const uint64_t mn = dA + (((kChunk >> 4) - 1) << 16);
  wg_fence();
  wg96h<XL, 1>(u, s, mn); wg96h<1, 1>(u, s + 4, mn + 64); wg96h<1, 1>(u, s + 8, mn + 128); wg96h<1, 1>(u, s + 12, mn + 192);
  wg_commit();
}
__device__ __forceinline__ uint32_t key48(uint32_t (&s)[16], uint32_t tid) {
  pin<14>(s);
  return fresh(sel(tid & 3, 0xfc00fc00u, __byte_perm(s[12], s[13], 0x5410)));
}
__device__ __forceinline__ uint32_t amax3(uint32_t a, uint32_t b, uint32_t c) {
  return as_u(__hmax2(__hmax2(__habs2(as_h2(a)), __habs2(as_h2(b))), __habs2(as_h2(c))));
}
template <int N>
__device__ __forceinline__ void soft_check(uint32_t (&s)[16], uint32_t& t, uint32_t (&v)[24], Frame& F, float2& e) {
  const uint32_t am = h2max(h2max(h2max(amax3(s[0], s[1], s[2]), amax3(s[3], s[4], s[5])), amax3(s[6], s[7], s[8])), h2max(amax3(s[9], s[10], s[11]), t));
  const uint32_t al = __byte_perm(F.e0, F.e1, 0x5410);
  e = unpack_h2(al);
  uint32_t rare, sp[N + 1];
#pragma unroll
  for (int j = 0; j < N; j++) sp[j] = fresh(h2ex2(s[j]));
  asm("{\n.reg .pred p, q;\nsetp.eq.u32 q, %3, 0;\nsetp.le.and.f16x2 p|q, %1, %2, q;\nand.pred p, p, q;\nselp.b32 %0, 0, 1, p;\n}"
      : "=r"(rare) : "r"(am), "r"(0x49004900u), "r"(al & 0x80008000u));
  if (__any_sync(0xffffffffu, rare)) {
    const uint32_t x0 = h2max(h2max(h2max(s[0], s[2]), h2max(s[4], s[6])), h2max(s[8], s[10]));
    const uint32_t x1 = h2max(h2max(h2max(s[1], s[3]), h2max(s[5], s[7])), h2max(s[9], s[11]));
    uint32_t mx = h2max(h2max(__byte_perm(x0, x1, 0x5410), __byte_perm(x0, x1, 0x7632)), t);
    mx = h2max(mx, __shfl_xor_sync(0xffffffffu, mx, 1));
    mx = h2max(mx, __shfl_xor_sync(0xffffffffu, mx, 2));
#pragma unroll
    for (int j = 0; j < 6; j++) { s[2 * j] = h2sub(s[2 * j], lo2(mx)); s[2 * j + 1] = h2sub(s[2 * j + 1], hi2(mx)); }
    t = h2sub(t, mx);
    if (is_wide(F)) {
      const uint32_t cs = score_scale(&g_par.cS_s);
#pragma unroll
      for (int j = 0; j < 12; j++) s[j] = h2mul(s[j], cs);
      t = h2mul(t, cs);
      const float s0 = stat_f32(F.e0).x, s1 = stat_f32(F.e1).x;
      const float kb = __ldcg(&g_par.kb), ik = rcp_fast(__ldcg(&g_par.kappa));
      e.x = fmaxf(s0, kb); e.y = fmaxf(s1, kb);
      const uint32_t aw = pack_h2(__fdividef(s0, e.x), __fdividef(s1, e.y));
      e.x *= ik; e.y *= ik;
#pragma unroll
      for (int j = 0; j < 12; j++) { v[2 * j] = h2mul(v[2 * j], lo2(aw)); v[2 * j + 1] = h2mul(v[2 * j + 1], hi2(aw)); }
    }
#pragma unroll
    for (int j = 0; j < N; j++) sp[j] = h2ex2(s[j]);
  }
#pragma unroll
  for (int j = 0; j < N; j++) s[j] = sp[j];
}
template <int N, int M>
__device__ __forceinline__ void soft_part(uint32_t (&s)[16]) {
#pragma unroll
  for (int j = N; j < M; j++) s[j] = h2ex2(s[j]);
  pin<12>(s);
}
template <int N>
__device__ __forceinline__ uint32_t soft_sum(uint32_t (&s)[16], uint32_t& t) {
#pragma unroll
  for (int j = N; j < 12; j++) s[j] = h2ex2(s[j]);
  t = h2ex2(t);
  return fresh(h2add(t, fold_add(h2add(h2add(h2add(s[0], s[2]), h2add(s[4], s[6])), h2add(s[8], s[10])),
                                 h2add(h2add(h2add(s[1], s[3]), h2add(s[5], s[7])), h2add(s[9], s[11])))));
}
struct Quad { uint32_t v[4]; };
__device__ __forceinline__ Quad quad_send(uint32_t a) {
  Quad q;
  q.v[0] = a;
#pragma unroll
  for (int i = 1; i < (QS == 2 ? 4 : QS == 1 ? 2 : 1); i++) q.v[i] = __shfl_xor_sync(0xffffffffu, a, i);
  return q;
}
__device__ __forceinline__ uint32_t quad_recv(const Quad& q) {
  if (QS == 2) return h2add(h2add(q.v[0], q.v[1]), h2add(q.v[2], q.v[3]));
  if (QS == 0) return quad_h2add(q.v[0]);
  const uint32_t t = h2add(q.v[0], q.v[1]);
  return h2add(t, __shfl_xor_sync(0xffffffffu, t, 2));
}
__device__ __forceinline__ void soft_norm(uint32_t (&s)[16], uint32_t& t, const Quad& rsum, const Frame& F, float2 e, uint32_t tid) {
  const uint32_t kk2 = F.light ? ((tid & 28) == 0 ? 0xffffu : 0u) : 0xffffffffu;
  const float2 d = unpack_h2(quad_recv(rsum));
  const uint32_t cb = pack_h2(rcp_fast(d.x * e.x), rcp_fast(d.y * e.y)) & kk2;
#pragma unroll
  for (int j = 0; j < 6; j++) { s[2 * j] = h2mul(s[2 * j], lo2(cb)); s[2 * j + 1] = h2mul(s[2 * j + 1], hi2(cb)); }
  t = fresh(h2mul(t, cb));
  pin<12>(s);
}
__device__ __forceinline__ void soft_tail(uint32_t (&s)[16], uint32_t t) {
  s[12] = t & 0xffffu; s[13] = t >> 16;
  asm volatile("mov.b32 %0, 0;\nmov.b32 %1, 0;" : "=r"(s[14]), "=r"(s[15]));
}
template <int H>
__device__ __forceinline__ uint8_t* row_ptr(const Frame& F, uint8_t* o) {
  const uint32_t oo = fresh(F.oo);
  o += (size_t)(H ? oo >> 16 : oo & 0xffffu) * 16;
  asm volatile("" : "+l"(o));
  return o;
}
template <int H>
__device__ __forceinline__ void affine(uint32_t* r, const uint32_t (&v)[24], const Frame& F) {
  const uint32_t e = H ? F.e1 : F.e0;
#pragma unroll
  for (int j = 0; j < 12; j++) r[j] = h2fma(v[2 * j + H], lo2(e), hi2(e));
  pin<12>(r);
}
template <int H>
__device__ __forceinline__ void finish(uint32_t* r, const Frame& F, uint8_t*& o, uint32_t off, uint32_t& tid) {
  o = row_ptr<H>(F, o);
  off = fresh(off);
#pragma unroll
  for (int j = 0; j < 12; j += 2) { const float2 f = unpack_h2(r[j]), g = unpack_h2(r[j + 1]); r[j] = pack_bf2(f.x, g.x); r[j + 1] = pack_bf2(f.y, g.y); }
  pin<12>(r);
  if (SE) sf();
  stg3(o, r, off);
}
__device__ __forceinline__ void finish_wide(const uint32_t (&v)[24], const Frame& F, uint8_t* o, uint32_t tid) {
  const float kb = __ldcg(&g_par.kb);
#pragma unroll
  for (int h = 0; h < 2; h++) {
    const float2 z = stat_f32(h ? F.e1 : F.e0);
    const float w = fmaxf(z.x, kb);
    uint32_t r[12];
#pragma unroll
    for (int j = 0; j < 12; j += 2) {
      const float2 f = unpack_h2(v[2 * j + h]), g = unpack_h2(v[2 * j + 2 + h]);
      r[j] = pack_bf2(fmaf(f.x, w, z.y), fmaf(g.x, w, z.y)); r[j + 1] = pack_bf2(fmaf(f.y, w, z.y), fmaf(g.y, w, z.y));
    }
    o = h ? row_ptr<1>(F, o) : row_ptr<0>(F, o);
    stg3(o, r, F.light ? (h ? 1 : tid & 28) : 0);
  }
}

__device__ __forceinline__ void release_slot(uint32_t sb, uint32_t i, int nw, uint32_t w, uint32_t wlast, int lane, const CUtensorMap* tm) {
  const uint32_t ia = i & 3;
  uint32_t old = 0;
  asm volatile("{\n.reg .pred p;\nsetp.eq.u32 p, %2, 0;\n@p atom.relaxed.cta.shared::cta.inc.u32 %0, [%1], 1;\n}"
               : "+r"(old) : "r"(sb + kOffBar + 80 + ia * 4), "r"(lane) : "memory");
  if (old == 1) {
    const uint32_t bar = sb + kOffBar + ia * 8;
    if (i + 4 < nw) {
      mbar_expect(bar, kXBytes);
      tma_load_win(sb + kOffBuf + ia * kBufStride, tm, bar, i + 5 == nw ? wlast : w + 4 * gridDim.x);
      if (PF == 1 && i + 5 < nw) tma_prefetch_win(tm, i + 6 == nw ? wlast : w + 5 * gridDim.x);
      if (PF == 3 && i + 6 < nw) tma_prefetch_win(tm, i + 7 == nw ? wlast : w + 6 * gridDim.x);
    } else if (i + 4 == nw) {
      mbar_arrive(bar);
    }
  }
  __syncwarp();
}
__device__ __forceinline__ void run_S(uint32_t sb, uint64_t d0, int nw, int i0, int nwS, uint32_t wlast, int sg, int wp, int lane,
                                      const CUtensorMap* tm, uint8_t* __restrict__ out) {
  constexpr size_t kFrame = (size_t)kH * kW * 192;
  Frame A, B;
  uint32_t tid = lane + (frame_init(A, 2 * sg, wp, lane) << 4) + (frame_init(B, 2 * sg + 1, wp, lane) << 16);
  const uint64_t dQ = d0 + (kOffAs >> 4), dO = d0 + (kOffWs >> 4);
  uint32_t va[24], vb[24], x[24], sa[16], sc[16], r0[12], r1[12], ta, tb;
  Quad rs;
  float2 e;
#pragma unroll
  for (int j = 0; j < 24; j++) { vb[j] = 0; x[j] = 0; }
  uint8_t *ob = out, *o;
  uint32_t wn = blockIdx.x + i0 * gridDim.x;
  mbar_wait(sb + kOffBar + 32 + (i0 & 3) * 8, (i0 >> 2) & 1);
  if (FEN) asm volatile("fence.proxy.async.shared::cta;" ::: "memory");
  load_frame(va, (tid >> 4) & 0xfff0u, sb + kOffBuf + (i0 & 3) * kBufStride);
  int i = i0;
  do {
    const uint32_t ia = i & 3;
    const uint32_t buf = sb + kOffBuf + ia * kBufStride;
    const uint64_t pa = d0 + (uint32_t)((kOffBuf >> 4) + ia * (kBufStride >> 4) + sg * (2 * kPlane >> 4)), pb = pa + (kPlane >> 4);
    gemm_w<2>(x, va, dQ);
    FG(GS, 1);
    const uint32_t wb = is_wide(B);
    if (wb && i != i0) finish_wide(vb, B, ob + kFrame, tid);
    affine<0>(r0, vb, B); affine<1>(r1, vb, B);
    sf();
    load_frame(vb, (tid >> 16) & 0xfff0u, buf);
    load_stats(A, buf + (tid & 0x1c));
    FG(HS, 1);
    o = ob + kFrame;
    finish<0>(r0, B, o, (tid & (B.light ? 28 : 0)) | wb, tid);
    sf();
    wg_wait<0>(); hand_over<TM / 1000>(x);
    gemm_s(sa, x, pa);
    FG(GS, 2);
    const uint32_t w = i + 1 == nw ? wlast : wn;
    if (!B.light) finish<1>(r1, B, o, wb, tid);
    else if (PF == 2 && sg == 0 && i + 4 < nw) {
      if ((tid & 31) == 0) tma_prefetch_win(tm, i + 5 == nw ? wlast : w + 4 * gridDim.x);
      __syncwarp();
    }
    wn += gridDim.x;
    ob = out + (size_t)((((w * 57457u) >> 22) * (7 * kW - 7 * kNWX) + w * 7 + sg * (2 * kH * kW)) * 192u);
    FG(HS, 2);
    wg_wait<0>(); pin<14>(sa);
    gemm_w<2>(x, vb, dQ);
    FG(GS, 4);
    ta = key48(sa, tid);
    soft_check<NA>(sa, ta, va, A, e);
    rs = quad_send(soft_sum<NA>(sa, ta));
    FG(HS, 4);
    wg_wait<0>(); hand_over<TM / 100 % 10>(x);
    gemm_s(sc, x, pb);
    FG(GS, 8);
    load_stats(B, buf + (tid & 0x1c));
    soft_norm(sa, ta, rs, A, e, tid);
    FG(HS, 8);
    wg_wait<0>();
    tb = key48(sc, tid);
    sf();
    soft_tail(sa, ta);
    gemm_u(x, sa, pa);
    FG(GS, 16);
    soft_check<NB>(sc, tb, vb, B, e);
    if (XS == 0) rs = quad_send(soft_sum<NB>(sc, tb));
    else soft_part<NB, XS>(sc);
    FG(HS, 16);
    wg_wait<0>(); hand_over<TM / 10 % 10>(x);
    gemm_w<1>(va, x, dO);
    FG(GS, 32);
    if (XS) rs = quad_send(soft_sum<XS>(sc, tb));
    soft_norm(sc, tb, rs, B, e, tid);
    soft_tail(sc, tb);
    const uint32_t wa = fresh(is_wide(A));
    FG(HS, 32);
    wg_wait<0>(); pin<24>(va);
    gemm_u(x, sc, pb);
    FG(GS, 64);
    const uint32_t nb = sb + kOffBar + 32 + ((i + 1) & 3) * 8, np = ((i + 1) >> 2) & 1;
    const uint32_t rdy = mbar_test(nb, np);
    affine<0>(r0, va, A);
    o = ob;
    finish<0>(r0, A, o, (tid & (A.light ? 28 : 0)) | wa, tid);
    const bool slow = __any_sync(0xffffffffu, !rdy | (wa != 0) | (!LR && A.light));
    FG(HS, 64);
    wg_wait<0>(); hand_over<TM % 10>(x);
    gemm_w<1>(vb, x, dO);
    FG(GS, 128);
    affine<1>(r1, va, A);
    if (wp == 2) TR(i + 1, 4 + 2 * sg);
    if (slow) {
      if (A.light) release_slot(sb, i, nw, w, wlast, tid & 31, tm);
      if (wa) finish_wide(va, A, ob, tid);
      if (i + 1 < nwS) mbar_wait(nb, np);
    }
    if (wp == 2) TR(i + 1, 5 + 2 * sg);
    load_frame(va, (tid >> 4) & 0xfff0u, sb + kOffBuf + ((i + 1) & 3) * kBufStride);
    if (!A.light) finish<1>(r1, A, o, wa, tid);
    else {
      if (LR && !slow) release_slot(sb, i, nw, w, wlast, tid & 31, tm);
      if (FEN) asm volatile("fence.proxy.async.shared::cta;" ::: "memory");
    }
    wg_wait<0>(); pin<24>(vb);
    launder<24>(vb);
    launder<24>(va);
  } while (++i < nwS);
  const uint32_t wb = is_wide(B);
  if (wb) finish_wide(vb, B, ob + kFrame, tid);
  o = ob + kFrame;
  affine<0>(r0, vb, B); finish<0>(r0, B, o, (tid & (B.light ? 28 : 0)) | wb, tid);
  affine<1>(r1, vb, B); finish<1>(r1, B, o, B.light | wb, tid);
}

__global__ void __launch_bounds__(LB, 1) swin_main(const __grid_constant__ CUtensorMap tm, uint8_t* __restrict__ out, const uint64_t d0) {
  extern __shared__ __align__(1024) uint8_t smem[];
  const uint32_t sb = CB ? 1024u : smem_u32(smem);
  const int tid = threadIdx.x;
  const int wg = __shfl_sync(0xffffffffu, tid >> 7, 0);
  const int wp = __shfl_sync(0xffffffffu, (tid >> 5) & 3, 0);
  const int lane = tid & 31;
  const int b = blockIdx.x, nb = gridDim.x;
  const int nfull = kNWIN / nb, nrem = kNWIN - nfull * nb;
  const bool share = 2 * nrem <= nb;
  const int nw = nfull + (b < (share ? 2 * nrem : nrem));
  const bool half = share && nw > nfull;
  const uint32_t wlast = half && b >= nrem ? b - nrem + nfull * nb : b + (nw - 1) * nb;
  if (tid == 0) {
    if (smem_u32(smem) != 1024 || nw > 700 || nw < 5) __trap();
#pragma unroll
    for (int i = 0; i < 4; i++) {
      mbar_init(sb + kOffBar + i * 8, 1);
      mbar_init(sb + kOffBar + 32 + i * 8, 49);
      asm volatile("st.shared.b32 [%0], %1;" ::"r"(sb + kOffBar + 80 + i * 4), "r"(0) : "memory");
    }
    for (int i = 0; i < 4; i++) asm volatile("st.shared.b32 [%0], %1;" ::"r"(sb + kOffFlag + i * 4), "r"(0) : "memory");
    mbar_init(sb + kOffBar + 64, 1); mbar_init(sb + kOffBar + 72, 1);
    asm volatile("fence.mbarrier_init.release.cluster;" ::: "memory");
    for (int i = 0; i < PRE; i++) {
      mbar_expect(sb + kOffBar + i * 8, kXBytes);
      tma_load_win(sb + kOffBuf + i * kBufStride, &tm, sb + kOffBar + i * 8, b + i * nb);
    }
  }
  __syncwarp();
  if (wg == 1 || wg == 2)
    asm volatile("st.shared.v4.b32 [%0], {%1,%1,%1,%1};" ::"r"(sb + kOffBuf + ((tid - 128) >> 6) * kBufStride + kXBytes + (tid & 63) * 16), "r"(0) : "memory");
  __syncthreads();
  asm volatile("griddepcontrol.wait;" ::: "memory");
#pragma unroll
  for (int q = 0; q < kWBytes / 16 / 512; q++)
    asm volatile("cp.async.cg.shared.global [%0], [%1], 16;" ::"r"(sb + (tid + q * 512) * 16), "l"(g_wimg + tid + q * 512) : "memory");
  if (wg == 0 && wp < 3) {
    static_assert(kWBytes / 16 == 9 * 512 + 96, "weight copy split");
    const int e = tid + 9 * 512;
    asm volatile("cp.async.cg.shared.global [%0], [%1], 16;" ::"r"(sb + e * 16), "l"(g_wimg + e) : "memory");
  }
  Params P;
  {
    const float4 p0 = __ldcg(reinterpret_cast<const float4*>(&g_par));
    P.cS_t = p0.x; P.cS_s = p0.y; P.kt = p0.z; P.kappa = p0.w;
    const float kb = __ldcg(&g_par.kb);
    P.kb = P.cS_s != 1.f || P.kappa != 1.f ? 1e30f : kb;
  }
  const bool scaled = __any_sync(0xffffffffu, P.cS_t != 1.f);
  const bool direct = __all_sync(0xffffffffu, !scaled && P.kt <= 256.f);
  asm volatile("cp.async.wait_all;\nfence.proxy.async.shared::cta;" ::: "memory");
  if (tid == 0) {
    for (int i = PRE; i < 4; i++) {
      mbar_expect(sb + kOffBar + i * 8, kXBytes);
      tma_load_win(sb + kOffBuf + i * kBufStride, &tm, sb + kOffBar + i * 8, b + i * nb);
    }
  }
  __syncthreads();
  const bool isT = (wg >> 1) == TROLE;
  const int g2 = wg & 1;
  run_T(sb, d0, nw, 32 * g2 + (isT && HELP & 1 ? 64 : 0), isT ? 49 * nw : HELP & 1 ? 64 : 0, wg, wp, tid, P, scaled, direct);
  const int skip = half && (b >= nrem) != g2;
  const int i0 = isT ? (HELP & 2 ? nw - 1 : nw) : 0, i1 = isT || !(HELP & 2) ? nw - skip : nw - 1;
  if (i0 < i1) run_S(sb, d0, nw, i0, i1, wlast, g2, wp, lane, &tm, out);
}

__device__ __forceinline__ int ch_pos(int ch) { return 32 * (ch >> 5) + 16 * ((ch >> 2) & 1) + 8 * (ch & 1) + 2 * ((ch >> 3) & 3) + ((ch >> 1) & 1); }
__device__ __forceinline__ float pow2_ceil(float v) {
  return __uint_as_float((__float_as_uint(v) + 0x7fffffu) & 0x7f800000u);
}

constexpr int kPrepSplit = 12;
constexpr int kPrepThreads = 384;
__global__ void __launch_bounds__(kPrepThreads) swin_prep(const __nv_bfloat16* __restrict__ wqkv_t, const __nv_bfloat16* __restrict__ wo_t,
                                                          const __nv_bfloat16* __restrict__ wqkv_s, const __nv_bfloat16* __restrict__ wo_s) {
  asm volatile("griddepcontrol.launch_dependents;");
  __shared__ __align__(16) uint32_t raw[2][96][52];
  __shared__ __align__(16) uint32_t mu[3][52];
  __shared__ float nrm[12], nrm2[6], csum[6][9];
  const int mat = blockIdx.x / kPrepSplit, blk = blockIdx.x % kPrepSplit;
  const int tid = threadIdx.x, lane = tid & 31, warp = tid >> 5, g = lane >> 2, c = lane & 3;
  const __nv_bfloat16* wqkv = mat < 2 ? wqkv_t : wqkv_s;
  const __nv_bfloat16* wo = mat < 2 ? wo_t : wo_s;
  const bool isA = (mat & 1) == 0;
  {
    uint4 v[3], u[3];
#pragma unroll
    for (int q = 0; q < 3; q++) {
      const int e = tid + q * kPrepThreads, i = e / 12, c8 = (e % 12) * 8;
      v[q] = __ldg(reinterpret_cast<const uint4*>(wqkv + i * 288 + (isA ? 0 : 192) + c8));
      u[q] = __ldg(reinterpret_cast<const uint4*>(isA ? wqkv + i * 288 + 96 + c8 : wo + i * 96 + c8));
    }
#pragma unroll
    for (int q = 0; q < 3; q++) {
      const int e = tid + q * kPrepThreads, i = e / 12, c4 = (e % 12) * 4;
      *reinterpret_cast<uint4*>(&raw[0][i][c4]) = v[q];
      *reinterpret_cast<uint4*>(&raw[1][i][c4]) = u[q];
    }
  }
  __syncthreads();
  {
    const int m = warp / 6, cp = (warp % 6) * 8 + g;
    float s0 = 0.f, s1 = 0.f, q0 = 0.f, q1 = 0.f;
#pragma unroll
    for (int i = 0; i < 24; i++) {
      const uint32_t w = raw[m][4 * i + c][cp];
      const float lo = __uint_as_float(w << 16), hi = __uint_as_float(w & 0xffff0000u);
      s0 += lo; s1 += hi; q0 = fmaf(lo, lo, q0); q1 = fmaf(hi, hi, q1);
    }
    s0 = quad_sum(s0) * (1.f / 96.f); s1 = quad_sum(s1) * (1.f / 96.f); q0 = quad_sum(q0); q1 = quad_sum(q1);
    if (mat == 1 && m == 1) {
      float r0 = 0.f, r1 = 0.f;
#pragma unroll
      for (int i = 0; i < 12; i++) {
        const uint32_t w0 = raw[1][2 * cp][4 * i + c], w1 = raw[1][2 * cp + 1][4 * i + c];
        r0 += __uint_as_float(w0 << 16) + __uint_as_float(w0 & 0xffff0000u);
        r1 += __uint_as_float(w1 << 16) + __uint_as_float(w1 & 0xffff0000u);
      }
      r0 = quad_sum(r0) * (1.f / 96.f); r1 = quad_sum(r1) * (1.f / 96.f);
      s0 = r0; s1 = r1;
    }
    if (m == 1 && c == 0) {
      const uint32_t hi = mat == 3 ? 0u : pack_bf2(s0, s1);
      mu[0][cp] = hi;
      mu[1][cp] = mat == 3 ? 0u : pack_bf2(s0 - __uint_as_float(hi << 16), s1 - __uint_as_float(hi & 0xffff0000u));
      mu[2][cp] = 0u;
    }
    if (m == 0 || isA) {
      q0 = fmaxf(fmaf(-96.f * s0, s0, q0), 0.f) + q0 * 1e-6f;
      q1 = fmaxf(fmaf(-96.f * s1, s1, q1), 0.f) + q1 * 1e-6f;
    }
    const bool usemax = m == 1 && mat == 3;
    float t = usemax ? fmaxf(q0, q1) : q0 + q1;
#pragma unroll
    for (int o = 4; o < 32; o <<= 1) { const float z = __shfl_xor_sync(0xffffffffu, t, o); t = usemax ? fmaxf(t, z) : t + z; }
    if (lane == 0) nrm[warp] = t;
  }
  __syncthreads();
  if (warp >= 6) return;
  float d[4] = {0.f, 0.f, 0.f, 0.f}, e[4] = {0.f, 0.f, 0.f, 0.f}, v0, v1;
  {
    const uint32_t arow = smem_u32(&raw[0][16 * warp + (lane & 15)][(lane >> 4) * 4]);
    const uint32_t brow = isA ? smem_u32(&raw[1][blk * 8 + (lane & 7)][(lane >> 3) * 4]) : smem_u32(&raw[1][lane][blk * 4]);
    const uint32_t mrow = smem_u32(&mu[min(lane & 7, 2)][(lane >> 3) * 4]);
#pragma unroll
    for (int k2 = 0; k2 < 3; k2++) {
      uint32_t b[4], m[4];
      if (isA) ldsm4(b, brow + k2 * 64);
      else asm volatile("ldmatrix.sync.aligned.m8n8.x4.trans.shared.b16 {%0,%1,%2,%3}, [%4];"
                        : "=r"(b[0]), "=r"(b[1]), "=r"(b[2]), "=r"(b[3]) : "r"(brow + k2 * (32 * 208)) : "memory");
      ldsm4(m, mrow + k2 * 64);
#pragma unroll
      for (int hf = 0; hf < 2; hf++) {
        uint32_t a[4];
        ldsm4(a, arow + (2 * k2 + hf) * 32);
        asm volatile("mma.sync.aligned.m16n8k16.row.col.f32.bf16.bf16.f32 {%0,%1,%2,%3},{%4,%5,%6,%7},{%8,%9},{%0,%1,%2,%3};"
                     : "+f"(d[0]), "+f"(d[1]), "+f"(d[2]), "+f"(d[3])
                     : "r"(a[0]), "r"(a[1]), "r"(a[2]), "r"(a[3]), "r"(b[2 * hf]), "r"(b[2 * hf + 1]));
        asm volatile("mma.sync.aligned.m16n8k16.row.col.f32.bf16.bf16.f32 {%0,%1,%2,%3},{%4,%5,%6,%7},{%8,%9},{%0,%1,%2,%3};"
                     : "+f"(e[0]), "+f"(e[1]), "+f"(e[2]), "+f"(e[3])
                     : "r"(a[0]), "r"(a[1]), "r"(a[2]), "r"(a[3]), "r"(m[2 * hf]), "r"(m[2 * hf + 1]));
      }
    }
    v0 = __shfl_sync(0xffffffffu, e[0] + e[1], lane & ~3); v1 = __shfl_sync(0xffffffffu, e[2] + e[3], lane & ~3);
    d[0] -= v0; d[1] -= v0; d[2] -= v1; d[3] -= v1;
    float t0 = d[0] + d[2], t1 = d[1] + d[3], t2 = v0 + v1;
#pragma unroll
    for (int o = 4; o < 32; o <<= 1) {
      t0 += __shfl_xor_sync(0xffffffffu, t0, o); t1 += __shfl_xor_sync(0xffffffffu, t1, o); t2 += __shfl_xor_sync(0xffffffffu, t2, o);
    }
    if (g == 0) { csum[warp][2 * c] = t0; csum[warp][2 * c + 1] = t1; csum[warp][8] = t2; }
  }
  const float nl = nrm[0] + nrm[1] + nrm[2] + nrm[3] + nrm[4] + nrm[5];
  const float nr = mat == 3 ? fmaxf(fmaxf(fmaxf(nrm[6], nrm[7]), fmaxf(nrm[8], nrm[9])), fmaxf(nrm[10], nrm[11]))
                            : nrm[6] + nrm[7] + nrm[8] + nrm[9] + nrm[10] + nrm[11];
  const float bound = __fsqrt_rn(nl) * __fsqrt_rn(nr) * 1.01f;
  const float f = isA ? 0.14724448f : 1.f;
  float sc = pow2_ceil(fmaxf(bound * (isA ? 0.14724448f / 160.f : mat == 1 ? 1.f / 16.f : 1.f / 64.f), 1e-30f));
  if (isA) sc = fminf(fmaxf(sc, 1.f), 32768.f);
  if (mat == 3) {
    if (blk == 0 && tid == 0) g_par.kb = sc;
    if (sc <= 1.f && sc >= 1.f / 1024.f) sc = 1.f;
  }
  const float mul = f * __uint_as_float(0x7f000000u - __float_as_uint(sc));
  if (blk == 0 && tid == 0) (mat == 0 ? g_par.cS_t : mat == 1 ? g_par.kt : mat == 2 ? g_par.cS_s : g_par.kappa) = sc;
  asm volatile("bar.sync 1, 192;" ::: "memory");
  float mean[2];
#pragma unroll
  for (int b = 0; b < 2; b++)
    mean[b] = (csum[0][2 * c + b] + csum[1][2 * c + b] + csum[2][2 * c + b] + csum[3][2 * c + b] + csum[4][2 * c + b] + csum[5][2 * c + b]) *
              (1.f / 96.f);
  uint8_t* img = reinterpret_cast<uint8_t*>(g_wimg) + (mat == 0 ? 0 : mat == 1 ? kOffWt : mat == 2 ? kOffAs : kOffWs);
  const float vmean = (csum[0][8] + csum[1][8] + csum[2][8] + csum[3][8] + csum[4][8] + csum[5][8]) * (1.f / 96.f);
  float off = 0.f;
  if (mat == 2) {
    float q2 = 0.f;
#pragma unroll
    for (int q = 0; q < 4; q++) q2 = fmaf(d[q] - mean[q & 1], d[q] - mean[q & 1], q2);
#pragma unroll
    for (int o = 16; o; o >>= 1) q2 += __shfl_xor_sync(0xffffffffu, q2, o);
    if (lane == 0) nrm2[warp] = q2;
    asm volatile("bar.sync 1, 192;" ::: "memory");
    q2 = nrm2[0] + nrm2[1] + nrm2[2] + nrm2[3] + nrm2[4] + nrm2[5];
    off = 1.5f * pow2_ceil(fmaxf(__fsqrt_rn(q2 * (1.f / 768.f)) * mul * 3.f, 1e-4f));
  }
#pragma unroll
  for (int q = 0; q < 4; q++) {
    const int kp = ch_pos(16 * warp + g + 8 * (q >> 1)), np = ch_pos(blk * 8 + 2 * c + (q & 1));
    const uint32_t ko = (kp >> 5) * (mat < 2 ? kAtChunk : 6144) + (kp & 31) * 2;
    uint32_t a = ko + np * 64;
    a ^= ((a >> 7) & 3) << 4;
    float o = (d[q] - mean[q & 1]) * mul;
    o = mat == 2 ? o + off : __uint_as_float((__float_as_uint(o) + 0x8000u) & 0xffff0000u);
    *reinterpret_cast<__half*>(img + a) = __float2half_rn(o);
    if (mat == 1 && blk == 0) {
      a = (kp >> 5) * kAtChunk + (kp & 31) * 2 + (96 + 2 * c + (q & 1)) * 64;
      a ^= ((a >> 7) & 3) << 4;
      *reinterpret_cast<__half*>(reinterpret_cast<uint8_t*>(g_wimg) + a) = __float2half_rn((q & 1) ? ((q >> 1 ? v1 : v0) - vmean) * mul : 1.f / 96.f);
    }
  }
}

typedef CUresult (*EncodeFn)(CUtensorMap*, CUtensorMapDataType, cuuint32_t, void*, const cuuint64_t*, const cuuint64_t*,
                             const cuuint32_t*, const cuuint32_t*, CUtensorMapInterleave, CUtensorMapSwizzle,
                             CUtensorMapL2promotion, CUtensorMapFloatOOBfill);

}

extern "C" void kernel_launch(void* const* d_in, const int* in_sizes, int n_in, void* d_out, int out_size) {
  (void)in_sizes; (void)n_in; (void)out_size;
  static EncodeFn enc = nullptr;
  static int nsm = 0;
  if (!enc) {
    void* fn = nullptr;
    cudaDriverEntryPointQueryResult qr;
    cudaGetDriverEntryPoint("cuTensorMapEncodeTiled", &fn, cudaEnableDefault, &qr);
    enc = reinterpret_cast<EncodeFn>(fn);
    int dev = 0;
    cudaGetDevice(&dev);
    cudaDeviceGetAttribute(&nsm, cudaDevAttrMultiProcessorCount, dev);
    cudaFuncSetAttribute(swin_main, cudaFuncAttributeMaxDynamicSharedMemorySize, kSmemBytes);
  }
  CUtensorMap tm;
  const cuuint64_t dims[5] = {32, kW, kH, kT, 3};
  const cuuint64_t strides[4] = {192, 192ull * kW, 192ull * kW * kH, 64};
  const cuuint32_t box[5] = {32, 7, 7, 4, 3};
  const cuuint32_t es[5] = {1, 1, 1, 1, 1};
  enc(&tm, CU_TENSOR_MAP_DATA_TYPE_BFLOAT16, 5, d_in[0], dims, strides, box, es, CU_TENSOR_MAP_INTERLEAVE_NONE,
      CU_TENSOR_MAP_SWIZZLE_64B, CU_TENSOR_MAP_L2_PROMOTION_L2_128B, CU_TENSOR_MAP_FLOAT_OOB_FILL_NONE);

  cudaStream_t st = cudaStreamPerThread;
  swin_prep<<<4 * kPrepSplit, kPrepThreads, 0, st>>>(
      static_cast<const __nv_bfloat16*>(d_in[1]), static_cast<const __nv_bfloat16*>(d_in[2]),
      static_cast<const __nv_bfloat16*>(d_in[3]), static_cast<const __nv_bfloat16*>(d_in[4]));

  cudaLaunchConfig_t cfg = {};
  cfg.gridDim = dim3(nsm);
  cfg.blockDim = dim3(kNWG * 128);
  cfg.dynamicSmemBytes = kSmemBytes;
  cfg.stream = st;
  cudaLaunchAttribute at[1];
  at[0].id = cudaLaunchAttributeProgrammaticStreamSerialization;
  at[0].val.programmaticStreamSerializationAllowed = 1;
  cfg.attrs = at;
  cfg.numAttrs = 1;
  cudaLaunchKernelEx(&cfg, swin_main, tm, static_cast<uint8_t*>(d_out), mk_desc(1024, 1));
}
```

```cpp
#include <cuda_runtime.h>
#include <cuda.h>
#include <cuda_bf16.h>
#include <cuda_fp16.h>
#include <stdint.h>

namespace {

constexpr int kH = 511, kW = 511, kT = 4;
constexpr int kNWX = 73, kNWIN = 73 * 73;
constexpr int kChunk = 12544;
constexpr int kPlane = 3136;
constexpr int kXBytes = 37632;
constexpr int kZero = kXBytes + 896, kFull = kXBytes + 1024, kDone = kFull + 8, kRel = kFull + 16, kFlag = kFull + 20, kExtra = kFull + 24;
constexpr int kSlot = 38912;
constexpr int kWMat = 18432;
constexpr int kAtChunk = 200 * 64;
constexpr int kOffWt = 104 * 64;
constexpr int kOffAs = 3 * kAtChunk, kOffWs = kOffAs + kWMat;
constexpr int kWBytes = kOffWs + kWMat;
constexpr int kSmemBytes = kWBytes + 4 * kSlot;

struct Params {
  float cS_t, cS_s;
  float kt;
  float kappa;
  float kb;
  uint32_t ticket;
};

__device__ uint4 g_wimg[kWBytes / 16];
__device__ __align__(16) Params g_par;
#define TR(i, k)
#define GT 254
#define GS 0x7eec
#define FT(k) do { if ((GT >> (k)) & 1) sfence(lane); } while (0)
#define FS(k) do { if ((GS >> (k)) & 1) sfence(tid); } while (0)
#define DB 0
#define KA 0
#define LF 0
#define SG 1
#define GO 0
#define TM 0
#define SE 1
#define CB 0
#define NSP 4
#define L2P 1
#define DYN 1
#define NWH 8
#define MBHINT ""

__device__ __forceinline__ uint32_t smem_u32(const void* p) { return (uint32_t)__cvta_generic_to_shared(p); }
__device__ __forceinline__ void mbar_init(uint32_t a, int c) { asm volatile("mbarrier.init.shared::cta.b64 [%0], %1;" ::"r"(a), "r"(c)); }
__device__ __forceinline__ void mbar_expect(uint32_t a, int bytes) {
  asm volatile("mbarrier.arrive.expect_tx.shared::cta.b64 _, [%0], %1;" ::"r"(a), "r"(bytes) : "memory");
}
__device__ __forceinline__ void mbar_arrive(uint32_t a, uint32_t off = 0) {
  asm volatile("{\n.reg .pred p;\nsetp.eq.u32 p, %1, 0;\n@p mbarrier.arrive.shared::cta.b64 _, [%0];\n}" ::"r"(a), "r"(off) : "memory");
}
__device__ __forceinline__ void mbar_wait(uint32_t a, uint32_t par) {
  asm volatile(
      "{\n.reg .pred p;\n.reg .u32 n;\n"
      "mbarrier.try_wait.parity.shared::cta.b64 p, [%0], %1" MBHINT ";\n"
      "@p bra.uni WDONE;\n"
      "mov.u32 n, 0;\n"
      "WLOOP:\n"
      "mbarrier.try_wait.parity.shared::cta.b64 p, [%0], %1" MBHINT ";\n"
      "@p bra.uni WDONE;\n"
      "add.u32 n, n, 1;\n"
      "setp.lt.u32 p, n, 0x100000;\n"
      "@p bra.uni WLOOP;\n"
      "trap;\n"
      "WDONE:\n}" ::"r"(a), "r"(par & 1) : "memory");
}
__device__ __forceinline__ bool mbar_pending_or(uint32_t a, uint32_t par, uint32_t c) {
  uint32_t r;
  asm volatile("{\n.reg .pred p;\nmbarrier.test_wait.parity.shared::cta.b64 p, [%1], %2;\nsetp.ne.or.u32 p, %3, 0, !p;\n"
               "vote.sync.any.pred p, p, 0xffffffff;\nselp.b32 %0, 1, 0, p;\n}" : "=r"(r) : "r"(a), "r"(par & 1), "r"(c) : "memory");
  return r;
}
__device__ __forceinline__ uint32_t lds32(uint32_t a) {
  uint32_t v; asm volatile("ld.shared.b32 %0, [%1];" : "=r"(v) : "r"(a) : "memory"); return v;
}
__device__ __forceinline__ void sts32(uint32_t a, uint32_t v) { asm volatile("st.shared.b32 [%0], %1;" ::"r"(a), "r"(v) : "memory"); }
__device__ __forceinline__ void tma_load_win(uint32_t slot, const CUtensorMap* m, uint32_t w) {
  const uint32_t wy = (w * 57457u) >> 22, wx = w - wy * kNWX;
  mbar_expect(slot + kFull, kXBytes);
  asm volatile(
      "cp.async.bulk.tensor.5d.shared::cluster.global.mbarrier::complete_tx::bytes [%0], [%1, {%3,%4,%5,%3,%3}], [%2];" ::"r"(slot),
      "l"(m), "r"(slot + kFull), "r"(0), "r"(wx * 7), "r"(wy * 7)
      : "memory");
}
__device__ __forceinline__ void tma_prefetch_win(const CUtensorMap* m, uint32_t w) {
  const uint32_t wy = (w * 57457u) >> 22, wx = w - wy * kNWX;
  asm volatile("cp.async.bulk.prefetch.tensor.5d.L2.global [%0, {%1,%2,%3,%1,%1}];" ::"l"(m), "r"(0), "r"(wx * 7), "r"(wy * 7) : "memory");
}
__device__ __forceinline__ void wg_fence() { asm volatile("wgmma.fence.sync.aligned;" ::: "memory"); }
__device__ __forceinline__ void wg_commit() { asm volatile("wgmma.commit_group.sync.aligned;" ::: "memory"); }
__device__ __forceinline__ void wg_wait() { asm volatile("wgmma.wait_group.sync.aligned 0;" ::: "memory"); }
template <int N>
__device__ __forceinline__ void pin(uint32_t* d) {
#pragma unroll
  for (int i = 0; i < N; i++) asm volatile("" : "+r"(d[i])::"memory");
}
__device__ __forceinline__ uint32_t fresh(uint32_t v) { asm volatile("" : "+r"(v)); return v; }
__device__ __forceinline__ float fresh(float v) { asm volatile("" : "+f"(v)); return v; }
template <int N>
__device__ __forceinline__ void launder(uint32_t* q) {
#pragma unroll
  for (int j = 0; j < N; j++) { uint32_t t; asm volatile("mov.b32 %0, %1;" : "=r"(t) : "r"(q[j])); q[j] = t; }
}
__device__ __forceinline__ void sfence(uint32_t& v) {
  asm volatile("{\n.reg .pred p;\nsetp.eq.u32 p, %1, 0x7fffffff;\n@p mov.u32 %0, %%clock;\n}" : "+r"(v) : "r"(gridDim.x) : "memory");
}
constexpr uint64_t mk_desc(uint32_t addr) { return ((uint64_t)0x80000020u << 32) | (addr >> 4) | (1u << 16); }

#define R4(d, i) "+r"(d[i]), "+r"(d[i + 1]), "+r"(d[i + 2]), "+r"(d[i + 3])
#define O4(d, i) "=r"(d[i]), "=r"(d[i + 1]), "=r"(d[i + 2]), "=r"(d[i + 3])
#define D26 "{%0,%1,%2,%3,%4,%5,%6,%7,%8,%9,%10,%11,%12,%13,%14,%15,%16,%17,%18,%19,%20,%21,%22,%23,%24,%25},"
#define D24 "{%0,%1,%2,%3,%4,%5,%6,%7,%8,%9,%10,%11,%12,%13,%14,%15,%16,%17,%18,%19,%20,%21,%22,%23},"
#define D14 "{%0,%1,%2,%3,%4,%5,%6,%7,%8,%9,%10,%11,%12,%13},"

template <int SC, int TB>
__device__ __forceinline__ void wgmma(uint32_t (&d)[24], const uint32_t* a, uint64_t db) {
  if (SC == 2)
    asm volatile("{\n.reg .pred p;\nsetp.eq.u32 p, %30, 0x7fffffff;\n"
                 "wgmma.mma_async.sync.aligned.m64n96k16.f16.f16.f16 " D24 "{%24,%25,%26,%27}, %28, p, 1, 1, %29;\n}"
                 : R4(d, 0), R4(d, 4), R4(d, 8), R4(d, 12), R4(d, 16), R4(d, 20)
                 : "r"(a[0]), "r"(a[1]), "r"(a[2]), "r"(a[3]), "l"(db), "n"(TB), "r"(gridDim.x));
  else if (SC)
    asm volatile("wgmma.mma_async.sync.aligned.m64n96k16.f16.f16.f16 " D24 "{%24,%25,%26,%27}, %28, 1, 1, 1, %29;"
                 : R4(d, 0), R4(d, 4), R4(d, 8), R4(d, 12), R4(d, 16), R4(d, 20)
                 : "r"(a[0]), "r"(a[1]), "r"(a[2]), "r"(a[3]), "l"(db), "n"(TB));
  else
    asm volatile("wgmma.mma_async.sync.aligned.m64n96k16.f16.f16.f16 " D24 "{%24,%25,%26,%27}, %28, 0, 1, 1, %29;"
                 : O4(d, 0), O4(d, 4), O4(d, 8), O4(d, 12), O4(d, 16), O4(d, 20)
                 : "r"(a[0]), "r"(a[1]), "r"(a[2]), "r"(a[3]), "l"(db), "n"(TB));
}
template <int SC, int TB>
__device__ __forceinline__ void wgmma(uint32_t (&d)[26], const uint32_t* a, uint64_t db) {
  if (SC)
    asm volatile("wgmma.mma_async.sync.aligned.m64n104k16.f16.f16.f16 " D26 "{%26,%27,%28,%29}, %30, 1, 1, 1, 0;"
                 : R4(d, 0), R4(d, 4), R4(d, 8), R4(d, 12), R4(d, 16), R4(d, 20), "+r"(d[24]), "+r"(d[25])
                 : "r"(a[0]), "r"(a[1]), "r"(a[2]), "r"(a[3]), "l"(db));
  else
    asm volatile("wgmma.mma_async.sync.aligned.m64n104k16.f16.f16.f16 " D26 "{%26,%27,%28,%29}, %30, 0, 1, 1, 0;"
                 : O4(d, 0), O4(d, 4), O4(d, 8), O4(d, 12), O4(d, 16), O4(d, 20), "=r"(d[24]), "=r"(d[25])
                 : "r"(a[0]), "r"(a[1]), "r"(a[2]), "r"(a[3]), "l"(db));
}
template <int SC, int TB>
__device__ __forceinline__ void wgmma(uint32_t (&d)[16], const uint32_t* a, uint64_t db) {
  if (SC)
    asm volatile("wgmma.mma_async.sync.aligned.m64n56k16.f16.f16.f16 " D14 "{%14,%15,%16,%17}, %18, 1, 1, 1, 0;"
                 : R4(d, 0), R4(d, 4), R4(d, 8), "+r"(d[12]), "+r"(d[13])
                 : "r"(a[0]), "r"(a[1]), "r"(a[2]), "r"(a[3]), "l"(db));
  else
    asm volatile("wgmma.mma_async.sync.aligned.m64n56k16.f16.f16.f16 " D14 "{%14,%15,%16,%17}, %18, 0, 1, 1, 0;"
                 : O4(d, 0), O4(d, 4), O4(d, 8), "=r"(d[12]), "=r"(d[13])
                 : "r"(a[0]), "r"(a[1]), "r"(a[2]), "r"(a[3]), "l"(db));
}
template <int SC, int OFF, int CH, int ND>
__device__ __forceinline__ void gemm(uint32_t (&d)[ND], const uint32_t* a, uint64_t db) {
  asm volatile("" : "+l"(db));
  wg_fence();
  wgmma<SC, 0>(d, a, db + OFF / 16);
#pragma unroll
  for (int k = 1; k < 6; k++) wgmma<1, 0>(d, a + 4 * k, db + (OFF + (k >> 1) * CH + (k & 1) * 32) / 16);
  wg_commit();
}
__device__ __forceinline__ void lds128(uint32_t* r, uint32_t a) {
  asm volatile("ld.shared.v4.b32 {%0,%1,%2,%3}, [%4];" : "=r"(r[0]), "=r"(r[1]), "=r"(r[2]), "=r"(r[3]) : "r"(a) : "memory");
}
__device__ __forceinline__ void ldsm4(uint32_t* r, uint32_t a) {
  asm volatile("ldmatrix.sync.aligned.m8n8.x4.shared.b16 {%0,%1,%2,%3}, [%4];"
               : "=r"(r[0]), "=r"(r[1]), "=r"(r[2]), "=r"(r[3]) : "r"(a) : "memory");
}
__device__ __forceinline__ void stsm4(uint32_t a, const uint32_t* r) {
  asm volatile("stmatrix.sync.aligned.m8n8.x4.shared.b16 [%0], {%1,%2,%3,%4};" ::"r"(a), "r"(r[0]), "r"(r[1]), "r"(r[2]), "r"(r[3])
               : "memory");
}
__device__ __forceinline__ void stg3(uint8_t* p, const uint32_t* r, uint32_t off) {
  asm volatile("{\n.reg .pred p;\nsetp.eq.u32 p, %13, 0;\n@p st.global.v4.b32 [%0], {%1,%2,%3,%4};\n"
               "@p st.global.v4.b32 [%0+64], {%5,%6,%7,%8};\n@p st.global.v4.b32 [%0+128], {%9,%10,%11,%12};\n}" ::"l"(p),
               "r"(r[0]), "r"(r[1]), "r"(r[2]), "r"(r[3]), "r"(r[4]), "r"(r[5]), "r"(r[6]), "r"(r[7]), "r"(r[8]), "r"(r[9]), "r"(r[10]), "r"(r[11]),
               "r"(off) : "memory");
}
__device__ __forceinline__ uint32_t pack_h2(float lo, float hi) {
  uint32_t r; asm("cvt.rn.f16x2.f32 %0, %1, %2;" : "=r"(r) : "f"(hi), "f"(lo)); return r;
}
__device__ __forceinline__ uint32_t pack_h2_sat(float lo, float hi) {
  uint32_t r; asm("cvt.rn.satfinite.f16x2.f32 %0, %1, %2;" : "=r"(r) : "f"(hi), "f"(lo)); return r;
}
__device__ __forceinline__ uint32_t pack_bf2(float lo, float hi) {
  uint32_t r; asm("cvt.rn.bf16x2.f32 %0, %1, %2;" : "=r"(r) : "f"(hi), "f"(lo)); return r;
}
__device__ __forceinline__ __half2 as_h2(uint32_t v) { return *reinterpret_cast<__half2*>(&v); }
__device__ __forceinline__ uint32_t as_u(__half2 v) { return *reinterpret_cast<uint32_t*>(&v); }
__device__ __forceinline__ float2 unpack_h2(uint32_t v) { return __half22float2(as_h2(v)); }
__device__ __forceinline__ float low_f(uint32_t v) { return __low2float(as_h2(v)); }
__device__ __forceinline__ uint32_t h2ex2(uint32_t v) { uint32_t r; asm("ex2.approx.f16x2 %0, %1;" : "=r"(r) : "r"(v)); return r; }
__device__ __forceinline__ uint32_t h2max(uint32_t a, uint32_t b) { return as_u(__hmax2(as_h2(a), as_h2(b))); }
__device__ __forceinline__ uint32_t h2add(uint32_t a, uint32_t b) { return as_u(__hadd2(as_h2(a), as_h2(b))); }
__device__ __forceinline__ uint32_t h2sub(uint32_t a, uint32_t b) { return as_u(__hsub2(as_h2(a), as_h2(b))); }
__device__ __forceinline__ uint32_t h2mul(uint32_t a, uint32_t b) { return as_u(__hmul2(as_h2(a), as_h2(b))); }
__device__ __forceinline__ uint32_t h2neg(uint32_t a) { return as_u(__hneg2(as_h2(a))); }
__device__ __forceinline__ uint32_t h2fma(uint32_t a, uint32_t b, uint32_t c) { return as_u(__hfma2(as_h2(a), as_h2(b), as_h2(c))); }
__device__ __forceinline__ uint32_t lo2(uint32_t v) { return as_u(__low2half2(as_h2(v))); }
__device__ __forceinline__ uint32_t hi2(uint32_t v) { return as_u(__high2half2(as_h2(v))); }
__device__ __forceinline__ uint32_t fold_add(uint32_t a, uint32_t b) { return h2add(__byte_perm(a, b, 0x5410), __byte_perm(a, b, 0x7632)); }
__device__ __forceinline__ uint32_t sel(uint32_t p, uint32_t a, uint32_t b) {
  uint32_t r; asm("{\n.reg .pred p;\nsetp.ne.u32 p, %3, 0;\nselp.b32 %0, %1, %2, p;\n}" : "=r"(r) : "r"(a), "r"(b), "r"(p)); return r;
}
__device__ __forceinline__ float sel4(uint32_t c, float a0, float a1, float a2, float a3) {
  return __uint_as_float(sel(c & 2, sel(c & 1, __float_as_uint(a3), __float_as_uint(a2)), sel(c & 1, __float_as_uint(a1), __float_as_uint(a0))));
}
__device__ __forceinline__ float rcp_fast(float v) { float r; asm("rcp.approx.ftz.f32 %0, %1;" : "=f"(r) : "f"(v)); return r; }
__device__ __forceinline__ float rsq_fast(float v) { float r; asm("rsqrt.approx.ftz.f32 %0, %1;" : "=f"(r) : "f"(v)); return r; }
__device__ __forceinline__ uint32_t shfl_x(uint32_t v, int m) { return __shfl_xor_sync(0xffffffffu, v, m); }
__device__ __forceinline__ uint32_t shfl_q(uint32_t v, int i) { return __shfl_sync(0xffffffffu, v, i, 4); }
__device__ __forceinline__ float quad_sum(float v) {
  v += __shfl_xor_sync(0xffffffffu, v, 1);
  return v + __shfl_xor_sync(0xffffffffu, v, 2);
}
__device__ __forceinline__ uint32_t score_scale(const float* p) { const float v = __ldcg(p); return pack_h2(v, v); }

constexpr float kEps96 = 1e-5f * 96.f * 96.f;
__device__ __forceinline__ float2 stat_f32(uint32_t e) {
  const float2 h = unpack_h2(e);
  return make_float2(__uint_as_float(sel(e & 0x8000u, (e << 16) & 0x7fff0000u, __float_as_uint(h.x))),
                     __uint_as_float(sel(e & 0x8000u, e & 0xffff0000u, __float_as_uint(h.y))));
}

struct Tile {
  uint32_t a;
  uint32_t next;
  uint32_t n;
  int live;
  uint32_t stat, wrap;
  uint32_t flag;
  uint32_t gate;
};
struct TPar { float kt, sgmin, outmax; };

__device__ __forceinline__ void load_rows(uint32_t* x0, uint32_t* x1, uint32_t a0, uint32_t a1) {
  a0 ^= (a0 >> 3) & 0x30; a1 ^= (a1 >> 3) & 0x30;
  lds128(x0, a0); lds128(x1, a1);
  lds128(x0 + 4, (a0 ^ 32) + kChunk); lds128(x1 + 4, (a1 ^ 32) + kChunk);
  lds128(x0 + 8, a0 + 2 * kChunk); lds128(x1 + 8, a1 + 2 * kChunk);
}
__device__ __forceinline__ void to_half(uint32_t (&z)[24], const uint32_t* x) {
#pragma unroll
  for (int j = 0; j < 24; j += 2) {
    const int o = j < 12 ? 2 * j : 2 * j - 23;
    uint32_t t;
    asm("cvt.rz.f16x2.f32 %0, %1, %2;" : "=r"(t) : "f"(__uint_as_float(x[j + 1])), "f"(__uint_as_float(x[j])));
    z[o] = pack_h2(__uint_as_float(x[j] << 16), __uint_as_float(x[j + 1] << 16));
    z[o + 2] = t & 0xfff8fff8u;
  }
}
__device__ __forceinline__ void load_general(uint32_t (&z)[24], uint32_t a0, float& ie0, float& ie1, float& m0, float& m1) {
  float acc[48];
  uint32_t x0[12], x1[12];
  load_rows(x0, x1, a0, a0 + kPlane);
#pragma unroll
  for (int j = 0; j < 12; j++) {
    acc[4 * j] = __uint_as_float(x0[j] << 16); acc[4 * j + 1] = __uint_as_float(x0[j] & 0xffff0000u);
    acc[4 * j + 2] = __uint_as_float(x1[j] << 16); acc[4 * j + 3] = __uint_as_float(x1[j] & 0xffff0000u);
  }
  float s[4], q[4];
#pragma unroll
  for (int e = 0; e < 4; e++) { s[e] = acc[e]; q[e] = acc[e] * acc[e]; }
#pragma unroll
  for (int j = 4; j < 48; j++) { s[j & 3] += acc[j]; q[j & 3] = fmaf(acc[j], acc[j], q[j & 3]); }
  const float s0 = quad_sum(s[0] + s[1]), s1 = quad_sum(s[2] + s[3]), q0 = quad_sum(q[0] + q[1]), q1 = quad_sum(q[2] + q[3]);
  const float u0 = rsq_fast(fmaxf(fmaf(-s0, s0, fmaf(q0, 96.f, kEps96)), kEps96));
  const float u1 = rsq_fast(fmaxf(fmaf(-s1, s1, fmaf(q1, 96.f, kEps96)), kEps96));
  const float n0 = -s0 * u0, n1 = -s1 * u1;
  ie0 = 96.f * u0; ie1 = 96.f * u1;
  m0 = s0 * (1.f / 96.f); m1 = s1 * (1.f / 96.f);
#pragma unroll
  for (int j = 0; j < 12; j++) {
    const int o = 8 * (j >> 1) + (j & 1);
    z[2 * j] = pack_h2(fmaf(acc[o], ie0, n0), fmaf(acc[o + 4], ie0, n0));
    z[2 * j + 1] = pack_h2(fmaf(acc[o + 2], ie1, n1), fmaf(acc[o + 6], ie1, n1));
  }
}
template <bool kDown>
__device__ __forceinline__ uint32_t sumsq2(const uint32_t* z) {
  uint32_t q0, q1;
#pragma unroll
  for (int j = 0; j < 12; j++) {
    const uint32_t u = kDown ? h2mul(z[2 * j], 0x1c001c00u) : z[2 * j], v = kDown ? h2mul(z[2 * j + 1], 0x1c001c00u) : z[2 * j + 1];
    q0 = j ? h2fma(u, u, q0) : h2mul(u, u); q1 = j ? h2fma(v, v, q1) : h2mul(v, v);
  }
  return fold_add(q0, q1);
}
template <bool kDown>
__device__ __forceinline__ float row_sumsq(const uint32_t* z0, const uint32_t* z1, uint32_t c) {
  const uint32_t a = sumsq2<kDown>(z0), b = sumsq2<kDown>(z1);
  uint32_t t = h2add(sel(c & 2, b, a), shfl_x(sel(c & 2, a, b), 2));
  t = h2add(t, shfl_x(t, 1));
  return low_f(sel(c & 1, t >> 16, t));
}
__device__ __forceinline__ void scores2(const uint32_t* q, const uint32_t* z0, const uint32_t* z1, uint32_t* f) {
  uint32_t d[8];
#pragma unroll
  for (int j = 0; j < 12; j++) {
    const uint32_t kk[4] = {z0[2 * j], z0[2 * j + 1], z1[2 * j], z1[2 * j + 1]};
#pragma unroll
    for (int e = 0; e < 4; e++) {
      d[e] = j ? h2fma(q[2 * j], kk[e], d[e]) : h2mul(q[2 * j], kk[e]);
      d[4 + e] = j ? h2fma(q[2 * j + 1], kk[e], d[4 + e]) : h2mul(q[2 * j + 1], kk[e]);
    }
  }
#pragma unroll
  for (int e = 0; e < 4; e++) f[e] = fold_add(d[2 * e], d[2 * e + 1]);
}
struct Xch { uint32_t keep[2], got[2]; };
__device__ __forceinline__ Xch pair_send(const uint32_t* a, const uint32_t* b, uint32_t c, int m) {
  Xch x;
#pragma unroll
  for (int e = 0; e < 2; e++) { x.keep[e] = fresh(sel(c & m, b[e], a[e])); x.got[e] = shfl_x(sel(c & m, a[e], b[e]), m); }
  return x;
}
__device__ __forceinline__ void pair_recv(uint32_t* k, const Xch& x) { k[0] = h2add(x.keep[0], x.got[0]); k[1] = h2add(x.keep[1], x.got[1]); }
__device__ __forceinline__ void mix2(uint32_t* y, const uint32_t* v, uint32_t c0, uint32_t c1) {
#pragma unroll
  for (int j = 0; j < 12; j++) {
    y[2 * j] = h2fma(v[2 * j + 1], hi2(c0), h2fma(v[2 * j], lo2(c0), y[2 * j]));
    y[2 * j + 1] = h2fma(v[2 * j + 1], hi2(c1), h2fma(v[2 * j], lo2(c1), y[2 * j + 1]));
  }
  pin<24>(y);
}
__device__ __forceinline__ void norm_store(uint32_t* y, uint32_t r0, uint32_t r1, uint32_t ma) {
#pragma unroll
  for (int j = 0; j < 12; j++) { y[2 * j] = h2fma(y[2 * j], lo2(r0), hi2(r0)); y[2 * j + 1] = h2fma(y[2 * j + 1], lo2(r1), hi2(r1)); }
  ma ^= (ma >> 3) & 0x30;
  const uint32_t mb = ma ^ 32;
  stsm4(ma, y); stsm4(mb, y + 4);
  stsm4(mb + kChunk, y + 8); stsm4(ma + kChunk, y + 12);
  stsm4(ma + 2 * kChunk, y + 16); stsm4(mb + 2 * kChunk, y + 20);
}

__device__ __forceinline__ void gate_open(uint32_t id) {
  asm volatile("{\n.reg .pred p;\nsetp.ne.u32 p, %0, 0;\n@p barrier.cta.arrive.aligned %0, 256;\n}" ::"r"(id) : "memory");
}

template <bool kDirect>
__device__ __forceinline__ bool temporal(uint64_t da, uint64_t db, const Tile& T, const TPar& P, bool scaled, uint32_t& lane, uint32_t lst) {
  const uint32_t c = lane;
  const uint32_t a0 = T.a + lane * 16 + (lane >= 4 * T.n ? T.next : 0);
  uint32_t z0[24], z1[24], q0[26], q1[24], v0[24], w1[26], nn = 0, ng = 0, ca0 = 0, ca1 = 0;
  uint32_t* const v1 = w1 + 2;
  float ie = 1.f, mm = 0.f;
  bool tiny = false;
  if (kDirect) {
    uint32_t x[48];
    load_rows(x, x + 12, a0, a0 + kPlane);
    load_rows(x + 24, x + 36, a0 + 2 * kPlane, a0 + 3 * kPlane);
    FT(0);
    to_half(z0, x);
    gemm<0, 0, kAtChunk>(q0, z0, da);
    FT(1);
    to_half(z1, x + 24);
    const uint32_t n0 = sumsq2<false>(z0), n1 = sumsq2<false>(z1);
    nn = fresh(sel(c & 2, n1, n0)); ng = shfl_x(sel(c & 2, n0, n1), 2);
    pin<24>(z1); FT(2);
  } else {
    float e[4], m[4];
    load_general(z0, a0, e[0], e[1], m[0], m[1]);
    pin<24>(z0); sfence(lane);
    load_general(z1, a0 + 2 * kPlane, e[2], e[3], m[2], m[3]);
    ie = sel4(c, e[0], e[1], e[2], e[3]);
    mm = sel4(c, m[0], m[1], m[2], m[3]);
    tiny = __any_sync(0xffffffffu, ie * P.kt > 400.f);
    if (tiny) {
      float u = 0.f;
#pragma unroll
      for (int r = 0; r < 4; r++) {
        float t = 0.f;
#pragma unroll
        for (int j = 0; j < 12; j++) { const float2 f = unpack_h2((r & 2 ? z1 : z0)[2 * j + (r & 1)]); t = fmaf(f.x, f.x, fmaf(f.y, f.y, t)); }
        u = fmaxf(u, quad_sum(t));
      }
      const float t = fminf(ie, 9.8f * rsq_fast(fmaxf(u, 2e-7f)) * rcp_fast(fresh(P.kt)));
      const uint32_t a = pack_h2(__fdividef(t, ie), 0.f);
      ca0 = __byte_perm(shfl_q(a, 0), shfl_q(a, 1), 0x5410); ca1 = __byte_perm(shfl_q(a, 2), shfl_q(a, 3), 0x5410);
      ie = t;
    }
    gemm<0, 0, kAtChunk>(q0, z0, da);
  }
  uint32_t f[4], k0[2], k1[2], sk[2];
  if (SG == 0) gate_open(T.gate);
  wg_wait(); pin<26>(q0);
  gemm<0, 0, kAtChunk>(q1, z1, DB ? db : da);
  if (SG == 1) gate_open(T.gate);
  FT(3);
  if (kDirect) { nn = h2add(nn, ng); ng = shfl_x(nn, 1); FT(4); }
  scores2(q0, z0, z1, f);
  const uint32_t nu0 = fresh(__byte_perm(q0[24], q0[25], 0x7632)), m01 = fresh(sel(c & 1, q0[25], q0[24]));
  Xch xc = pair_send(f, f + 2, c, 1);
  if (SG == 4) gate_open(T.gate);
  sfence(lane);
  wg_wait(); pin<24>(q1);
  gemm<0, kOffWt - 512, kAtChunk>(w1, z1, da);
  if (SG == 2) gate_open(T.gate);
  FT(5);
  pair_recv(k0, xc);
  float e2 = 0.f, lim = 0.f;
  if (kDirect) {
    nn = h2add(nn, ng);
    e2 = fresh(fmaf(low_f(sel(c & 1, nn >> 16, nn)), 1.f / 96.f, 1e-5f));
    lim = fresh(e2 <= 4.f ? fmaxf(0.5f * e2, 4e-4f) : 1e30f);
  }
  scores2(q1, z0, z1, f);
  xc = pair_send(f, f + 2, c, 1);
  pin<2>(k0); sfence(lane);
  wg_wait(); pin<26>(w1);
  float mz = 0.f, d2 = 0.f;
  if (kDirect) {
    mz = low_f(sel(c & 2, sel(c & 1, w1[1], w1[0]), m01));
    d2 = fmaf(-mz, mz, e2);
    asm volatile("{\n.reg .pred p;\nsetp.lt.s32 p, %3, %4;\nsetp.ltu.and.f32 p, %1, %2, p;\n@p st.volatile.shared.f32 [%0], %2;\n}" ::"r"(T.flag), "f"(d2),
                 "f"(lim), "r"(lane), "r"(T.live) : "memory");
  }
  gemm<0, kOffWt, kAtChunk>(v0, z0, da);
  if (SG == 3) gate_open(T.gate);
  FT(6);
  uint32_t cw[8], mu;
  {
    uint32_t rc = 0, r0 = 0, r1 = 0;
    if (kDirect) {
      const float r = rsq_fast(d2);
      rc = pack_h2(r, r);
      r0 = __byte_perm(shfl_q(rc, 0), shfl_q(rc, 1), 0x5410); r1 = __byte_perm(shfl_q(rc, 2), shfl_q(rc, 3), 0x5410);
    }
    pair_recv(k1, xc);
    pair_recv(sk, pair_send(k0, k1, c, 2));
    if (kDirect) { sk[0] = h2mul(sk[0], r0); sk[1] = h2mul(sk[1], r1); }
    uint32_t mx = h2max(sk[0], sk[1]);
    mx = h2max(lo2(mx), hi2(mx));
    if (kDirect) {
      const uint32_t nm = h2mul(h2neg(mx), rc);
      sk[0] = h2fma(sk[0], rc, nm); sk[1] = h2fma(sk[1], rc, nm);
    } else {
      sk[0] = h2sub(sk[0], mx); sk[1] = h2sub(sk[1], mx);
      if (scaled) {
        const uint32_t cs = score_scale(&g_par.cS_t);
        sk[0] = h2mul(sk[0], cs); sk[1] = h2mul(sk[1], cs);
      }
    }
    sk[0] = h2ex2(sk[0]); sk[1] = h2ex2(sk[1]);
    const uint32_t sm = h2add(sk[0], sk[1]);
    const float iv = (kDirect ? P.kt : P.kt * ie) * rcp_fast(low_f(h2add(lo2(sm), hi2(sm))));
    const uint32_t inv = pack_h2(iv, iv);
    if (kDirect) { sk[0] = h2mul(sk[0], r0); sk[1] = h2mul(sk[1], r1); }
    sk[0] = h2mul(sk[0], inv); sk[1] = h2mul(sk[1], inv);
#pragma unroll
    for (int i = 0; i < 4; i++) { cw[2 * i] = shfl_q(sk[0], i); cw[2 * i + 1] = shfl_q(sk[1], i); }
    mu = h2fma(sk[1], __byte_perm(w1[0], w1[1], 0x7632), h2mul(sk[0], nu0));
    mu = h2add(lo2(mu), hi2(mu));
  }
  uint32_t bad = 0;
  if (kDirect) {
    mix2(z1, v1, cw[5], cw[7]);
    FT(7);
    wg_wait(); pin<24>(v0);
    mix2(z1, v0, cw[4], cw[6]);
    sfence(lane);
    bad = lds32(T.flag);
  } else {
    wg_wait(); pin<24>(v0);
    if (tiny) {
#pragma unroll
      for (int j = 0; j < 12; j++) {
        z0[2 * j] = h2mul(z0[2 * j], lo2(ca0)); z0[2 * j + 1] = h2mul(z0[2 * j + 1], hi2(ca0));
        z1[2 * j] = h2mul(z1[2 * j], lo2(ca1)); z1[2 * j + 1] = h2mul(z1[2 * j + 1], hi2(ca1));
      }
    }
    mix2(z1, v1, cw[5], cw[7]);
    mix2(z1, v0, cw[4], cw[6]);
  }
  mix2(z0, v1, cw[1], cw[3]);
  mix2(z0, v0, cw[0], cw[2]);
  float qq = row_sumsq<false>(z0, z1, c);
  if (__any_sync(0xffffffffu, (!(qq < 65000.f) & ((int)lane < T.live)) | (bad != 0))) {
    if (kDirect && __any_sync(0xffffffffu, bad != 0)) return false;
    const float q2 = row_sumsq<true>(z0, z1, c) * 65536.f;
    qq = qq < 65000.f ? qq : q2;
  }
  const float rf = kDirect ? rsq_fast(fmaxf(fmaf(-mz, mz, fmaf(qq, 1.f / 96.f, 1e-5f)), 1e-5f)) : rsq_fast(fmaf(qq, 1.f / 96.f, 1e-5f * ie * ie));
  const uint32_t rn = pack_h2_sat(rf, -mz * rf);
  uint32_t rr[4];
#pragma unroll
  for (int i = 0; i < 4; i++) rr[i] = shfl_q(rn, i);
  if (!L2P) lst = (lane & 7) * 64 + (lane & 8) * (kPlane / 8) + (lane & 16);
  const uint32_t ma = T.a + lst + ((lane & 7) >= T.n ? T.next : 0);
  norm_store(z0, rr[0], rr[1], ma);
  norm_store(z1, rr[2], rr[3], ma + 2 * kPlane);
  const float2 rm = unpack_h2(rn);
  const float sg = rcp_fast(kDirect ? rm.x : rm.x * ie);
  mm = kDirect ? fmaf(-rm.y, sg, low_f(mu)) : fmaf(low_f(mu) * rm.x, sg, mm);
  const bool ok = (sg >= P.sgmin) & (fmaf(sg, 9.8f, fabsf(mm)) < P.outmax);
  asm volatile("{\n.reg .pred p;\nsetp.lt.s32 p, %2, %3;\n@p st.shared.b32 [%0], %1;\n}" ::"r"(
                   T.stat + fresh((lane & 3) * (kSlot - 1) + lane + (lane >= 4 * T.n ? T.wrap : 0))),
               "r"(sel(ok, pack_h2(sg, mm), pack_bf2(sg, mm) | 0x8000u)), "r"(lane), "r"(T.live) : "memory");
  return true;
}

__device__ __forceinline__ void run_T(uint32_t ring, uint64_t d0, uint64_t d1, uint32_t nfull, uint32_t nrem, bool helper, int wg, int wp, uint32_t lane,
                                      const TPar& P, bool scaled, bool direct) {
  const uint32_t lst = (lane & 7) * 64 + (lane & 8) * (kPlane / 8) + (lane & 16);
  uint32_t p0 = 32 * (wg & 1) + (helper ? 0 : 64) + 8 * wp;
  uint32_t npx = 49 * nfull, pstop = npx - 6 * 49 + 8 * wp;
  if (helper) pstop = 0;
  Tile T;
  T.flag = ring + wg * kSlot + kFlag;
  T.gate = helper && !(wg & 1) ? 0 : 5 + (wg & 1);
  while (true) {
    const uint32_t iw = (p0 * 21400u) >> 20, ow = p0 - 49 * iw;
    const uint32_t slot = ring + (iw & 3) * kSlot, dn = (iw & 3) == 3 ? -3 * kSlot : kSlot;
    if (wp == 3) TR(p0 >> 5, 1);
    if (GO == 0) asm volatile("{\n.reg .pred p;\nsetp.eq.u32 p, %1, 0;\n@p barrier.cta.sync.aligned %0, 256;\n}" ::"r"(6 - (wg & 1)), "r"((uint32_t)helper) : "memory");
    mbar_wait(slot + kFull, iw >> 2);
    if (ow > 41) mbar_wait(slot + dn + kFull, (iw + 1) >> 2);
    if (GO == 1) asm volatile("{\n.reg .pred p;\nsetp.eq.u32 p, %1, 0;\n@p barrier.cta.sync.aligned %0, 256;\n}" ::"r"(6 - (wg & 1)), "r"((uint32_t)helper) : "memory");
    if (wp == 3) TR(p0 >> 5, 2);
    T.a = slot + ow * 64; T.next = dn - kPlane; T.n = 49 - ow;
    T.live = 4 * (npx - p0);
    T.stat = ring + kXBytes + (p0 - 196 * (iw >> 2)) * 4; T.wrap = (iw & 3) == 3 ? -784 : 0;
    bool done = false;
    if (direct) done = temporal<true>(d0, d1, T, P, false, lane, lst);
    if (!done) {
      Tile G = T;
      if (direct) {
        asm volatile("barrier.cta.sync.aligned %0, 128;" ::"r"(wg + 1) : "memory");
        asm volatile("st.shared.b32 [%0], %1;\nfence.acq_rel.cta;" ::"r"(T.flag), "r"(0) : "memory");
        G.gate = 0;
      }
      temporal<false>(d1, d0, G, P, scaled, lane, lst);
    }
    const uint32_t pn = __shfl_sync(0xffffffffu, p0 + 64, 0);
    bool last = false;
    if (pn >= pstop) {
      if (helper) last = true;
      else if (pstop < npx - 4 * 49) {
        if (((wg & 1) | wp | lane) == 0) {
          const uint32_t nb = gridDim.x, nwh = min(max((int)(2 * nrem - nb), (int)(nrem * NWH / 16)), nrem);
          const uint32_t r = DYN ? atomicAdd(&g_par.ticket, 1u) : blockIdx.x, j = r - nwh;
          sts32(ring + kExtra, r < nwh ? (nfull * nb + r) * 4 + 3 : j < 2 * (nrem - nwh) ? (nfull * nb + nwh + (j >> 1)) * 4 + 1 + (j & 1) : 0);
        }
        __syncwarp();
        pstop = npx - 2 * 49 + 8 * wp;
      } else if (pstop < npx) {
        if (__shfl_sync(0xffffffffu, lds32(ring + kExtra), 0)) npx += 49;
        pstop = npx + 8 * wp;
      } else last = true;
    }
    asm volatile("fence.proxy.async.shared::cta;" ::: "memory");
    __syncwarp();
    mbar_arrive(slot + kDone + (lane >= 4 * T.n ? dn : 0), lane & 3);
    __syncwarp();
    if (wp == 3) TR(p0 >> 5, 3);
    if (last) break;
    p0 = pn;
  }
}

struct Frame {
  bool light;
  uint32_t sta;
  uint32_t oo;
  uint32_t e0, e1;
};
__device__ __forceinline__ uint32_t frame_init(Frame& F, uint32_t ring, uint32_t t, int wp, int lane) {
  wp = (wp + t) & 3;
  F.light = wp == 3;
  F.sta = ring + t * kSlot + kXBytes + 64 * wp;
  const uint32_t r = 16 * wp + (lane >> 2);
  F.oo = ((r / 7) * (kW - 7) + r) * 192u + (lane & 3) * 16 + (((((r + 8) / 7 - r / 7) * (kW - 7) + 8) * 3u) << 20);
  F.e0 = F.e1 = 0x8000u;
  const uint32_t am = t * kPlane + wp * 1024 + ((lane * 65) & 0x3d0);
  return F.light && (lane & 15) ? kZero : am ^ ((am >> 3) & 0x30);
}
template <bool F>
__device__ __forceinline__ void load_frame(uint32_t (&v)[24], uint32_t ma, uint32_t slot, uint32_t& tid) {
  const uint32_t st = ma < kXBytes ? kChunk : 0, mb = ma ^ 32;
  uint32_t a[6] = {ma, mb, mb + st, ma + st, ma + 2 * st, mb + 2 * st};
  pin<6>(a);
  if (F) sfence(tid);
#pragma unroll
  for (int k = 0; k < 6; k++) ldsm4(v + 4 * k, slot + a[k]);
}
__device__ __forceinline__ uint32_t load_stats(Frame& F, uint32_t ia, uint32_t tid) {
  const uint32_t a = fresh(tid & (F.light ? 0 : 0x1c)), u = F.sta + ia * 196;
  F.e0 = lds32(a + u);
  F.e1 = lds32(a + fresh(u + (F.light ? 0 : 32)));
  return a;
}
__device__ __forceinline__ uint32_t is_wide(const Frame& F) {
  uint32_t r;
  asm volatile("{\n.reg .pred p;\n.reg .b32 t;\nlop3.b32 t, %1, %2, 0x8000, 0xa8;\nsetp.ne.u32 p, t, 0;\nvote.sync.ballot.b32 %0, p, 0xffffffff;\n}"
               : "=r"(r) : "r"(F.e0), "r"(F.e1));
  return r;
}
template <int OFF>
__device__ __forceinline__ void gemm_u(uint32_t (&u)[24], const uint32_t* s, uint64_t db) {
  constexpr uint32_t kMN = (((kChunk >> 4) - 1) << 16) + OFF / 16;
  asm volatile("" : "+l"(db));
  wg_fence();
  wgmma<2, 1>(u, s, db + kMN); wgmma<1, 1>(u, s + 4, db + kMN + 64); wgmma<1, 1>(u, s + 8, db + kMN + 128); wgmma<1, 1>(u, s + 12, db + kMN + 192);
  wg_commit();
}
__device__ __forceinline__ uint32_t key48(uint32_t (&s)[16], uint32_t tid) {
  return fresh(sel(tid & 3, 0xfc00fc00u, __byte_perm(s[12], s[13], 0x5410)));
}
__device__ __forceinline__ uint32_t amax3(uint32_t a, uint32_t b, uint32_t c) {
  return as_u(__hmax2(__hmax2(__habs2(as_h2(a)), __habs2(as_h2(b))), __habs2(as_h2(c))));
}
struct Quad { uint32_t v[4]; };
__device__ __forceinline__ Quad soft_exp(uint32_t (&s)[16], uint32_t& t, uint32_t (&v)[24], const Frame& F, float2& e) {
  const uint32_t am = h2max(h2max(h2max(amax3(s[0], s[1], s[2]), amax3(s[3], s[4], s[5])), amax3(s[6], s[7], s[8])), h2max(amax3(s[9], s[10], s[11]), t));
  e = make_float2(low_f(F.e0), low_f(F.e1));
  uint32_t rare, sp[NSP + 1];
#pragma unroll
  for (int j = 0; j < NSP; j++) sp[j] = fresh(h2ex2(s[j]));
  asm("{\n.reg .pred p, q;\n.reg .b32 t;\nlop3.b32 t, %2, %3, 0x8000, 0xa8;\nsetp.eq.u32 q, t, 0;\nmov.b32 t, 0x49004900;\n"
      "setp.le.and.f16x2 p|q, %1, t, q;\nand.pred p, p, q;\nselp.b32 %0, 0, 1, p;\n}" : "=r"(rare) : "r"(am), "r"(F.e0), "r"(F.e1));
  if (__any_sync(0xffffffffu, rare)) {
    const uint32_t x0 = h2max(h2max(h2max(s[0], s[2]), h2max(s[4], s[6])), h2max(s[8], s[10]));
    const uint32_t x1 = h2max(h2max(h2max(s[1], s[3]), h2max(s[5], s[7])), h2max(s[9], s[11]));
    uint32_t mx = h2max(h2max(__byte_perm(x0, x1, 0x5410), __byte_perm(x0, x1, 0x7632)), t);
    mx = h2max(mx, shfl_x(mx, 1));
    mx = h2max(mx, shfl_x(mx, 2));
#pragma unroll
    for (int j = 0; j < 6; j++) { s[2 * j] = h2sub(s[2 * j], lo2(mx)); s[2 * j + 1] = h2sub(s[2 * j + 1], hi2(mx)); }
    t = h2sub(t, mx);
    if (is_wide(F)) {
      const uint32_t cs = score_scale(&g_par.cS_s);
#pragma unroll
      for (int j = 0; j < 12; j++) s[j] = h2mul(s[j], cs);
      t = h2mul(t, cs);
      const float s0 = stat_f32(F.e0).x, s1 = stat_f32(F.e1).x;
      const float kb = __ldcg(&g_par.kb), ik = rcp_fast(__ldcg(&g_par.kappa));
      e.x = fmaxf(s0, kb); e.y = fmaxf(s1, kb);
      const uint32_t aw = pack_h2(__fdividef(s0, e.x), __fdividef(s1, e.y));
      e.x *= ik; e.y *= ik;
#pragma unroll
      for (int j = 0; j < 12; j++) { v[2 * j] = h2mul(v[2 * j], lo2(aw)); v[2 * j + 1] = h2mul(v[2 * j + 1], hi2(aw)); }
    }
#pragma unroll
    for (int j = 0; j < NSP; j++) sp[j] = h2ex2(s[j]);
  }
#pragma unroll
  for (int j = 0; j < 12; j++) s[j] = j < NSP ? sp[j] : h2ex2(s[j]);
  t = h2ex2(t);
  Quad q;
  q.v[0] = h2add(t, fold_add(h2add(h2add(h2add(s[0], s[2]), h2add(s[4], s[6])), h2add(s[8], s[10])),
                             h2add(h2add(h2add(s[1], s[3]), h2add(s[5], s[7])), h2add(s[9], s[11]))));
#pragma unroll
  for (int i = 1; i < 4; i++) q.v[i] = shfl_x(q.v[0], i);
  return q;
}
__device__ __forceinline__ void soft_norm(uint32_t (&s)[16], uint32_t& t, const Quad& q, const Frame& F, float2 e, uint32_t tid) {
  const float2 d = unpack_h2(h2add(h2add(q.v[0], q.v[1]), h2add(q.v[2], q.v[3])));
  const uint32_t cb = pack_h2(rcp_fast(d.x * e.x), rcp_fast(d.y * e.y)) & (sel(tid & 28, 0u, 0xffffu) | fresh(F.light ? 0u : 0xffffffffu));
#pragma unroll
  for (int j = 0; j < 6; j++) { s[2 * j] = h2mul(s[2 * j], lo2(cb)); s[2 * j + 1] = h2mul(s[2 * j + 1], hi2(cb)); }
  t = fresh(h2mul(t, cb));
  pin<12>(s);
}
__device__ __forceinline__ void soft_tail(uint32_t (&s)[16], uint32_t t) {
  s[12] = t & 0xffffu; s[13] = t >> 16;
  asm volatile("mov.b32 %0, 0;\nmov.b32 %1, 0;" : "=r"(s[14]), "=r"(s[15]));
}
template <int H>
__device__ __forceinline__ uint8_t* row_ptr(const Frame& F, uint8_t* o) {
  const uint32_t oo = fresh(F.oo);
  if (H) asm volatile("mad.wide.u32 %0, %1, 64, %0;" : "+l"(o) : "r"(oo >> 20));
  else { o += oo & 0xfffffu; asm volatile("" : "+l"(o)); }
  return o;
}
template <int H>
__device__ __forceinline__ void affine(uint32_t* r, const uint32_t (&v)[24], const Frame& F) {
  const uint32_t e = H ? F.e1 : F.e0;
#pragma unroll
  for (int j = 0; j < 12; j++) r[j] = h2fma(v[2 * j + H], lo2(e), hi2(e));
  pin<12>(r);
}
template <int H>
__device__ __forceinline__ void finish(uint32_t* r, const Frame& F, uint8_t*& o, uint32_t off, uint32_t a, uint32_t m, uint32_t& tid, uint32_t a2 = 0) {
  o = row_ptr<H>(F, o);
#pragma unroll
  for (int j = 0; j < 12; j += 2) { const float2 f = unpack_h2(r[j]), g = unpack_h2(r[j + 1]); r[j] = pack_bf2(f.x, g.x); r[j + 1] = pack_bf2(f.y, g.y); }
  pin<12>(r);
  if (SE) sfence(tid);
  stg3(o, r, off | (fresh(a) & m) | (a2 & 0x4000));
}
__device__ __forceinline__ void finish_wide(const uint32_t (&v)[24], const Frame& F, uint8_t* o, uint32_t tid) {
  const float kb = __ldcg(&g_par.kb);
#pragma unroll
  for (int h = 0; h < 2; h++) {
    const float2 z = stat_f32(h ? F.e1 : F.e0);
    const float w = fmaxf(z.x, kb);
    uint32_t r[12];
#pragma unroll
    for (int j = 0; j < 12; j += 2) {
      const float2 f = unpack_h2(v[2 * j + h]), g = unpack_h2(v[2 * j + 2 + h]);
      r[j] = pack_bf2(fmaf(f.x, w, z.y), fmaf(g.x, w, z.y)); r[j + 1] = pack_bf2(fmaf(f.y, w, z.y), fmaf(g.y, w, z.y));
    }
    o = h ? row_ptr<1>(F, o) : row_ptr<0>(F, o);
    stg3(o, r, F.light ? (h ? 1 : tid & 28) : 0);
  }
}
__device__ __forceinline__ uint32_t window_ahead(uint32_t ring, uint32_t i, uint32_t nfull, uint32_t w) {
  return i + 4 < nfull ? w + 4 * gridDim.x : i + 4 == nfull ? lds32(ring + kExtra) >> 2 : 0;
}

__device__ __forceinline__ void run_S(uint32_t ring, uint64_t d0, uint64_t d1, uint32_t frame, uint32_t nfull, uint32_t i0, uint32_t i1, uint32_t w, int sg, int wp, int lane,
                                      const CUtensorMap* tm, uint8_t* __restrict__ out) {
  Frame A, B;
  uint32_t tid = lane + (frame_init(A, ring, 2 * sg, wp, lane) << 4) + (frame_init(B, ring, 2 * sg + 1, wp, lane) << 16);
  uint32_t va[24], vb[24], x[24], sa[16], sc[16], r0[12], r1[12], ta, tb;
  Quad rs;
  float2 e;
#pragma unroll
  for (int j = 0; j < 24; j++) { vb[j] = 0; x[j] = 0; }
  out += sg * 2 * frame;
  uint8_t *ob = out, *o;
  const uint64_t dr = d0 + (uint32_t)(kWBytes / 16 + sg * (2 * kPlane / 16));
  uint32_t i = i0, slot = ring + (i & 3) * kSlot;
  mbar_wait(slot + kDone, i >> 2);
  load_frame<false>(va, (tid >> 4) & 0xfff0u, slot, tid);
  do {
    const uint32_t ia = i & 3;
    gemm<2, kOffAs, 6144>(x, va, d0);
    FS(0);
    const uint32_t wb = is_wide(B);
    if (wb && i != i0) finish_wide(vb, B, ob + frame, tid);
    affine<0>(r0, vb, B); affine<1>(r1, vb, B);
    const uint32_t lb = (tid >> 16) & 0xfff0u;
    load_frame<true>(vb, lb, slot, tid);
    const uint32_t g4 = load_stats(A, ia, tid);
    uint64_t dp = dr + ia * (kSlot / 16);
    asm volatile("" : "+l"(dp));
    FS(1);
    o = ob + frame;
    finish<0>(r0, B, o, wb, g4, B.light ? 28 : 0, tid, KA ? lb : 0);
    FS(2);
    wg_wait(); pin<24>(x); if (TM & 1) launder<24>(x);
    gemm<0, 0, kChunk>(sa, x, dp);
    if (!B.light) finish<1>(r1, B, o, wb, 0, 0, tid);
    else if (sg == 0) {
      if ((tid & 31) == 0) {
        const uint32_t wn = window_ahead(ring, i, nfull, w);
        if (wn) tma_prefetch_win(tm, wn);
      }
      __syncwarp();
    }
    ob = out + (size_t)((((w * 57457u) >> 22) * (7 * kW - 7 * kNWX) + w * 7) * 192u);
    FS(3);
    wg_wait(); pin<14>(sa);
    gemm<2, kOffAs, 6144>(x, vb, d1);
    FS(4);
    ta = key48(sa, tid);
    rs = soft_exp(sa, ta, va, A, e);
    FS(5);
    wg_wait(); pin<24>(x); if (TM & 2) launder<24>(x);
    gemm<0, kPlane, kChunk>(sc, x, dp);
    FS(6);
    load_stats(B, ia, tid);
    soft_norm(sa, ta, rs, A, e, tid);
    FS(7);
    wg_wait(); pin<14>(sc);
    tb = key48(sc, tid);
    sfence(tid);
    soft_tail(sa, ta);
    gemm_u<0>(x, sa, dp);
    FS(8);
    rs = soft_exp(sc, tb, vb, B, e);
    FS(9);
    wg_wait(); pin<24>(x); if (TM & 4) launder<24>(x);
    gemm<1, kOffWs, 6144>(va, x, d0);
    FS(10);
    soft_norm(sc, tb, rs, B, e, tid);
    soft_tail(sc, tb);
    const uint32_t wa = is_wide(A);
    FS(11);
    wg_wait(); pin<24>(va);
    gemm_u<kPlane>(x, sc, dp);
    FS(12);
    const uint32_t sn = ring + ((i + 1) & 3) * kSlot;
    const bool slow = mbar_pending_or(sn + kDone, (i + 1) >> 2, wa | A.light);
    affine<0>(r0, va, A);
    o = ob;
    finish<0>(r0, A, o, wa, tid, A.light ? 28 : 0, tid);
    FS(13);
    wg_wait(); pin<24>(x); if (TM & 8) launder<24>(x);
    gemm<1, kOffWs, 6144>(vb, x, d1);
    FS(14);
    affine<1>(r1, va, A);
    if (wp == 2) TR(i + 1, 4 + 2 * sg);
    if (slow) {
      if (A.light) {
        if ((tid & 31) == 0) {
          uint32_t old;
          asm volatile("atom.relaxed.cta.shared::cta.inc.u32 %0, [%1], 1;" : "=r"(old) : "r"(slot + kRel) : "memory");
          if (old) {
            const uint32_t wn = window_ahead(ring, i, nfull, w);
            if (wn) tma_load_win(slot, tm, wn);
            else mbar_arrive(slot + kFull);
          }
        }
        __syncwarp();
      }
      if (wa) finish_wide(va, A, ob, tid);
      if (i + 1 < i1) mbar_wait(sn + kDone, (i + 1) >> 2);
    }
    if (wp == 2) TR(i + 1, 5 + 2 * sg);
    const uint32_t la = (tid >> 4) & 0xfff0u;
    load_frame<LF>(va, la, sn, tid);
    if (!A.light) finish<1>(r1, A, o, wa, la, 0x4000, tid);
    wg_wait(); pin<24>(vb);
    launder<24>(vb);
    launder<24>(va);
    slot = sn; w += gridDim.x;
  } while (++i < i1);
  const uint32_t wb = is_wide(B);
  if (wb) finish_wide(vb, B, ob + frame, tid);
  o = ob + frame;
  affine<0>(r0, vb, B); finish<0>(r0, B, o, wb, tid, B.light ? 28 : 0, tid);
  affine<1>(r1, vb, B); finish<1>(r1, B, o, B.light | wb, 0, 0, tid);
}

__global__ void __launch_bounds__(512, 1) swin_main(const __grid_constant__ CUtensorMap tm, uint8_t* __restrict__ out, const uint64_t d0,
                                                    const uint64_t d1, const uint32_t frame) {
  extern __shared__ __align__(1024) uint8_t smem[];
  const uint32_t sb = CB ? 1024u : smem_u32(smem), ring = sb + kWBytes;
  const int tid = threadIdx.x;
  const int wg = __shfl_sync(0xffffffffu, tid >> 7, 0);
  const int wp = __shfl_sync(0xffffffffu, (tid >> 5) & 3, 0);
  const int lane = tid & 31;
  const uint32_t b = blockIdx.x, nb = gridDim.x;
  const uint32_t nfull = kNWIN / nb, nrem = kNWIN - nfull * nb;
  if (tid == 0) {
    if (smem_u32(smem) != 1024 || nfull > 700 || nfull < 12) __trap();
#pragma unroll
    for (int i = 0; i < 4; i++) {
      mbar_init(ring + i * kSlot + kFull, 1);
      mbar_init(ring + i * kSlot + kDone, 49);
      sts32(ring + i * kSlot + kRel, 0); sts32(ring + i * kSlot + kFlag, 0);
    }
    asm volatile("fence.mbarrier_init.release.cluster;" ::: "memory");
    for (int i = 0; i < 2; i++) tma_load_win(ring + i * kSlot, &tm, b + i * nb);
  }
  __syncwarp();
  if (wg == 1 || wg == 2)
    asm volatile("st.shared.v4.b32 [%0], {%1,%1,%1,%1};" ::"r"(ring + ((tid - 128) >> 6) * kSlot + kXBytes + (tid & 63) * 16), "r"(0) : "memory");
  __syncthreads();
  asm volatile("griddepcontrol.wait;" ::: "memory");
#pragma unroll
  for (int q = 0; q < kWBytes / 16 / 512; q++)
    asm volatile("cp.async.cg.shared.global [%0], [%1], 16;" ::"r"(sb + (tid + q * 512) * 16), "l"(g_wimg + tid + q * 512) : "memory");
  if (wg == 0 && wp < 3) {
    static_assert(kWBytes / 16 == 9 * 512 + 96, "weight copy split");
    const int e = tid + 9 * 512;
    asm volatile("cp.async.cg.shared.global [%0], [%1], 16;" ::"r"(sb + e * 16), "l"(g_wimg + e) : "memory");
  }
  const float4 p0 = __ldcg(reinterpret_cast<const float4*>(&g_par));
  const float kb = __ldcg(&g_par.kb);
  TPar P;
  P.kt = p0.z;
  P.sgmin = p0.y != 1.f || p0.w != 1.f ? 1e30f : fmaxf(0.0045f, kb * 0.011f);
  P.outmax = fmaf(kb, -627.2f, 60000.f);
  const bool scaled = __any_sync(0xffffffffu, p0.x != 1.f);
  const bool direct = __all_sync(0xffffffffu, !scaled && P.kt <= 256.f);
  asm volatile("cp.async.wait_all;\nfence.proxy.async.shared::cta;" ::: "memory");
  __syncthreads();
  if (tid == 128) for (int i = 2; i < 4; i++) tma_load_win(ring + i * kSlot, &tm, b + i * nb);
  __syncwarp();
  const bool isT = wg < 2;
  run_T(ring, d0, d1, nfull, nrem, !isT, wg, wp, lane, P, scaled, direct);
  const uint32_t ex = isT ? __shfl_sync(0xffffffffu, lds32(ring + kExtra), 0) : 3;
  if ((ex >> (wg & 1)) & 1) run_S(ring, d0, d1, frame, nfull, isT ? nfull : 0, nfull + isT, isT ? ex >> 2 : b, wg & 1, wp, lane, &tm, out);
}

__device__ __forceinline__ int ch_pos(int ch) { return 32 * (ch >> 5) + 16 * ((ch >> 2) & 1) + 8 * (ch & 1) + 2 * ((ch >> 3) & 3) + ((ch >> 1) & 1); }
__device__ __forceinline__ float pow2_ceil(float v) {
  return __uint_as_float((__float_as_uint(v) + 0x7fffffu) & 0x7f800000u);
}

constexpr int kPrepSplit = 12;
constexpr int kPrepThreads = 384;
__global__ void __launch_bounds__(kPrepThreads) swin_prep(const __nv_bfloat16* __restrict__ wqkv_t, const __nv_bfloat16* __restrict__ wo_t,
                                                          const __nv_bfloat16* __restrict__ wqkv_s, const __nv_bfloat16* __restrict__ wo_s) {
  asm volatile("griddepcontrol.launch_dependents;");
  __shared__ __align__(16) uint32_t raw[2][96][52];
  __shared__ __align__(16) uint32_t mu[3][52];
  __shared__ float nrm[12], nrm2[6], csum[6][9];
  const int mat = blockIdx.x / kPrepSplit, blk = blockIdx.x % kPrepSplit;
  const int tid = threadIdx.x, lane = tid & 31, warp = tid >> 5, g = lane >> 2, c = lane & 3;
  const __nv_bfloat16* wqkv = mat < 2 ? wqkv_t : wqkv_s;
  const __nv_bfloat16* wo = mat < 2 ? wo_t : wo_s;
  const bool isA = (mat & 1) == 0;
  {
    uint4 v[3], u[3];
#pragma unroll
    for (int q = 0; q < 3; q++) {
      const int e = tid + q * kPrepThreads, i = e / 12, c8 = (e % 12) * 8;
      v[q] = __ldg(reinterpret_cast<const uint4*>(wqkv + i * 288 + (isA ? 0 : 192) + c8));
      u[q] = __ldg(reinterpret_cast<const uint4*>(isA ? wqkv + i * 288 + 96 + c8 : wo + i * 96 + c8));
    }
#pragma unroll
    for (int q = 0; q < 3; q++) {
      const int e = tid + q * kPrepThreads, i = e / 12, c4 = (e % 12) * 4;
      *reinterpret_cast<uint4*>(&raw[0][i][c4]) = v[q];
      *reinterpret_cast<uint4*>(&raw[1][i][c4]) = u[q];
    }
  }
  __syncthreads();
  {
    const int m = warp / 6, cp = (warp % 6) * 8 + g;
    float s0 = 0.f, s1 = 0.f, q0 = 0.f, q1 = 0.f;
#pragma unroll
    for (int i = 0; i < 24; i++) {
      const uint32_t w = raw[m][4 * i + c][cp];
      const float lo = __uint_as_float(w << 16), hi = __uint_as_float(w & 0xffff0000u);
      s0 += lo; s1 += hi; q0 = fmaf(lo, lo, q0); q1 = fmaf(hi, hi, q1);
    }
    s0 = quad_sum(s0) * (1.f / 96.f); s1 = quad_sum(s1) * (1.f / 96.f); q0 = quad_sum(q0); q1 = quad_sum(q1);
    if (mat == 1 && m == 1) {
      float r0 = 0.f, r1 = 0.f;
#pragma unroll
      for (int i = 0; i < 12; i++) {
        const uint32_t w0 = raw[1][2 * cp][4 * i + c], w1 = raw[1][2 * cp + 1][4 * i + c];
        r0 += __uint_as_float(w0 << 16) + __uint_as_float(w0 & 0xffff0000u);
        r1 += __uint_as_float(w1 << 16) + __uint_as_float(w1 & 0xffff0000u);
      }
      r0 = quad_sum(r0) * (1.f / 96.f); r1 = quad_sum(r1) * (1.f / 96.f);
      s0 = r0; s1 = r1;
    }
    if (m == 1 && c == 0) {
      const uint32_t hi = mat == 3 ? 0u : pack_bf2(s0, s1);
      mu[0][cp] = hi;
      mu[1][cp] = mat == 3 ? 0u : pack_bf2(s0 - __uint_as_float(hi << 16), s1 - __uint_as_float(hi & 0xffff0000u));
      mu[2][cp] = 0u;
    }
    if (m == 0 || isA) {
      q0 = fmaxf(fmaf(-96.f * s0, s0, q0), 0.f) + q0 * 1e-6f;
      q1 = fmaxf(fmaf(-96.f * s1, s1, q1), 0.f) + q1 * 1e-6f;
    }
    const bool usemax = m == 1 && mat == 3;
    float t = usemax ? fmaxf(q0, q1) : q0 + q1;
#pragma unroll
    for (int o = 4; o < 32; o <<= 1) { const float z = __shfl_xor_sync(0xffffffffu, t, o); t = usemax ? fmaxf(t, z) : t + z; }
    if (lane == 0) nrm[warp] = t;
  }
  __syncthreads();
  if (warp >= 6) return;
  float d[4] = {0.f, 0.f, 0.f, 0.f}, e[4] = {0.f, 0.f, 0.f, 0.f}, v0, v1;
  {
    const uint32_t arow = smem_u32(&raw[0][16 * warp + (lane & 15)][(lane >> 4) * 4]);
    const uint32_t brow = isA ? smem_u32(&raw[1][blk * 8 + (lane & 7)][(lane >> 3) * 4]) : smem_u32(&raw[1][lane][blk * 4]);
    const uint32_t mrow = smem_u32(&mu[min(lane & 7, 2)][(lane >> 3) * 4]);
#pragma unroll
    for (int k2 = 0; k2 < 3; k2++) {
      uint32_t b[4], m[4];
      if (isA) ldsm4(b, brow + k2 * 64);
      else asm volatile("ldmatrix.sync.aligned.m8n8.x4.trans.shared.b16 {%0,%1,%2,%3}, [%4];"
                        : "=r"(b[0]), "=r"(b[1]), "=r"(b[2]), "=r"(b[3]) : "r"(brow + k2 * (32 * 208)) : "memory");
      ldsm4(m, mrow + k2 * 64);
#pragma unroll
      for (int hf = 0; hf < 2; hf++) {
        uint32_t a[4];
        ldsm4(a, arow + (2 * k2 + hf) * 32);
        asm volatile("mma.sync.aligned.m16n8k16.row.col.f32.bf16.bf16.f32 {%0,%1,%2,%3},{%4,%5,%6,%7},{%8,%9},{%0,%1,%2,%3};"
                     : "+f"(d[0]), "+f"(d[1]), "+f"(d[2]), "+f"(d[3])
                     : "r"(a[0]), "r"(a[1]), "r"(a[2]), "r"(a[3]), "r"(b[2 * hf]), "r"(b[2 * hf + 1]));
        asm volatile("mma.sync.aligned.m16n8k16.row.col.f32.bf16.bf16.f32 {%0,%1,%2,%3},{%4,%5,%6,%7},{%8,%9},{%0,%1,%2,%3};"
                     : "+f"(e[0]), "+f"(e[1]), "+f"(e[2]), "+f"(e[3])
                     : "r"(a[0]), "r"(a[1]), "r"(a[2]), "r"(a[3]), "r"(m[2 * hf]), "r"(m[2 * hf + 1]));
      }
    }
    v0 = __shfl_sync(0xffffffffu, e[0] + e[1], lane & ~3); v1 = __shfl_sync(0xffffffffu, e[2] + e[3], lane & ~3);
    d[0] -= v0; d[1] -= v0; d[2] -= v1; d[3] -= v1;
    float t0 = d[0] + d[2], t1 = d[1] + d[3], t2 = v0 + v1;
#pragma unroll
    for (int o = 4; o < 32; o <<= 1) {
      t0 += __shfl_xor_sync(0xffffffffu, t0, o); t1 += __shfl_xor_sync(0xffffffffu, t1, o); t2 += __shfl_xor_sync(0xffffffffu, t2, o);
    }
    if (g == 0) { csum[warp][2 * c] = t0; csum[warp][2 * c + 1] = t1; csum[warp][8] = t2; }
  }
  const float nl = nrm[0] + nrm[1] + nrm[2] + nrm[3] + nrm[4] + nrm[5];
  const float nr = mat == 3 ? fmaxf(fmaxf(fmaxf(nrm[6], nrm[7]), fmaxf(nrm[8], nrm[9])), fmaxf(nrm[10], nrm[11]))
                            : nrm[6] + nrm[7] + nrm[8] + nrm[9] + nrm[10] + nrm[11];
  const float bound = __fsqrt_rn(nl) * __fsqrt_rn(nr) * 1.01f;
  const float f = isA ? 0.14724448f : 1.f;
  float sc = pow2_ceil(fmaxf(bound * (isA ? 0.14724448f / 160.f : mat == 1 ? 1.f / 16.f : 1.f / 64.f), 1e-30f));
  if (isA) sc = fminf(fmaxf(sc, 1.f), 32768.f);
  if (mat == 3) {
    if (blk == 0 && tid == 0) { g_par.kb = sc; g_par.ticket = 0; }
    if (sc <= 1.f && sc >= 1.f / 1024.f) sc = 1.f;
  }
  const float mul = f * __uint_as_float(0x7f000000u - __float_as_uint(sc));
  if (blk == 0 && tid == 0) (mat == 0 ? g_par.cS_t : mat == 1 ? g_par.kt : mat == 2 ? g_par.cS_s : g_par.kappa) = sc;
  asm volatile("bar.sync 1, 192;" ::: "memory");
  float mean[2];
#pragma unroll
  for (int b = 0; b < 2; b++)
    mean[b] = (csum[0][2 * c + b] + csum[1][2 * c + b] + csum[2][2 * c + b] + csum[3][2 * c + b] + csum[4][2 * c + b] + csum[5][2 * c + b]) *
              (1.f / 96.f);
  uint8_t* img = reinterpret_cast<uint8_t*>(g_wimg) + (mat == 0 ? 0 : mat == 1 ? kOffWt : mat == 2 ? kOffAs : kOffWs);
  const float vmean = (csum[0][8] + csum[1][8] + csum[2][8] + csum[3][8] + csum[4][8] + csum[5][8]) * (1.f / 96.f);
  float off = 0.f;
  if (mat == 2) {
    float q2 = 0.f;
#pragma unroll
    for (int q = 0; q < 4; q++) q2 = fmaf(d[q] - mean[q & 1], d[q] - mean[q & 1], q2);
#pragma unroll
    for (int o = 16; o; o >>= 1) q2 += __shfl_xor_sync(0xffffffffu, q2, o);
    if (lane == 0) nrm2[warp] = q2;
    asm volatile("bar.sync 1, 192;" ::: "memory");
    q2 = nrm2[0] + nrm2[1] + nrm2[2] + nrm2[3] + nrm2[4] + nrm2[5];
    off = 1.5f * pow2_ceil(fmaxf(__fsqrt_rn(q2 * (1.f / 768.f)) * mul * 3.f, 1e-4f));
  }
#pragma unroll
  for (int q = 0; q < 4; q++) {
    const int kp = ch_pos(16 * warp + g + 8 * (q >> 1)), np = ch_pos(blk * 8 + 2 * c + (q & 1));
    const uint32_t ko = (kp >> 5) * (mat < 2 ? kAtChunk : 6144) + (kp & 31) * 2;
    uint32_t a = ko + np * 64;
    a ^= ((a >> 7) & 3) << 4;
    float o = (d[q] - mean[q & 1]) * mul;
    o = mat == 2 ? o + off : __uint_as_float((__float_as_uint(o) + 0x8000u) & 0xffff0000u);
    *reinterpret_cast<__half*>(img + a) = __float2half_rn(o);
    if (mat == 1 && blk == 0) {
      a = (kp >> 5) * kAtChunk + (kp & 31) * 2 + (96 + 2 * c + (q & 1)) * 64;
      a ^= ((a >> 7) & 3) << 4;
      *reinterpret_cast<__half*>(reinterpret_cast<uint8_t*>(g_wimg) + a) = __float2half_rn((q & 1) ? ((q >> 1 ? v1 : v0) - vmean) * mul : 1.f / 96.f);
    }
  }
}

typedef CUresult (*EncodeFn)(CUtensorMap*, CUtensorMapDataType, cuuint32_t, void*, const cuuint64_t*, const cuuint64_t*,
                             const cuuint32_t*, const cuuint32_t*, CUtensorMapInterleave, CUtensorMapSwizzle,
                             CUtensorMapL2promotion, CUtensorMapFloatOOBfill);

}

extern "C" void kernel_launch(void* const* d_in, const int* in_sizes, int n_in, void* d_out, int out_size) {
  (void)in_sizes; (void)n_in; (void)out_size;
  static EncodeFn enc = nullptr;
  static int nsm = 0;
  if (!enc) {
    void* fn = nullptr;
    cudaDriverEntryPointQueryResult qr;
    cudaGetDriverEntryPoint("cuTensorMapEncodeTiled", &fn, cudaEnableDefault, &qr);
    enc = reinterpret_cast<EncodeFn>(fn);
    int dev = 0;
    cudaGetDevice(&dev);
    cudaDeviceGetAttribute(&nsm, cudaDevAttrMultiProcessorCount, dev);
    cudaFuncSetAttribute(swin_main, cudaFuncAttributeMaxDynamicSharedMemorySize, kSmemBytes);
  }
  CUtensorMap tm;
  const cuuint64_t dims[5] = {32, kW, kH, kT, 3};
  const cuuint64_t strides[4] = {192, 192ull * kW, 192ull * kW * kH, 64};
  const cuuint32_t box[5] = {32, 7, 7, 4, 3};
  const cuuint32_t es[5] = {1, 1, 1, 1, 1};
  enc(&tm, CU_TENSOR_MAP_DATA_TYPE_BFLOAT16, 5, d_in[0], dims, strides, box, es, CU_TENSOR_MAP_INTERLEAVE_NONE,
      CU_TENSOR_MAP_SWIZZLE_64B, CU_TENSOR_MAP_L2_PROMOTION_L2_128B, CU_TENSOR_MAP_FLOAT_OOB_FILL_NONE);

  cudaStream_t st = cudaStreamPerThread;
  swin_prep<<<4 * kPrepSplit, kPrepThreads, 0, st>>>(
      static_cast<const __nv_bfloat16*>(d_in[1]), static_cast<const __nv_bfloat16*>(d_in[2]),
      static_cast<const __nv_bfloat16*>(d_in[3]), static_cast<const __nv_bfloat16*>(d_in[4]));

  cudaLaunchConfig_t cfg = {};
  cfg.gridDim = dim3(nsm);
  cfg.blockDim = dim3(512);
  cfg.dynamicSmemBytes = kSmemBytes;
  cfg.stream = st;
  cudaLaunchAttribute at[1];
  at[0].id = cudaLaunchAttributeProgrammaticStreamSerialization;
  at[0].val.programmaticStreamSerializationAllowed = 1;
  cfg.attrs = at;
  cfg.numAttrs = 1;
  cudaLaunchKernelEx(&cfg, swin_main, tm, static_cast<uint8_t*>(d_out), mk_desc(1024), mk_desc(1024), (uint32_t)(kH * kW * 192));
}
```

```cpp
#include <cuda_runtime.h>
#include <cuda.h>
#include <cuda_bf16.h>
#include <cuda_fp16.h>
#include <stdint.h>

namespace {

constexpr int kH = 511, kW = 511, kT = 4;
constexpr int kNWX = 73, kNWIN = 73 * 73;
constexpr int kChunk = 12544;
constexpr int kPlane = 3136;
constexpr int kXBytes = 37632;
constexpr int kZero = kXBytes + 896, kFull = kXBytes + 1024, kDone = kFull + 8, kRel = kFull + 16, kFlag = kFull + 20, kExtra = kFull + 24;
constexpr int kSlot = 38912;
constexpr int kWMat = 18432;
constexpr int kAtChunk = 200 * 64;
constexpr int kOffWt = 104 * 64;
constexpr int kOffAs = 3 * kAtChunk, kOffWs = kOffAs + kWMat;
constexpr int kWBytes = kOffWs + kWMat;
constexpr int kSmemBytes = kWBytes + 4 * kSlot;

struct Params {
  float cS_t, cS_s;
  float kt;
  float kappa;
  float kb;
  uint32_t ticket;
};

__device__ uint4 g_wimg[kWBytes / 16];
__device__ __align__(16) Params g_par;
#define TR(i, k)
#define GT 254
#define GS 0x7eec
#define FT(k) do { if ((GT >> (k)) & 1) sfence(lane); } while (0)
#define FS(k) do { if ((GS >> (k)) & 1) sfence(tid); } while (0)
#define DB 0
#define KA 0
#define LF 0
#define SG 1
#define GO 0
#define TM 0
#define SE 1
#define CB 0
#define NSP 4
#define L2P 1
#define DYN 1
#define NWH 8
#define MBHINT ""

__device__ __forceinline__ uint32_t smem_u32(const void* p) { return (uint32_t)__cvta_generic_to_shared(p); }
__device__ __forceinline__ void mbar_init(uint32_t a, int c) { asm volatile("mbarrier.init.shared::cta.b64 [%0], %1;" ::"r"(a), "r"(c)); }
__device__ __forceinline__ void mbar_expect(uint32_t a, int bytes) {
  asm volatile("mbarrier.arrive.expect_tx.shared::cta.b64 _, [%0], %1;" ::"r"(a), "r"(bytes) : "memory");
}
__device__ __forceinline__ void mbar_arrive(uint32_t a, uint32_t off = 0) {
  asm volatile("{\n.reg .pred p;\nsetp.eq.u32 p, %1, 0;\n@p mbarrier.arrive.shared::cta.b64 _, [%0];\n}" ::"r"(a), "r"(off) : "memory");
}
__device__ __forceinline__ void mbar_wait(uint32_t a, uint32_t par) {
  asm volatile(
      "{\n.reg .pred p;\n.reg .u32 n;\n"
      "mbarrier.try_wait.parity.shared::cta.b64 p, [%0], %1" MBHINT ";\n"
      "@p bra.uni WDONE;\n"
      "mov.u32 n, 0;\n"
      "WLOOP:\n"
      "mbarrier.try_wait.parity.shared::cta.b64 p, [%0], %1" MBHINT ";\n"
      "@p bra.uni WDONE;\n"
      "add.u32 n, n, 1;\n"
      "setp.lt.u32 p, n, 0x100000;\n"
      "@p bra.uni WLOOP;\n"
      "trap;\n"
      "WDONE:\n}" ::"r"(a), "r"(par & 1) : "memory");
}
__device__ __forceinline__ bool mbar_pending_or(uint32_t a, uint32_t par, uint32_t c) {
  uint32_t r;
  asm volatile("{\n.reg .pred p;\nmbarrier.test_wait.parity.shared::cta.b64 p, [%1], %2;\nsetp.ne.or.u32 p, %3, 0, !p;\n"
               "vote.sync.any.pred p, p, 0xffffffff;\nselp.b32 %0, 1, 0, p;\n}" : "=r"(r) : "r"(a), "r"(par & 1), "r"(c) : "memory");
  return r;
}
__device__ __forceinline__ uint32_t lds32(uint32_t a) {
  uint32_t v; asm volatile("ld.shared.b32 %0, [%1];" : "=r"(v) : "r"(a) : "memory"); return v;
}
__device__ __forceinline__ void sts32(uint32_t a, uint32_t v) { asm volatile("st.shared.b32 [%0], %1;" ::"r"(a), "r"(v) : "memory"); }
__device__ __forceinline__ void tma_load_win(uint32_t slot, const CUtensorMap* m, uint32_t w) {
  const uint32_t wy = (w * 57457u) >> 22, wx = w - wy * kNWX;
  mbar_expect(slot + kFull, kXBytes);
  asm volatile(
      "cp.async.bulk.tensor.5d.shared::cluster.global.mbarrier::complete_tx::bytes [%0], [%1, {%3,%4,%5,%3,%3}], [%2];" ::"r"(slot),
      "l"(m), "r"(slot + kFull), "r"(0), "r"(wx * 7), "r"(wy * 7)
      : "memory");
}
__device__ __forceinline__ void tma_prefetch_win(const CUtensorMap* m, uint32_t w) {
  const uint32_t wy = (w * 57457u) >> 22, wx = w - wy * kNWX;
  asm volatile("cp.async.bulk.prefetch.tensor.5d.L2.global [%0, {%1,%2,%3,%1,%1}];" ::"l"(m), "r"(0), "r"(wx * 7), "r"(wy * 7) : "memory");
}
__device__ __forceinline__ void wg_fence() { asm volatile("wgmma.fence.sync.aligned;" ::: "memory"); }
__device__ __forceinline__ void wg_commit() { asm volatile("wgmma.commit_group.sync.aligned;" ::: "memory"); }
__device__ __forceinline__ void wg_wait() { asm volatile("wgmma.wait_group.sync.aligned 0;" ::: "memory"); }
template <int N>
__device__ __forceinline__ void pin(uint32_t* d) {
#pragma unroll
  for (int i = 0; i < N; i++) asm volatile("" : "+r"(d[i])::"memory");
}
__device__ __forceinline__ uint32_t fresh(uint32_t v) { asm volatile("" : "+r"(v)); return v; }
__device__ __forceinline__ float fresh(float v) { asm volatile("" : "+f"(v)); return v; }
template <int N>
__device__ __forceinline__ void launder(uint32_t* q) {
#pragma unroll
  for (int j = 0; j < N; j++) { uint32_t t; asm volatile("mov.b32 %0, %1;" : "=r"(t) : "r"(q[j])); q[j] = t; }
}
__device__ __forceinline__ void sfence(uint32_t& v) {
  asm volatile("{\n.reg .pred p;\nsetp.eq.u32 p, %1, 0x7fffffff;\n@p mov.u32 %0, %%clock;\n}" : "+r"(v) : "r"(gridDim.x) : "memory");
}
constexpr uint64_t mk_desc(uint32_t addr) { return ((uint64_t)0x80000020u << 32) | (addr >> 4) | (1u << 16); }

#define R4(d, i) "+r"(d[i]), "+r"(d[i + 1]), "+r"(d[i + 2]), "+r"(d[i + 3])
#define O4(d, i) "=r"(d[i]), "=r"(d[i + 1]), "=r"(d[i + 2]), "=r"(d[i + 3])
#define D26 "{%0,%1,%2,%3,%4,%5,%6,%7,%8,%9,%10,%11,%12,%13,%14,%15,%16,%17,%18,%19,%20,%21,%22,%23,%24,%25},"
#define D24 "{%0,%1,%2,%3,%4,%5,%6,%7,%8,%9,%10,%11,%12,%13,%14,%15,%16,%17,%18,%19,%20,%21,%22,%23},"
#define D14 "{%0,%1,%2,%3,%4,%5,%6,%7,%8,%9,%10,%11,%12,%13},"

template <int SC, int TB>
__device__ __forceinline__ void wgmma(uint32_t (&d)[24], const uint32_t* a, uint64_t db) {
  if (SC == 2)
    asm volatile("{\n.reg .pred p;\nsetp.eq.u32 p, %30, 0x7fffffff;\n"
                 "wgmma.mma_async.sync.aligned.m64n96k16.f16.f16.f16 " D24 "{%24,%25,%26,%27}, %28, p, 1, 1, %29;\n}"
                 : R4(d, 0), R4(d, 4), R4(d, 8), R4(d, 12), R4(d, 16), R4(d, 20)
                 : "r"(a[0]), "r"(a[1]), "r"(a[2]), "r"(a[3]), "l"(db), "n"(TB), "r"(gridDim.x));
  else if (SC)
    asm volatile("wgmma.mma_async.sync.aligned.m64n96k16.f16.f16.f16 " D24 "{%24,%25,%26,%27}, %28, 1, 1, 1, %29;"
                 : R4(d, 0), R4(d, 4), R4(d, 8), R4(d, 12), R4(d, 16), R4(d, 20)
                 : "r"(a[0]), "r"(a[1]), "r"(a[2]), "r"(a[3]), "l"(db), "n"(TB));
  else
    asm volatile("wgmma.mma_async.sync.aligned.m64n96k16.f16.f16.f16 " D24 "{%24,%25,%26,%27}, %28, 0, 1, 1, %29;"
                 : O4(d, 0), O4(d, 4), O4(d, 8), O4(d, 12), O4(d, 16), O4(d, 20)
                 : "r"(a[0]), "r"(a[1]), "r"(a[2]), "r"(a[3]), "l"(db), "n"(TB));
}
template <int SC, int TB>
__device__ __forceinline__ void wgmma(uint32_t (&d)[26], const uint32_t* a, uint64_t db) {
  if (SC)
    asm volatile("wgmma.mma_async.sync.aligned.m64n104k16.f16.f16.f16 " D26 "{%26,%27,%28,%29}, %30, 1, 1, 1, 0;"
                 : R4(d, 0), R4(d, 4), R4(d, 8), R4(d, 12), R4(d, 16), R4(d, 20), "+r"(d[24]), "+r"(d[25])
                 : "r"(a[0]), "r"(a[1]), "r"(a[2]), "r"(a[3]), "l"(db));
  else
    asm volatile("wgmma.mma_async.sync.aligned.m64n104k16.f16.f16.f16 " D26 "{%26,%27,%28,%29}, %30, 0, 1, 1, 0;"
                 : O4(d, 0), O4(d, 4), O4(d, 8), O4(d, 12), O4(d, 16), O4(d, 20), "=r"(d[24]), "=r"(d[25])
                 : "r"(a[0]), "r"(a[1]), "r"(a[2]), "r"(a[3]), "l"(db));
}
template <int SC, int TB>
__device__ __forceinline__ void wgmma(uint32_t (&d)[16], const uint32_t* a, uint64_t db) {
  if (SC)
    asm volatile("wgmma.mma_async.sync.aligned.m64n56k16.f16.f16.f16 " D14 "{%14,%15,%16,%17}, %18, 1, 1, 1, 0;"
                 : R4(d, 0), R4(d, 4), R4(d, 8), "+r"(d[12]), "+r"(d[13])
                 : "r"(a[0]), "r"(a[1]), "r"(a[2]), "r"(a[3]), "l"(db));
  else
    asm volatile("wgmma.mma_async.sync.aligned.m64n56k16.f16.f16.f16 " D14 "{%14,%15,%16,%17}, %18, 0, 1, 1, 0;"
                 : O4(d, 0), O4(d, 4), O4(d, 8), "=r"(d[12]), "=r"(d[13])
                 : "r"(a[0]), "r"(a[1]), "r"(a[2]), "r"(a[3]), "l"(db));
}
template <int SC, int OFF, int CH, int ND>
__device__ __forceinline__ void gemm(uint32_t (&d)[ND], const uint32_t* a, uint64_t db) {
  asm volatile("" : "+l"(db));
  wg_fence();
  wgmma<SC, 0>(d, a, db + OFF / 16);
#pragma unroll
  for (int k = 1; k < 6; k++) wgmma<1, 0>(d, a + 4 * k, db + (OFF + (k >> 1) * CH + (k & 1) * 32) / 16);
  wg_commit();
}
__device__ __forceinline__ void lds128(uint32_t* r, uint32_t a) {
  asm volatile("ld.shared.v4.b32 {%0,%1,%2,%3}, [%4];" : "=r"(r[0]), "=r"(r[1]), "=r"(r[2]), "=r"(r[3]) : "r"(a) : "memory");
}
__device__ __forceinline__ void ldsm4(uint32_t* r, uint32_t a) {
  asm volatile("ldmatrix.sync.aligned.m8n8.x4.shared.b16 {%0,%1,%2,%3}, [%4];"
               : "=r"(r[0]), "=r"(r[1]), "=r"(r[2]), "=r"(r[3]) : "r"(a) : "memory");
}
__device__ __forceinline__ void stsm4(uint32_t a, const uint32_t* r) {
  asm volatile("stmatrix.sync.aligned.m8n8.x4.shared.b16 [%0], {%1,%2,%3,%4};" ::"r"(a), "r"(r[0]), "r"(r[1]), "r"(r[2]), "r"(r[3])
               : "memory");
}
__device__ __forceinline__ void stg3(uint8_t* p, const uint32_t* r, uint32_t off) {
  asm volatile("{\n.reg .pred p;\nsetp.eq.u32 p, %13, 0;\n@p st.global.v4.b32 [%0], {%1,%2,%3,%4};\n"
               "@p st.global.v4.b32 [%0+64], {%5,%6,%7,%8};\n@p st.global.v4.b32 [%0+128], {%9,%10,%11,%12};\n}" ::"l"(p),
               "r"(r[0]), "r"(r[1]), "r"(r[2]), "r"(r[3]), "r"(r[4]), "r"(r[5]), "r"(r[6]), "r"(r[7]), "r"(r[8]), "r"(r[9]), "r"(r[10]), "r"(r[11]),
               "r"(off) : "memory");
}
__device__ __forceinline__ uint32_t pack_h2(float lo, float hi) {
  uint32_t r; asm("cvt.rn.f16x2.f32 %0, %1, %2;" : "=r"(r) : "f"(hi), "f"(lo)); return r;
}
__device__ __forceinline__ uint32_t pack_h2_sat(float lo, float hi) {
  uint32_t r; asm("cvt.rn.satfinite.f16x2.f32 %0, %1, %2;" : "=r"(r) : "f"(hi), "f"(lo)); return r;
}
__device__ __forceinline__ uint32_t pack_bf2(float lo, float hi) {
  uint32_t r; asm("cvt.rn.bf16x2.f32 %0, %1, %2;" : "=r"(r) : "f"(hi), "f"(lo)); return r;
}
__device__ __forceinline__ __half2 as_h2(uint32_t v) { return *reinterpret_cast<__half2*>(&v); }
__device__ __forceinline__ uint32_t as_u(__half2 v) { return *reinterpret_cast<uint32_t*>(&v); }
__device__ __forceinline__ float2 unpack_h2(uint32_t v) { return __half22float2(as_h2(v)); }
__device__ __forceinline__ float low_f(uint32_t v) { return __low2float(as_h2(v)); }
__device__ __forceinline__ uint32_t h2ex2(uint32_t v) { uint32_t r; asm("ex2.approx.f16x2 %0, %1;" : "=r"(r) : "r"(v)); return r; }
__device__ __forceinline__ uint32_t h2max(uint32_t a, uint32_t b) { return as_u(__hmax2(as_h2(a), as_h2(b))); }
__device__ __forceinline__ uint32_t h2add(uint32_t a, uint32_t b) { return as_u(__hadd2(as_h2(a), as_h2(b))); }
__device__ __forceinline__ uint32_t h2sub(uint32_t a, uint32_t b) { return as_u(__hsub2(as_h2(a), as_h2(b))); }
__device__ __forceinline__ uint32_t h2mul(uint32_t a, uint32_t b) { return as_u(__hmul2(as_h2(a), as_h2(b))); }
__device__ __forceinline__ uint32_t h2neg(uint32_t a) { return as_u(__hneg2(as_h2(a))); }
__device__ __forceinline__ uint32_t h2fma(uint32_t a, uint32_t b, uint32_t c) { return as_u(__hfma2(as_h2(a), as_h2(b), as_h2(c))); }
__device__ __forceinline__ uint32_t lo2(uint32_t v) { return as_u(__low2half2(as_h2(v))); }
__device__ __forceinline__ uint32_t hi2(uint32_t v) { return as_u(__high2half2(as_h2(v))); }
__device__ __forceinline__ uint32_t fold_add(uint32_t a, uint32_t b) { return h2add(__byte_perm(a, b, 0x5410), __byte_perm(a, b, 0x7632)); }
__device__ __forceinline__ uint32_t sel(uint32_t p, uint32_t a, uint32_t b) {
  uint32_t r; asm("{\n.reg .pred p;\nsetp.ne.u32 p, %3, 0;\nselp.b32 %0, %1, %2, p;\n}" : "=r"(r) : "r"(a), "r"(b), "r"(p)); return r;
}
__device__ __forceinline__ float sel4(uint32_t c, float a0, float a1, float a2, float a3) {
  return __uint_as_float(sel(c & 2, sel(c & 1, __float_as_uint(a3), __float_as_uint(a2)), sel(c & 1, __float_as_uint(a1), __float_as_uint(a0))));
}
__device__ __forceinline__ float rcp_fast(float v) { float r; asm("rcp.approx.ftz.f32 %0, %1;" : "=f"(r) : "f"(v)); return r; }
__device__ __forceinline__ float rsq_fast(float v) { float r; asm("rsqrt.approx.ftz.f32 %0, %1;" : "=f"(r) : "f"(v)); return r; }
__device__ __forceinline__ uint32_t shfl_x(uint32_t v, int m) { return __shfl_xor_sync(0xffffffffu, v, m); }
__device__ __forceinline__ uint32_t shfl_q(uint32_t v, int i) { return __shfl_sync(0xffffffffu, v, i, 4); }
__device__ __forceinline__ float quad_sum(float v) {
  v += __shfl_xor_sync(0xffffffffu, v, 1);
  return v + __shfl_xor_sync(0xffffffffu, v, 2);
}
__device__ __forceinline__ uint32_t score_scale(const float* p) { const float v = __ldcg(p); return pack_h2(v, v); }

constexpr float kEps96 = 1e-5f * 96.f * 96.f;
__device__ __forceinline__ float2 stat_f32(uint32_t e) {
  const float2 h = unpack_h2(e);
  return make_float2(__uint_as_float(sel(e & 0x8000u, (e << 16) & 0x7fff0000u, __float_as_uint(h.x))),
                     __uint_as_float(sel(e & 0x8000u, e & 0xffff0000u, __float_as_uint(h.y))));
}

struct Tile {
  uint32_t a;
  uint32_t next;
  uint32_t n;
  int live;
  uint32_t stat, wrap;
  uint32_t flag;
  uint32_t gate;
};
struct TPar { float kt, sgmin, outmax; };

__device__ __forceinline__ void load_rows(uint32_t* x0, uint32_t* x1, uint32_t a0, uint32_t a1) {
  a0 ^= (a0 >> 3) & 0x30; a1 ^= (a1 >> 3) & 0x30;
  lds128(x0, a0); lds128(x1, a1);
  lds128(x0 + 4, (a0 ^ 32) + kChunk); lds128(x1 + 4, (a1 ^ 32) + kChunk);
  lds128(x0 + 8, a0 + 2 * kChunk); lds128(x1 + 8, a1 + 2 * kChunk);
}
__device__ __forceinline__ void to_half(uint32_t (&z)[24], const uint32_t* x) {
#pragma unroll
  for (int j = 0; j < 24; j += 2) {
    const int o = j < 12 ? 2 * j : 2 * j - 23;
    uint32_t t;
    asm("cvt.rz.f16x2.f32 %0, %1, %2;" : "=r"(t) : "f"(__uint_as_float(x[j + 1])), "f"(__uint_as_float(x[j])));
    z[o] = pack_h2(__uint_as_float(x[j] << 16), __uint_as_float(x[j + 1] << 16));
    z[o + 2] = t & 0xfff8fff8u;
  }
}
__device__ __forceinline__ void load_general(uint32_t (&z)[24], uint32_t a0, float& ie0, float& ie1, float& m0, float& m1) {
  float acc[48];
  uint32_t x0[12], x1[12];
  load_rows(x0, x1, a0, a0 + kPlane);
#pragma unroll
  for (int j = 0; j < 12; j++) {
    acc[4 * j] = __uint_as_float(x0[j] << 16); acc[4 * j + 1] = __uint_as_float(x0[j] & 0xffff0000u);
    acc[4 * j + 2] = __uint_as_float(x1[j] << 16); acc[4 * j + 3] = __uint_as_float(x1[j] & 0xffff0000u);
  }
  float s[4], q[4];
#pragma unroll
  for (int e = 0; e < 4; e++) { s[e] = acc[e]; q[e] = acc[e] * acc[e]; }
#pragma unroll
  for (int j = 4; j < 48; j++) { s[j & 3] += acc[j]; q[j & 3] = fmaf(acc[j], acc[j], q[j & 3]); }
  const float s0 = quad_sum(s[0] + s[1]), s1 = quad_sum(s[2] + s[3]), q0 = quad_sum(q[0] + q[1]), q1 = quad_sum(q[2] + q[3]);
  const float u0 = rsq_fast(fmaxf(fmaf(-s0, s0, fmaf(q0, 96.f, kEps96)), kEps96));
  const float u1 = rsq_fast(fmaxf(fmaf(-s1, s1, fmaf(q1, 96.f, kEps96)), kEps96));
  const float n0 = -s0 * u0, n1 = -s1 * u1;
  ie0 = 96.f * u0; ie1 = 96.f * u1;
  m0 = s0 * (1.f / 96.f); m1 = s1 * (1.f / 96.f);
#pragma unroll
  for (int j = 0; j < 12; j++) {
    const int o = 8 * (j >> 1) + (j & 1);
    z[2 * j] = pack_h2(fmaf(acc[o], ie0, n0), fmaf(acc[o + 4], ie0, n0));
    z[2 * j + 1] = pack_h2(fmaf(acc[o + 2], ie1, n1), fmaf(acc[o + 6], ie1, n1));
  }
}
template <bool kDown>
__device__ __forceinline__ uint32_t sumsq2(const uint32_t* z) {
  uint32_t q0, q1;
#pragma unroll
  for (int j = 0; j < 12; j++) {
    const uint32_t u = kDown ? h2mul(z[2 * j], 0x1c001c00u) : z[2 * j], v = kDown ? h2mul(z[2 * j + 1], 0x1c001c00u) : z[2 * j + 1];
    q0 = j ? h2fma(u, u, q0) : h2mul(u, u); q1 = j ? h2fma(v, v, q1) : h2mul(v, v);
  }
  return fold_add(q0, q1);
}
template <bool kDown>
__device__ __forceinline__ float row_sumsq(const uint32_t* z0, const uint32_t* z1, uint32_t c) {
  const uint32_t a = sumsq2<kDown>(z0), b = sumsq2<kDown>(z1);
  uint32_t t = h2add(sel(c & 2, b, a), shfl_x(sel(c & 2, a, b), 2));
  t = h2add(t, shfl_x(t, 1));
  return low_f(sel(c & 1, t >> 16, t));
}
__device__ __forceinline__ void scores2(const uint32_t* q, const uint32_t* z0, const uint32_t* z1, uint32_t* f) {
  uint32_t d[8];
#pragma unroll
  for (int j = 0; j < 12; j++) {
    const uint32_t kk[4] = {z0[2 * j], z0[2 * j + 1], z1[2 * j], z1[2 * j + 1]};
#pragma unroll
    for (int e = 0; e < 4; e++) {
      d[e] = j ? h2fma(q[2 * j], kk[e], d[e]) : h2mul(q[2 * j], kk[e]);
      d[4 + e] = j ? h2fma(q[2 * j + 1], kk[e], d[4 + e]) : h2mul(q[2 * j + 1], kk[e]);
    }
  }
#pragma unroll
  for (int e = 0; e < 4; e++) f[e] = fold_add(d[2 * e], d[2 * e + 1]);
}
struct Xch { uint32_t keep[2], got[2]; };
__device__ __forceinline__ Xch pair_send(const uint32_t* a, const uint32_t* b, uint32_t c, int m) {
  Xch x;
#pragma unroll
  for (int e = 0; e < 2; e++) { x.keep[e] = fresh(sel(c & m, b[e], a[e])); x.got[e] = shfl_x(sel(c & m, a[e], b[e]), m); }
  return x;
}
__device__ __forceinline__ void pair_recv(uint32_t* k, const Xch& x) { k[0] = h2add(x.keep[0], x.got[0]); k[1] = h2add(x.keep[1], x.got[1]); }
__device__ __forceinline__ void mix2(uint32_t* y, const uint32_t* v, uint32_t c0, uint32_t c1) {
#pragma unroll
  for (int j = 0; j < 12; j++) {
    y[2 * j] = h2fma(v[2 * j + 1], hi2(c0), h2fma(v[2 * j], lo2(c0), y[2 * j]));
    y[2 * j + 1] = h2fma(v[2 * j + 1], hi2(c1), h2fma(v[2 * j], lo2(c1), y[2 * j + 1]));
  }
  pin<24>(y);
}
__device__ __forceinline__ void norm_store(uint32_t* y, uint32_t r0, uint32_t r1, uint32_t ma) {
#pragma unroll
  for (int j = 0; j < 12; j++) { y[2 * j] = h2fma(y[2 * j], lo2(r0), hi2(r0)); y[2 * j + 1] = h2fma(y[2 * j + 1], lo2(r1), hi2(r1)); }
  ma ^= (ma >> 3) & 0x30;
  const uint32_t mb = ma ^ 32;
  stsm4(ma, y); stsm4(mb, y + 4);
  stsm4(mb + kChunk, y + 8); stsm4(ma + kChunk, y + 12);
  stsm4(ma + 2 * kChunk, y + 16); stsm4(mb + 2 * kChunk, y + 20);
}

__device__ __forceinline__ void gate_open(uint32_t id) {
  asm volatile("{\n.reg .pred p;\nsetp.ne.u32 p, %0, 0;\n@p barrier.cta.arrive.aligned %0, 256;\n}" ::"r"(id) : "memory");
}

template <bool kDirect>
__device__ __forceinline__ bool temporal(uint64_t da, uint64_t db, const Tile& T, const TPar& P, bool scaled, uint32_t& lane, uint32_t lst) {
  const uint32_t c = lane;
  const uint32_t a0 = T.a + lane * 16 + (lane >= 4 * T.n ? T.next : 0);
  uint32_t z0[24], z1[24], q0[26], q1[24], v0[24], w1[26], nn = 0, ng = 0, ca0 = 0, ca1 = 0;
  uint32_t* const v1 = w1 + 2;
  float ie = 1.f, mm = 0.f;
  bool tiny = false;
  if (kDirect) {
    uint32_t x[48];
    load_rows(x, x + 12, a0, a0 + kPlane);
    load_rows(x + 24, x + 36, a0 + 2 * kPlane, a0 + 3 * kPlane);
    FT(0);
    to_half(z0, x);
    gemm<0, 0, kAtChunk>(q0, z0, da);
    FT(1);
    to_half(z1, x + 24);
    const uint32_t n0 = sumsq2<false>(z0), n1 = sumsq2<false>(z1);
    nn = fresh(sel(c & 2, n1, n0)); ng = shfl_x(sel(c & 2, n0, n1), 2);
    pin<24>(z1); FT(2);
  } else {
    float e[4], m[4];
    load_general(z0, a0, e[0], e[1], m[0], m[1]);
    pin<24>(z0); sfence(lane);
    load_general(z1, a0 + 2 * kPlane, e[2], e[3], m[2], m[3]);
    ie = sel4(c, e[0], e[1], e[2], e[3]);
    mm = sel4(c, m[0], m[1], m[2], m[3]);
    tiny = __any_sync(0xffffffffu, ie * P.kt > 400.f);
    if (tiny) {
      float u = 0.f;
#pragma unroll
      for (int r = 0; r < 4; r++) {
        float t = 0.f;
#pragma unroll
        for (int j = 0; j < 12; j++) { const float2 f = unpack_h2((r & 2 ? z1 : z0)[2 * j + (r & 1)]); t = fmaf(f.x, f.x, fmaf(f.y, f.y, t)); }
        u = fmaxf(u, quad_sum(t));
      }
      const float t = fminf(ie, 9.8f * rsq_fast(fmaxf(u, 2e-7f)) * rcp_fast(fresh(P.kt)));
      const uint32_t a = pack_h2(__fdividef(t, ie), 0.f);
      ca0 = __byte_perm(shfl_q(a, 0), shfl_q(a, 1), 0x5410); ca1 = __byte_perm(shfl_q(a, 2), shfl_q(a, 3), 0x5410);
      ie = t;
    }
    gemm<0, 0, kAtChunk>(q0, z0, da);
  }
  uint32_t f[4], k0[2], k1[2], sk[2];
  if (SG == 0) gate_open(T.gate);
  wg_wait(); pin<26>(q0);
  gemm<0, 0, kAtChunk>(q1, z1, DB ? db : da);
  if (SG == 1) gate_open(T.gate);
  FT(3);
  if (kDirect) { nn = h2add(nn, ng); ng = shfl_x(nn, 1); FT(4); }
  scores2(q0, z0, z1, f);
  const uint32_t nu0 = fresh(__byte_perm(q0[24], q0[25], 0x7632)), m01 = fresh(sel(c & 1, q0[25], q0[24]));
  Xch xc = pair_send(f, f + 2, c, 1);
  if (SG == 4) gate_open(T.gate);
  sfence(lane);
  wg_wait(); pin<24>(q1);
  gemm<0, kOffWt - 512, kAtChunk>(w1, z1, da);
  if (SG == 2) gate_open(T.gate);
  FT(5);
  pair_recv(k0, xc);
  float e2 = 0.f, lim = 0.f;
  if (kDirect) {
    nn = h2add(nn, ng);
    e2 = fresh(fmaf(low_f(sel(c & 1, nn >> 16, nn)), 1.f / 96.f, 1e-5f));
    lim = fresh(e2 <= 4.f ? fmaxf(0.5f * e2, 4e-4f) : __uint_as_float(0x7fffffffu));
  }
  scores2(q1, z0, z1, f);
  xc = pair_send(f, f + 2, c, 1);
  pin<2>(k0); sfence(lane);
  wg_wait(); pin<26>(w1);
  float mz = 0.f, d2 = 0.f;
  if (kDirect) {
    mz = low_f(sel(c & 2, sel(c & 1, w1[1], w1[0]), m01));
    d2 = fmaf(-mz, mz, e2);
    asm volatile("{\n.reg .pred p;\nsetp.lt.s32 p, %3, %4;\nsetp.ltu.and.f32 p, %1, %2, p;\n@p st.volatile.shared.f32 [%0], %2;\n}" ::"r"(T.flag), "f"(d2),
                 "f"(lim), "r"(lane), "r"(T.live) : "memory");
  }
  gemm<0, kOffWt, kAtChunk>(v0, z0, da);
  if (SG == 3) gate_open(T.gate);
  FT(6);
  uint32_t cw[8], mu;
  {
    uint32_t rc = 0, r0 = 0, r1 = 0;
    if (kDirect) {
      const float r = rsq_fast(d2);
      rc = pack_h2(r, r);
      r0 = __byte_perm(shfl_q(rc, 0), shfl_q(rc, 1), 0x5410); r1 = __byte_perm(shfl_q(rc, 2), shfl_q(rc, 3), 0x5410);
    }
    pair_recv(k1, xc);
    pair_recv(sk, pair_send(k0, k1, c, 2));
    if (kDirect) { sk[0] = h2mul(sk[0], r0); sk[1] = h2mul(sk[1], r1); }
    uint32_t mx = h2max(sk[0], sk[1]);
    mx = h2max(lo2(mx), hi2(mx));
    if (kDirect) {
      const uint32_t nm = h2mul(h2neg(mx), rc);
      sk[0] = h2fma(sk[0], rc, nm); sk[1] = h2fma(sk[1], rc, nm);
    } else {
      sk[0] = h2sub(sk[0], mx); sk[1] = h2sub(sk[1], mx);
      if (scaled) {
        const uint32_t cs = score_scale(&g_par.cS_t);
        sk[0] = h2mul(sk[0], cs); sk[1] = h2mul(sk[1], cs);
      }
    }
    sk[0] = h2ex2(sk[0]); sk[1] = h2ex2(sk[1]);
    const uint32_t sm = h2add(sk[0], sk[1]);
    const float iv = (kDirect ? P.kt : P.kt * ie) * rcp_fast(low_f(h2add(lo2(sm), hi2(sm))));
    const uint32_t inv = pack_h2(iv, iv);
    if (kDirect) { sk[0] = h2mul(sk[0], r0); sk[1] = h2mul(sk[1], r1); }
    sk[0] = h2mul(sk[0], inv); sk[1] = h2mul(sk[1], inv);
#pragma unroll
    for (int i = 0; i < 4; i++) { cw[2 * i] = shfl_q(sk[0], i); cw[2 * i + 1] = shfl_q(sk[1], i); }
    mu = h2fma(sk[1], __byte_perm(w1[0], w1[1], 0x7632), h2mul(sk[0], nu0));
    mu = h2add(lo2(mu), hi2(mu));
  }
  uint32_t bad = 0;
  if (kDirect) {
    mix2(z1, v1, cw[5], cw[7]);
    FT(7);
    wg_wait(); pin<24>(v0);
    mix2(z1, v0, cw[4], cw[6]);
    sfence(lane);
    bad = lds32(T.flag);
  } else {
    wg_wait(); pin<24>(v0);
    if (tiny) {
#pragma unroll
      for (int j = 0; j < 12; j++) {
        z0[2 * j] = h2mul(z0[2 * j], lo2(ca0)); z0[2 * j + 1] = h2mul(z0[2 * j + 1], hi2(ca0));
        z1[2 * j] = h2mul(z1[2 * j], lo2(ca1)); z1[2 * j + 1] = h2mul(z1[2 * j + 1], hi2(ca1));
      }
    }
    mix2(z1, v1, cw[5], cw[7]);
    mix2(z1, v0, cw[4], cw[6]);
  }
  mix2(z0, v1, cw[1], cw[3]);
  mix2(z0, v0, cw[0], cw[2]);
  float qq = row_sumsq<false>(z0, z1, c);
  if (__any_sync(0xffffffffu, (!(qq < 65000.f) & ((int)lane < T.live)) | (bad != 0))) {
    if (kDirect && __any_sync(0xffffffffu, bad != 0)) return false;
    const float q2 = row_sumsq<true>(z0, z1, c) * 65536.f;
    qq = qq < 65000.f ? qq : q2;
  }
  const float rf = kDirect ? rsq_fast(fmaxf(fmaf(-mz, mz, fmaf(qq, 1.f / 96.f, 1e-5f)), 1e-5f)) : rsq_fast(fmaf(qq, 1.f / 96.f, 1e-5f * ie * ie));
  const uint32_t rn = pack_h2_sat(rf, -mz * rf);
  uint32_t rr[4];
#pragma unroll
  for (int i = 0; i < 4; i++) rr[i] = shfl_q(rn, i);
  if (!L2P) lst = (lane & 7) * 64 + (lane & 8) * (kPlane / 8) + (lane & 16);
  const uint32_t ma = T.a + lst + ((lane & 7) >= T.n ? T.next : 0);
  norm_store(z0, rr[0], rr[1], ma);
  norm_store(z1, rr[2], rr[3], ma + 2 * kPlane);
  const float2 rm = unpack_h2(rn);
  const float sg = rcp_fast(kDirect ? rm.x : rm.x * ie);
  mm = kDirect ? fmaf(-rm.y, sg, low_f(mu)) : fmaf(low_f(mu) * rm.x, sg, mm);
  const bool ok = (sg >= P.sgmin) & (fmaf(sg, 9.8f, fabsf(mm)) < P.outmax);
  asm volatile("{\n.reg .pred p;\nsetp.lt.s32 p, %2, %3;\n@p st.shared.b32 [%0], %1;\n}" ::"r"(
                   T.stat + fresh((lane & 3) * (kSlot - 1) + lane + (lane >= 4 * T.n ? T.wrap : 0))),
               "r"(sel(ok, pack_h2(sg, mm), pack_bf2(sg, mm) | 0x8000u)), "r"(lane), "r"(T.live) : "memory");
  return true;
}

__device__ __forceinline__ void run_T(uint32_t ring, uint64_t d0, uint64_t d1, uint32_t nfull, uint32_t nrem, bool helper, int wg, int wp, uint32_t lane,
                                      const TPar& P, bool scaled, uint32_t pdir) {
  const uint32_t lst = (lane & 7) * 64 + (lane & 8) * (kPlane / 8) + (lane & 16);
  uint32_t p0 = 32 * (wg & 1) + (helper ? 0 : 64) + 8 * wp;
  uint32_t npx = 49 * nfull, pstop = npx - 6 * 49 + 8 * wp;
  if (helper) pstop = 0;
  uint32_t pgap = 0;
  Tile T;
  T.flag = ring + wg * kSlot + kFlag;
  T.gate = helper && !(wg & 1) ? 0 : 5 + (wg & 1);
  while (true) {
    const uint32_t iw = (p0 * 21400u) >> 20, ow = p0 - 49 * iw;
    const uint32_t slot = ring + (iw & 3) * kSlot, dn = (iw & 3) == 3 ? -3 * kSlot : kSlot;
    if (wp == 3) TR(p0 >> 5, 1);
    if (GO == 0) asm volatile("{\n.reg .pred p;\nsetp.eq.u32 p, %1, 0;\n@p barrier.cta.sync.aligned %0, 256;\n}" ::"r"(6 - (wg & 1)), "r"((uint32_t)helper) : "memory");
    mbar_wait(slot + kFull, iw >> 2);
    if (ow > 41) mbar_wait(slot + dn + kFull, (iw + 1) >> 2);
    if (GO == 1) asm volatile("{\n.reg .pred p;\nsetp.eq.u32 p, %1, 0;\n@p barrier.cta.sync.aligned %0, 256;\n}" ::"r"(6 - (wg & 1)), "r"((uint32_t)helper) : "memory");
    if (wp == 3) TR(p0 >> 5, 2);
    T.a = slot + ow * 64; T.next = dn - kPlane; T.n = 49 - ow;
    T.live = 4 * (npx - p0);
    T.stat = ring + kXBytes + (p0 - 196 * (iw >> 2)) * 4; T.wrap = (iw & 3) == 3 ? -784 : 0;
    const bool direct = p0 >= pdir;
    bool done = false;
    if (direct) done = temporal<true>(d0, d1, T, P, false, lane, lst);
    if (!done) {
      Tile G = T;
      if (direct) {
        asm volatile("barrier.cta.sync.aligned %0, 128;" ::"r"(wg + 1) : "memory");
        asm volatile("st.shared.b32 [%0], %1;\nfence.acq_rel.cta;" ::"r"(T.flag), "r"(0) : "memory");
        G.gate = 0;
        pgap = p0 == pdir ? 4 * pgap + 64 : 0;
        pdir = p0 + 64 + pgap;
      }
      temporal<false>(d1, d0, G, P, scaled, lane, lst);
    }
    const uint32_t pn = __shfl_sync(0xffffffffu, p0 + 64, 0);
    bool last = false;
    if (pn >= pstop) {
      if (helper) last = true;
      else if (pstop < npx - 4 * 49) {
        if (((wg & 1) | wp | lane) == 0) {
          const uint32_t nb = gridDim.x, nwh = min(max((int)(2 * nrem - nb), (int)(nrem * NWH / 16)), nrem);
          const uint32_t r = DYN ? atomicAdd(&g_par.ticket, 1u) : blockIdx.x, j = r - nwh;
          sts32(ring + kExtra, r < nwh ? (nfull * nb + r) * 4 + 3 : j < 2 * (nrem - nwh) ? (nfull * nb + nwh + (j >> 1)) * 4 + 1 + (j & 1) : 0);
        }
        __syncwarp();
        pstop = npx - 2 * 49 + 8 * wp;
      } else if (pstop < npx) {
        if (__shfl_sync(0xffffffffu, lds32(ring + kExtra), 0)) npx += 49;
        pstop = npx + 8 * wp;
      } else last = true;
    }
    asm volatile("fence.proxy.async.shared::cta;" ::: "memory");
    __syncwarp();
    mbar_arrive(slot + kDone + (lane >= 4 * T.n ? dn : 0), lane & 3);
    __syncwarp();
    if (wp == 3) TR(p0 >> 5, 3);
    if (last) break;
    p0 = pn;
  }
}

struct Frame {
  bool light;
  uint32_t sta;
  uint32_t oo;
  uint32_t e0, e1;
};
__device__ __forceinline__ uint32_t frame_init(Frame& F, uint32_t ring, uint32_t t, int wp, int lane) {
  wp = (wp + t) & 3;
  F.light = wp == 3;
  F.sta = ring + t * kSlot + kXBytes + 64 * wp;
  const uint32_t r = 16 * wp + (lane >> 2);
  F.oo = ((r / 7) * (kW - 7) + r) * 192u + (lane & 3) * 16 + (((((r + 8) / 7 - r / 7) * (kW - 7) + 8) * 3u) << 20);
  F.e0 = F.e1 = 0x8000u;
  const uint32_t am = t * kPlane + wp * 1024 + ((lane * 65) & 0x3d0);
  return F.light && (lane & 15) ? kZero : am ^ ((am >> 3) & 0x30);
}
template <bool F>
__device__ __forceinline__ void load_frame(uint32_t (&v)[24], uint32_t ma, uint32_t slot, uint32_t& tid) {
  const uint32_t st = ma < kXBytes ? kChunk : 0, mb = ma ^ 32;
  uint32_t a[6] = {ma, mb, mb + st, ma + st, ma + 2 * st, mb + 2 * st};
  pin<6>(a);
  if (F) sfence(tid);
#pragma unroll
  for (int k = 0; k < 6; k++) ldsm4(v + 4 * k, slot + a[k]);
}
__device__ __forceinline__ uint32_t load_stats(Frame& F, uint32_t ia, uint32_t tid) {
  const uint32_t a = fresh(tid & (F.light ? 0 : 0x1c)), u = F.sta + ia * 196;
  F.e0 = lds32(a + u);
  F.e1 = lds32(a + fresh(u + (F.light ? 0 : 32)));
  return a;
}
__device__ __forceinline__ uint32_t is_wide(const Frame& F) {
  uint32_t r;
  asm volatile("{\n.reg .pred p;\n.reg .b32 t;\nlop3.b32 t, %1, %2, 0x8000, 0xa8;\nsetp.ne.u32 p, t, 0;\nvote.sync.ballot.b32 %0, p, 0xffffffff;\n}"
               : "=r"(r) : "r"(F.e0), "r"(F.e1));
  return r;
}
template <int OFF>
__device__ __forceinline__ void gemm_u(uint32_t (&u)[24], const uint32_t* s, uint64_t db) {
  constexpr uint32_t kMN = (((kChunk >> 4) - 1) << 16) + OFF / 16;
  asm volatile("" : "+l"(db));
  wg_fence();
  wgmma<2, 1>(u, s, db + kMN); wgmma<1, 1>(u, s + 4, db + kMN + 64); wgmma<1, 1>(u, s + 8, db + kMN + 128); wgmma<1, 1>(u, s + 12, db + kMN + 192);
  wg_commit();
}
__device__ __forceinline__ uint32_t key48(uint32_t (&s)[16], uint32_t tid) {
  return fresh(sel(tid & 3, 0xfc00fc00u, __byte_perm(s[12], s[13], 0x5410)));
}
__device__ __forceinline__ uint32_t amax3(uint32_t a, uint32_t b, uint32_t c) {
  return as_u(__hmax2(__hmax2(__habs2(as_h2(a)), __habs2(as_h2(b))), __habs2(as_h2(c))));
}
struct Quad { uint32_t v[4]; };
__device__ __forceinline__ Quad soft_exp(uint32_t (&s)[16], uint32_t& t, uint32_t (&v)[24], const Frame& F, float2& e) {
  const uint32_t am = h2max(h2max(h2max(amax3(s[0], s[1], s[2]), amax3(s[3], s[4], s[5])), amax3(s[6], s[7], s[8])), h2max(amax3(s[9], s[10], s[11]), t));
  e = make_float2(low_f(F.e0), low_f(F.e1));
  uint32_t rare, sp[NSP + 1];
#pragma unroll
  for (int j = 0; j < NSP; j++) sp[j] = fresh(h2ex2(s[j]));
  asm("{\n.reg .pred p, q;\n.reg .b32 t;\nlop3.b32 t, %2, %3, 0x8000, 0xa8;\nsetp.eq.u32 q, t, 0;\nmov.b32 t, 0x49004900;\n"
      "setp.le.and.f16x2 p|q, %1, t, q;\nand.pred p, p, q;\nselp.b32 %0, 0, 1, p;\n}" : "=r"(rare) : "r"(am), "r"(F.e0), "r"(F.e1));
  if (__any_sync(0xffffffffu, rare)) {
    const uint32_t x0 = h2max(h2max(h2max(s[0], s[2]), h2max(s[4], s[6])), h2max(s[8], s[10]));
    const uint32_t x1 = h2max(h2max(h2max(s[1], s[3]), h2max(s[5], s[7])), h2max(s[9], s[11]));
    uint32_t mx = h2max(h2max(__byte_perm(x0, x1, 0x5410), __byte_perm(x0, x1, 0x7632)), t);
    mx = h2max(mx, shfl_x(mx, 1));
    mx = h2max(mx, shfl_x(mx, 2));
#pragma unroll
    for (int j = 0; j < 6; j++) { s[2 * j] = h2sub(s[2 * j], lo2(mx)); s[2 * j + 1] = h2sub(s[2 * j + 1], hi2(mx)); }
    t = h2sub(t, mx);
    if (is_wide(F)) {
      const uint32_t cs = score_scale(&g_par.cS_s);
#pragma unroll
      for (int j = 0; j < 12; j++) s[j] = h2mul(s[j], cs);
      t = h2mul(t, cs);
      const float s0 = stat_f32(F.e0).x, s1 = stat_f32(F.e1).x;
      const float kb = __ldcg(&g_par.kb), ik = rcp_fast(__ldcg(&g_par.kappa));
      e.x = fmaxf(s0, kb); e.y = fmaxf(s1, kb);
      const uint32_t aw = pack_h2(__fdividef(s0, e.x), __fdividef(s1, e.y));
      e.x *= ik; e.y *= ik;
#pragma unroll
      for (int j = 0; j < 12; j++) { v[2 * j] = h2mul(v[2 * j], lo2(aw)); v[2 * j + 1] = h2mul(v[2 * j + 1], hi2(aw)); }
    }
#pragma unroll
    for (int j = 0; j < NSP; j++) sp[j] = h2ex2(s[j]);
  }
#pragma unroll
  for (int j = 0; j < 12; j++) s[j] = j < NSP ? sp[j] : h2ex2(s[j]);
  t = h2ex2(t);
  Quad q;
  q.v[0] = h2add(t, fold_add(h2add(h2add(h2add(s[0], s[2]), h2add(s[4], s[6])), h2add(s[8], s[10])),
                             h2add(h2add(h2add(s[1], s[3]), h2add(s[5], s[7])), h2add(s[9], s[11]))));
#pragma unroll
  for (int i = 1; i < 4; i++) q.v[i] = shfl_x(q.v[0], i);
  return q;
}
__device__ __forceinline__ void soft_norm(uint32_t (&s)[16], uint32_t& t, const Quad& q, const Frame& F, float2 e, uint32_t tid) {
  const float2 d = unpack_h2(h2add(h2add(q.v[0], q.v[1]), h2add(q.v[2], q.v[3])));
  const uint32_t cb = pack_h2(rcp_fast(d.x * e.x), rcp_fast(d.y * e.y)) & (sel(tid & 28, 0u, 0xffffu) | fresh(F.light ? 0u : 0xffffffffu));
#pragma unroll
  for (int j = 0; j < 6; j++) { s[2 * j] = h2mul(s[2 * j], lo2(cb)); s[2 * j + 1] = h2mul(s[2 * j + 1], hi2(cb)); }
  t = fresh(h2mul(t, cb));
  pin<12>(s);
}
__device__ __forceinline__ void soft_tail(uint32_t (&s)[16], uint32_t t) {
  s[12] = t & 0xffffu; s[13] = t >> 16;
  asm volatile("mov.b32 %0, 0;\nmov.b32 %1, 0;" : "=r"(s[14]), "=r"(s[15]));
}
template <int H>
__device__ __forceinline__ uint8_t* row_ptr(const Frame& F, uint8_t* o) {
  const uint32_t oo = fresh(F.oo);
  if (H) asm volatile("mad.wide.u32 %0, %1, 64, %0;" : "+l"(o) : "r"(oo >> 20));
  else { o += oo & 0xfffffu; asm volatile("" : "+l"(o)); }
  return o;
}
template <int H>
__device__ __forceinline__ void affine(uint32_t* r, const uint32_t (&v)[24], const Frame& F) {
  const uint32_t e = H ? F.e1 : F.e0;
#pragma unroll
  for (int j = 0; j < 12; j++) r[j] = h2fma(v[2 * j + H], lo2(e), hi2(e));
  pin<12>(r);
}
template <int H>
__device__ __forceinline__ void finish(uint32_t* r, const Frame& F, uint8_t*& o, uint32_t off, uint32_t a, uint32_t m, uint32_t& tid, uint32_t a2 = 0) {
  o = row_ptr<H>(F, o);
#pragma unroll
  for (int j = 0; j < 12; j += 2) { const float2 f = unpack_h2(r[j]), g = unpack_h2(r[j + 1]); r[j] = pack_bf2(f.x, g.x); r[j + 1] = pack_bf2(f.y, g.y); }
  pin<12>(r);
  if (SE) sfence(tid);
  stg3(o, r, off | (fresh(a) & m) | (a2 & 0x4000));
}
__device__ __forceinline__ void finish_wide(const uint32_t (&v)[24], const Frame& F, uint8_t* o, uint32_t tid) {
  const float kb = __ldcg(&g_par.kb);
#pragma unroll
  for (int h = 0; h < 2; h++) {
    const float2 z = stat_f32(h ? F.e1 : F.e0);
    const float w = fmaxf(z.x, kb);
    uint32_t r[12];
#pragma unroll
    for (int j = 0; j < 12; j += 2) {
      const float2 f = unpack_h2(v[2 * j + h]), g = unpack_h2(v[2 * j + 2 + h]);
      r[j] = pack_bf2(fmaf(f.x, w, z.y), fmaf(g.x, w, z.y)); r[j + 1] = pack_bf2(fmaf(f.y, w, z.y), fmaf(g.y, w, z.y));
    }
    o = h ? row_ptr<1>(F, o) : row_ptr<0>(F, o);
    stg3(o, r, F.light ? (h ? 1 : tid & 28) : 0);
  }
}
__device__ __forceinline__ uint32_t window_ahead(uint32_t ring, uint32_t i, uint32_t nfull, uint32_t w) {
  return i + 4 < nfull ? w + 4 * gridDim.x : i + 4 == nfull ? lds32(ring + kExtra) >> 2 : 0;
}

__device__ __forceinline__ void run_S(uint32_t ring, uint64_t d0, uint64_t d1, uint32_t frame, uint32_t nfull, uint32_t i0, uint32_t i1, uint32_t w, int sg, int wp, int lane,
                                      const CUtensorMap* tm, uint8_t* __restrict__ out) {
  Frame A, B;
  uint32_t tid = lane + (frame_init(A, ring, 2 * sg, wp, lane) << 4) + (frame_init(B, ring, 2 * sg + 1, wp, lane) << 16);
  uint32_t va[24], vb[24], x[24], sa[16], sc[16], r0[12], r1[12], ta, tb;
  Quad rs;
  float2 e;
#pragma unroll
  for (int j = 0; j < 24; j++) { vb[j] = 0; x[j] = 0; }
  out += sg * 2 * frame;
  uint8_t *ob = out, *o;
  const uint64_t dr = d0 + (uint32_t)(kWBytes / 16 + sg * (2 * kPlane / 16));
  uint32_t i = i0, slot = ring + (i & 3) * kSlot;
  mbar_wait(slot + kDone, i >> 2);
  load_frame<false>(va, (tid >> 4) & 0xfff0u, slot, tid);
  do {
    const uint32_t ia = i & 3;
    gemm<2, kOffAs, 6144>(x, va, d0);
    FS(0);
    const uint32_t wb = is_wide(B);
    if (wb && i != i0) finish_wide(vb, B, ob + frame, tid);
    affine<0>(r0, vb, B); affine<1>(r1, vb, B);
    const uint32_t lb = (tid >> 16) & 0xfff0u;
    load_frame<true>(vb, lb, slot, tid);
    const uint32_t g4 = load_stats(A, ia, tid);
    uint64_t dp = dr + ia * (kSlot / 16);
    asm volatile("" : "+l"(dp));
    FS(1);
    o = ob + frame;
    finish<0>(r0, B, o, wb, g4, B.light ? 28 : 0, tid, KA ? lb : 0);
    FS(2);
    wg_wait(); pin<24>(x); if (TM & 1) launder<24>(x);
    gemm<0, 0, kChunk>(sa, x, dp);
    if (!B.light) finish<1>(r1, B, o, wb, 0, 0, tid);
    else if (sg == 0) {
      if ((tid & 31) == 0) {
        const uint32_t wn = window_ahead(ring, i, nfull, w);
        if (wn) tma_prefetch_win(tm, wn);
      }
      __syncwarp();
    }
    ob = out + (size_t)((((w * 57457u) >> 22) * (7 * kW - 7 * kNWX) + w * 7) * 192u);
    FS(3);
    wg_wait(); pin<14>(sa);
    gemm<2, kOffAs, 6144>(x, vb, d1);
    FS(4);
    ta = key48(sa, tid);
    rs = soft_exp(sa, ta, va, A, e);
    FS(5);
    wg_wait(); pin<24>(x); if (TM & 2) launder<24>(x);
    gemm<0, kPlane, kChunk>(sc, x, dp);
    FS(6);
    load_stats(B, ia, tid);
    soft_norm(sa, ta, rs, A, e, tid);
    FS(7);
    wg_wait(); pin<14>(sc);
    tb = key48(sc, tid);
    sfence(tid);
    soft_tail(sa, ta);
    gemm_u<0>(x, sa, dp);
    FS(8);
    rs = soft_exp(sc, tb, vb, B, e);
    FS(9);
    wg_wait(); pin<24>(x); if (TM & 4) launder<24>(x);
    gemm<1, kOffWs, 6144>(va, x, d0);
    FS(10);
    soft_norm(sc, tb, rs, B, e, tid);
    soft_tail(sc, tb);
    const uint32_t wa = is_wide(A);
    FS(11);
    wg_wait(); pin<24>(va);
    gemm_u<kPlane>(x, sc, dp);
    FS(12);
    const uint32_t sn = ring + ((i + 1) & 3) * kSlot;
    const bool slow = mbar_pending_or(sn + kDone, (i + 1) >> 2, wa | A.light);
    affine<0>(r0, va, A);
    o = ob;
    finish<0>(r0, A, o, wa, tid, A.light ? 28 : 0, tid);
    FS(13);
    wg_wait(); pin<24>(x); if (TM & 8) launder<24>(x);
    gemm<1, kOffWs, 6144>(vb, x, d1);
    FS(14);
    affine<1>(r1, va, A);
    if (wp == 2) TR(i + 1, 4 + 2 * sg);
    if (slow) {
      if (A.light) {
        if ((tid & 31) == 0) {
          uint32_t old;
          asm volatile("atom.relaxed.cta.shared::cta.inc.u32 %0, [%1], 1;" : "=r"(old) : "r"(slot + kRel) : "memory");
          if (old) {
            const uint32_t wn = window_ahead(ring, i, nfull, w);
            if (wn) tma_load_win(slot, tm, wn);
            else mbar_arrive(slot + kFull);
          }
        }
        __syncwarp();
      }
      if (wa) finish_wide(va, A, ob, tid);
      if (i + 1 < i1) mbar_wait(sn + kDone, (i + 1) >> 2);
    }
    if (wp == 2) TR(i + 1, 5 + 2 * sg);
    const uint32_t la = (tid >> 4) & 0xfff0u;
    load_frame<LF>(va, la, sn, tid);
    if (!A.light) finish<1>(r1, A, o, wa, la, 0x4000, tid);
    wg_wait(); pin<24>(vb);
    launder<24>(vb);
    launder<24>(va);
    slot = sn; w += gridDim.x;
  } while (++i < i1);
  const uint32_t wb = is_wide(B);
  if (wb) finish_wide(vb, B, ob + frame, tid);
  o = ob + frame;
  affine<0>(r0, vb, B); finish<0>(r0, B, o, wb, tid, B.light ? 28 : 0, tid);
  affine<1>(r1, vb, B); finish<1>(r1, B, o, B.light | wb, 0, 0, tid);
}

__global__ void __launch_bounds__(512, 1) swin_main(const __grid_constant__ CUtensorMap tm, uint8_t* __restrict__ out, const uint64_t d0,
                                                    const uint64_t d1, const uint32_t frame) {
  extern __shared__ __align__(1024) uint8_t smem[];
  const uint32_t sb = CB ? 1024u : smem_u32(smem), ring = sb + kWBytes;
  const int tid = threadIdx.x;
  const int wg = __shfl_sync(0xffffffffu, tid >> 7, 0);
  const int wp = __shfl_sync(0xffffffffu, (tid >> 5) & 3, 0);
  const int lane = tid & 31;
  const uint32_t b = blockIdx.x, nb = gridDim.x;
  const uint32_t nfull = kNWIN / nb, nrem = kNWIN - nfull * nb;
  if (tid == 0) {
    if (smem_u32(smem) != 1024 || nfull > 700 || nfull < 12) __trap();
#pragma unroll
    for (int i = 0; i < 4; i++) {
      mbar_init(ring + i * kSlot + kFull, 1);
      mbar_init(ring + i * kSlot + kDone, 49);
      sts32(ring + i * kSlot + kRel, 0); sts32(ring + i * kSlot + kFlag, 0);
    }
    asm volatile("fence.mbarrier_init.release.cluster;" ::: "memory");
    for (int i = 0; i < 2; i++) tma_load_win(ring + i * kSlot, &tm, b + i * nb);
  }
  __syncwarp();
  if (wg == 1 || wg == 2)
    asm volatile("st.shared.v4.b32 [%0], {%1,%1,%1,%1};" ::"r"(ring + ((tid - 128) >> 6) * kSlot + kXBytes + (tid & 63) * 16), "r"(0) : "memory");
  __syncthreads();
  asm volatile("griddepcontrol.wait;" ::: "memory");
#pragma unroll
  for (int q = 0; q < kWBytes / 16 / 512; q++)
    asm volatile("cp.async.cg.shared.global [%0], [%1], 16;" ::"r"(sb + (tid + q * 512) * 16), "l"(g_wimg + tid + q * 512) : "memory");
  if (wg == 0 && wp < 3) {
    static_assert(kWBytes / 16 == 9 * 512 + 96, "weight copy split");
    const int e = tid + 9 * 512;
    asm volatile("cp.async.cg.shared.global [%0], [%1], 16;" ::"r"(sb + e * 16), "l"(g_wimg + e) : "memory");
  }
  const float4 p0 = __ldcg(reinterpret_cast<const float4*>(&g_par));
  const float kb = __ldcg(&g_par.kb);
  TPar P;
  P.kt = p0.z;
  P.sgmin = p0.y != 1.f || p0.w != 1.f ? 1e30f : fmaxf(0.0045f, kb * 0.011f);
  P.outmax = fmaf(kb, -627.2f, 60000.f);
  const bool scaled = __any_sync(0xffffffffu, p0.x != 1.f);
  const uint32_t pdir = __ballot_sync(0xffffffffu, scaled || !(P.kt <= 256.f));
  asm volatile("cp.async.wait_all;\nfence.proxy.async.shared::cta;" ::: "memory");
  __syncthreads();
  if (tid == 128) for (int i = 2; i < 4; i++) tma_load_win(ring + i * kSlot, &tm, b + i * nb);
  __syncwarp();
  const bool isT = wg < 2;
  run_T(ring, d0, d1, nfull, nrem, !isT, wg, wp, lane, P, scaled, pdir);
  const uint32_t ex = isT ? __shfl_sync(0xffffffffu, lds32(ring + kExtra), 0) : 3;
  if ((ex >> (wg & 1)) & 1) run_S(ring, d0, d1, frame, nfull, isT ? nfull : 0, nfull + isT, isT ? ex >> 2 : b, wg & 1, wp, lane, &tm, out);
}

__device__ __forceinline__ int ch_pos(int ch) { return 32 * (ch >> 5) + 16 * ((ch >> 2) & 1) + 8 * (ch & 1) + 2 * ((ch >> 3) & 3) + ((ch >> 1) & 1); }
__device__ __forceinline__ float pow2_ceil(float v) {
  return __uint_as_float((__float_as_uint(v) + 0x7fffffu) & 0x7f800000u);
}

constexpr int kPrepSplit = 12;
constexpr int kPrepThreads = 384;
__global__ void __launch_bounds__(kPrepThreads) swin_prep(const __nv_bfloat16* __restrict__ wqkv_t, const __nv_bfloat16* __restrict__ wo_t,
                                                          const __nv_bfloat16* __restrict__ wqkv_s, const __nv_bfloat16* __restrict__ wo_s) {
  asm volatile("griddepcontrol.launch_dependents;");
  __shared__ __align__(16) uint32_t raw[2][96][52];
  __shared__ __align__(16) uint32_t mu[3][52];
  __shared__ float nrm[12], nrm2[6], csum[6][9];
  const int mat = blockIdx.x / kPrepSplit, blk = blockIdx.x % kPrepSplit;
  const int tid = threadIdx.x, lane = tid & 31, warp = tid >> 5, g = lane >> 2, c = lane & 3;
  const __nv_bfloat16* wqkv = mat < 2 ? wqkv_t : wqkv_s;
  const __nv_bfloat16* wo = mat < 2 ? wo_t : wo_s;
  const bool isA = (mat & 1) == 0;
  {
    uint4 v[3], u[3];
#pragma unroll
    for (int q = 0; q < 3; q++) {
      const int e = tid + q * kPrepThreads, i = e / 12, c8 = (e % 12) * 8;
      v[q] = __ldg(reinterpret_cast<const uint4*>(wqkv + i * 288 + (isA ? 0 : 192) + c8));
      u[q] = __ldg(reinterpret_cast<const uint4*>(isA ? wqkv + i * 288 + 96 + c8 : wo + i * 96 + c8));
    }
#pragma unroll
    for (int q = 0; q < 3; q++) {
      const int e = tid + q * kPrepThreads, i = e / 12, c4 = (e % 12) * 4;
      *reinterpret_cast<uint4*>(&raw[0][i][c4]) = v[q];
      *reinterpret_cast<uint4*>(&raw[1][i][c4]) = u[q];
    }
  }
  __syncthreads();
  {
    const int m = warp / 6, cp = (warp % 6) * 8 + g;
    float s0 = 0.f, s1 = 0.f, q0 = 0.f, q1 = 0.f;
#pragma unroll
    for (int i = 0; i < 24; i++) {
      const uint32_t w = raw[m][4 * i + c][cp];
      const float lo = __uint_as_float(w << 16), hi = __uint_as_float(w & 0xffff0000u);
      s0 += lo; s1 += hi; q0 = fmaf(lo, lo, q0); q1 = fmaf(hi, hi, q1);
    }
    s0 = quad_sum(s0) * (1.f / 96.f); s1 = quad_sum(s1) * (1.f / 96.f); q0 = quad_sum(q0); q1 = quad_sum(q1);
    if (mat == 1 && m == 1) {
      float r0 = 0.f, r1 = 0.f;
#pragma unroll
      for (int i = 0; i < 12; i++) {
        const uint32_t w0 = raw[1][2 * cp][4 * i + c], w1 = raw[1][2 * cp + 1][4 * i + c];
        r0 += __uint_as_float(w0 << 16) + __uint_as_float(w0 & 0xffff0000u);
        r1 += __uint_as_float(w1 << 16) + __uint_as_float(w1 & 0xffff0000u);
      }
      r0 = quad_sum(r0) * (1.f / 96.f); r1 = quad_sum(r1) * (1.f / 96.f);
      s0 = r0; s1 = r1;
    }
    if (m == 1 && c == 0) {
      const uint32_t hi = mat == 3 ? 0u : pack_bf2(s0, s1);
      mu[0][cp] = hi;
      mu[1][cp] = mat == 3 ? 0u : pack_bf2(s0 - __uint_as_float(hi << 16), s1 - __uint_as_float(hi & 0xffff0000u));
      mu[2][cp] = 0u;
    }
    if (m == 0 || isA) {
      q0 = fmaxf(fmaf(-96.f * s0, s0, q0), 0.f) + q0 * 1e-6f;
      q1 = fmaxf(fmaf(-96.f * s1, s1, q1), 0.f) + q1 * 1e-6f;
    }
    const bool usemax = m == 1 && mat == 3;
    float t = usemax ? fmaxf(q0, q1) : q0 + q1;
#pragma unroll
    for (int o = 4; o < 32; o <<= 1) { const float z = __shfl_xor_sync(0xffffffffu, t, o); t = usemax ? fmaxf(t, z) : t + z; }
    if (lane == 0) nrm[warp] = t;
  }
  __syncthreads();
  if (warp >= 6) return;
  float d[4] = {0.f, 0.f, 0.f, 0.f}, e[4] = {0.f, 0.f, 0.f, 0.f}, v0, v1;
  {
    const uint32_t arow = smem_u32(&raw[0][16 * warp + (lane & 15)][(lane >> 4) * 4]);
    const uint32_t brow = isA ? smem_u32(&raw[1][blk * 8 + (lane & 7)][(lane >> 3) * 4]) : smem_u32(&raw[1][lane][blk * 4]);
    const uint32_t mrow = smem_u32(&mu[min(lane & 7, 2)][(lane >> 3) * 4]);
#pragma unroll
    for (int k2 = 0; k2 < 3; k2++) {
      uint32_t b[4], m[4];
      if (isA) ldsm4(b, brow + k2 * 64);
      else asm volatile("ldmatrix.sync.aligned.m8n8.x4.trans.shared.b16 {%0,%1,%2,%3}, [%4];"
                        : "=r"(b[0]), "=r"(b[1]), "=r"(b[2]), "=r"(b[3]) : "r"(brow + k2 * (32 * 208)) : "memory");
      ldsm4(m, mrow + k2 * 64);
#pragma unroll
      for (int hf = 0; hf < 2; hf++) {
        uint32_t a[4];
        ldsm4(a, arow + (2 * k2 + hf) * 32);
        asm volatile("mma.sync.aligned.m16n8k16.row.col.f32.bf16.bf16.f32 {%0,%1,%2,%3},{%4,%5,%6,%7},{%8,%9},{%0,%1,%2,%3};"
                     : "+f"(d[0]), "+f"(d[1]), "+f"(d[2]), "+f"(d[3])
                     : "r"(a[0]), "r"(a[1]), "r"(a[2]), "r"(a[3]), "r"(b[2 * hf]), "r"(b[2 * hf + 1]));
        asm volatile("mma.sync.aligned.m16n8k16.row.col.f32.bf16.bf16.f32 {%0,%1,%2,%3},{%4,%5,%6,%7},{%8,%9},{%0,%1,%2,%3};"
                     : "+f"(e[0]), "+f"(e[1]), "+f"(e[2]), "+f"(e[3])
                     : "r"(a[0]), "r"(a[1]), "r"(a[2]), "r"(a[3]), "r"(m[2 * hf]), "r"(m[2 * hf + 1]));
      }
    }
    v0 = __shfl_sync(0xffffffffu, e[0] + e[1], lane & ~3); v1 = __shfl_sync(0xffffffffu, e[2] + e[3], lane & ~3);
    d[0] -= v0; d[1] -= v0; d[2] -= v1; d[3] -= v1;
    float t0 = d[0] + d[2], t1 = d[1] + d[3], t2 = v0 + v1;
#pragma unroll
    for (int o = 4; o < 32; o <<= 1) {
      t0 += __shfl_xor_sync(0xffffffffu, t0, o); t1 += __shfl_xor_sync(0xffffffffu, t1, o); t2 += __shfl_xor_sync(0xffffffffu, t2, o);
    }
    if (g == 0) { csum[warp][2 * c] = t0; csum[warp][2 * c + 1] = t1; csum[warp][8] = t2; }
  }
  const float nl = nrm[0] + nrm[1] + nrm[2] + nrm[3] + nrm[4] + nrm[5];
  const float nr = mat == 3 ? fmaxf(fmaxf(fmaxf(nrm[6], nrm[7]), fmaxf(nrm[8], nrm[9])), fmaxf(nrm[10], nrm[11]))
                            : nrm[6] + nrm[7] + nrm[8] + nrm[9] + nrm[10] + nrm[11];
  const float bound = __fsqrt_rn(nl) * __fsqrt_rn(nr) * 1.01f;
  const float f = isA ? 0.14724448f : 1.f;
  float sc = pow2_ceil(fmaxf(bound * (isA ? 0.14724448f / 160.f : mat == 1 ? 1.f / 16.f : 1.f / 64.f), 1e-30f));
  if (isA) sc = fminf(fmaxf(sc, 1.f), 32768.f);
  if (mat == 3) {
    if (blk == 0 && tid == 0) { g_par.kb = sc; g_par.ticket = 0; }
    if (sc <= 1.f && sc >= 1.f / 1024.f) sc = 1.f;
  }
  const float mul = f * __uint_as_float(0x7f000000u - __float_as_uint(sc));
  if (blk == 0 && tid == 0) (mat == 0 ? g_par.cS_t : mat == 1 ? g_par.kt : mat == 2 ? g_par.cS_s : g_par.kappa) = sc;
  asm volatile("bar.sync 1, 192;" ::: "memory");
  float mean[2];
#pragma unroll
  for (int b = 0; b < 2; b++)
    mean[b] = (csum[0][2 * c + b] + csum[1][2 * c + b] + csum[2][2 * c + b] + csum[3][2 * c + b] + csum[4][2 * c + b] + csum[5][2 * c + b]) *
              (1.f / 96.f);
  uint8_t* img = reinterpret_cast<uint8_t*>(g_wimg) + (mat == 0 ? 0 : mat == 1 ? kOffWt : mat == 2 ? kOffAs : kOffWs);
  const float vmean = (csum[0][8] + csum[1][8] + csum[2][8] + csum[3][8] + csum[4][8] + csum[5][8]) * (1.f / 96.f);
  float off = 0.f;
  if (mat == 2) {
    float q2 = 0.f;
#pragma unroll
    for (int q = 0; q < 4; q++) q2 = fmaf(d[q] - mean[q & 1], d[q] - mean[q & 1], q2);
#pragma unroll
    for (int o = 16; o; o >>= 1) q2 += __shfl_xor_sync(0xffffffffu, q2, o);
    if (lane == 0) nrm2[warp] = q2;
    asm volatile("bar.sync 1, 192;" ::: "memory");
    q2 = nrm2[0] + nrm2[1] + nrm2[2] + nrm2[3] + nrm2[4] + nrm2[5];
    off = 1.5f * pow2_ceil(fmaxf(__fsqrt_rn(q2 * (1.f / 768.f)) * mul * 3.f, 1e-4f));
  }
#pragma unroll
  for (int q = 0; q < 4; q++) {
    const int kp = ch_pos(16 * warp + g + 8 * (q >> 1)), np = ch_pos(blk * 8 + 2 * c + (q & 1));
    const uint32_t ko = (kp >> 5) * (mat < 2 ? kAtChunk : 6144) + (kp & 31) * 2;
    uint32_t a = ko + np * 64;
    a ^= ((a >> 7) & 3) << 4;
    float o = (d[q] - mean[q & 1]) * mul;
    o = mat == 2 ? o + off : __uint_as_float((__float_as_uint(o) + 0x8000u) & 0xffff0000u);
    *reinterpret_cast<__half*>(img + a) = __float2half_rn(o);
    if (mat == 1 && blk == 0) {
      a = (kp >> 5) * kAtChunk + (kp & 31) * 2 + (96 + 2 * c + (q & 1)) * 64;
      a ^= ((a >> 7) & 3) << 4;
      *reinterpret_cast<__half*>(reinterpret_cast<uint8_t*>(g_wimg) + a) = __float2half_rn((q & 1) ? ((q >> 1 ? v1 : v0) - vmean) * mul : 1.f / 96.f);
    }
  }
}

typedef CUresult (*EncodeFn)(CUtensorMap*, CUtensorMapDataType, cuuint32_t, void*, const cuuint64_t*, const cuuint64_t*,
                             const cuuint32_t*, const cuuint32_t*, CUtensorMapInterleave, CUtensorMapSwizzle,
                             CUtensorMapL2promotion, CUtensorMapFloatOOBfill);

}

extern "C" void kernel_launch(void* const* d_in, const int* in_sizes, int n_in, void* d_out, int out_size) {
  (void)in_sizes; (void)n_in; (void)out_size;
  static EncodeFn enc = nullptr;
  static int nsm = 0;
  if (!enc) {
    void* fn = nullptr;
    cudaDriverEntryPointQueryResult qr;
    cudaGetDriverEntryPoint("cuTensorMapEncodeTiled", &fn, cudaEnableDefault, &qr);
    enc = reinterpret_cast<EncodeFn>(fn);
    int dev = 0;
    cudaGetDevice(&dev);
    cudaDeviceGetAttribute(&nsm, cudaDevAttrMultiProcessorCount, dev);
    cudaFuncSetAttribute(swin_main, cudaFuncAttributeMaxDynamicSharedMemorySize, kSmemBytes);
  }
  CUtensorMap tm;
  const cuuint64_t dims[5] = {32, kW, kH, kT, 3};
  const cuuint64_t strides[4] = {192, 192ull * kW, 192ull * kW * kH, 64};
  const cuuint32_t box[5] = {32, 7, 7, 4, 3};
  const cuuint32_t es[5] = {1, 1, 1, 1, 1};
  enc(&tm, CU_TENSOR_MAP_DATA_TYPE_BFLOAT16, 5, d_in[0], dims, strides, box, es, CU_TENSOR_MAP_INTERLEAVE_NONE,
      CU_TENSOR_MAP_SWIZZLE_64B, CU_TENSOR_MAP_L2_PROMOTION_L2_128B, CU_TENSOR_MAP_FLOAT_OOB_FILL_NONE);

  cudaStream_t st = cudaStreamPerThread;
  swin_prep<<<4 * kPrepSplit, kPrepThreads, 0, st>>>(
      static_cast<const __nv_bfloat16*>(d_in[1]), static_cast<const __nv_bfloat16*>(d_in[2]),
      static_cast<const __nv_bfloat16*>(d_in[3]), static_cast<const __nv_bfloat16*>(d_in[4]));

  cudaLaunchConfig_t cfg = {};
  cfg.gridDim = dim3(nsm);
  cfg.blockDim = dim3(512);
  cfg.dynamicSmemBytes = kSmemBytes;
  cfg.stream = st;
  cudaLaunchAttribute at[1];
  at[0].id = cudaLaunchAttributeProgrammaticStreamSerialization;
  at[0].val.programmaticStreamSerializationAllowed = 1;
  cfg.attrs = at;
  cfg.numAttrs = 1;
  cudaLaunchKernelEx(&cfg, swin_main, tm, static_cast<uint8_t*>(d_out), mk_desc(1024), mk_desc(1024), (uint32_t)(kH * kW * 192));
}
```

```cpp
#include <cuda_runtime.h>
#include <cuda.h>
#include <cuda_bf16.h>
#include <cuda_fp16.h>
#include <stdint.h>

namespace {

constexpr int kH = 511, kW = 511, kT = 4;
constexpr int kNWX = 73, kNWIN = 73 * 73;
constexpr int kChunk = 12544;
constexpr int kPlane = 3136;
constexpr int kXBytes = 37632;
constexpr int kZero = kXBytes + 896, kFull = kXBytes + 1024, kDone = kFull + 8, kRel = kFull + 16, kFlag = kFull + 20, kExtra = kFull + 24;
constexpr int kSlot = 38912;
constexpr int kWMat = 18432;
constexpr int kAtChunk = 200 * 64;
constexpr int kOffWt = 104 * 64;
constexpr int kOffAs = 3 * kAtChunk, kOffWs = kOffAs + kWMat;
constexpr int kWBytes = kOffWs + kWMat;
constexpr int kSmemBytes = kWBytes + 4 * kSlot;

struct Params {
  float cS_t, cS_s;
  float kt;
  float kappa;
  float kb;
  uint32_t ticket;
};

__device__ uint4 g_wimg[kWBytes / 16];
__device__ __align__(16) Params g_par;
#define TR(i, k)
#define GT 254
#define GS 0x7eec
#define FT(k) do { if ((GT >> (k)) & 1) sfence(lane); } while (0)
#define FS(k) do { if ((GS >> (k)) & 1) sfence(tid); } while (0)
#define DB 0
#define KA 0
#define LF 0
#define SG 1
#define GO 0
#define PW 0
#define FV 0
#define EV 0
#define STH ""
#define PROMO ((CUtensorMapL2promotion)P1)
#define PM 1
#define P1 2
#define P2 2
#define PROMO2 ((CUtensorMapL2promotion)P2)
#define PF 2
#define PH 0
#define TM 0
#define SE 1
#define CB 0
#define NSP 4
#define L2P 1
#define DYN 1
#define NWH 8
#define MBHINT ""

__device__ __forceinline__ uint32_t smem_u32(const void* p) { return (uint32_t)__cvta_generic_to_shared(p); }
__device__ __forceinline__ void mbar_init(uint32_t a, int c) { asm volatile("mbarrier.init.shared::cta.b64 [%0], %1;" ::"r"(a), "r"(c)); }
__device__ __forceinline__ void mbar_expect(uint32_t a, int bytes) {
  asm volatile("mbarrier.arrive.expect_tx.shared::cta.b64 _, [%0], %1;" ::"r"(a), "r"(bytes) : "memory");
}
__device__ __forceinline__ void mbar_arrive(uint32_t a, uint32_t off = 0) {
  asm volatile("{\n.reg .pred p;\nsetp.eq.u32 p, %1, 0;\n@p mbarrier.arrive.shared::cta.b64 _, [%0];\n}" ::"r"(a), "r"(off) : "memory");
}
__device__ __forceinline__ void mbar_wait(uint32_t a, uint32_t par) {
  asm volatile(
      "{\n.reg .pred p;\n.reg .u32 n;\n"
      "mbarrier.try_wait.parity.shared::cta.b64 p, [%0], %1" MBHINT ";\n"
      "@p bra.uni WDONE;\n"
      "mov.u32 n, 0;\n"
      "WLOOP:\n"
      "mbarrier.try_wait.parity.shared::cta.b64 p, [%0], %1" MBHINT ";\n"
      "@p bra.uni WDONE;\n"
      "add.u32 n, n, 1;\n"
      "setp.lt.u32 p, n, 0x100000;\n"
      "@p bra.uni WLOOP;\n"
      "trap;\n"
      "WDONE:\n}" ::"r"(a), "r"(par & 1) : "memory");
}
__device__ __forceinline__ bool mbar_pending_or(uint32_t a, uint32_t par, uint32_t c) {
  uint32_t r;
  asm volatile("{\n.reg .pred p;\nmbarrier.test_wait.parity.shared::cta.b64 p, [%1], %2;\nsetp.ne.or.u32 p, %3, 0, !p;\n"
               "vote.sync.any.pred p, p, 0xffffffff;\nselp.b32 %0, 1, 0, p;\n}" : "=r"(r) : "r"(a), "r"(par & 1), "r"(c) : "memory");
  return r;
}
__device__ __forceinline__ uint32_t lds32(uint32_t a) {
  uint32_t v; asm volatile("ld.shared.b32 %0, [%1];" : "=r"(v) : "r"(a) : "memory"); return v;
}
__device__ __forceinline__ void sts32(uint32_t a, uint32_t v) { asm volatile("st.shared.b32 [%0], %1;" ::"r"(a), "r"(v) : "memory"); }
__device__ __forceinline__ void tma_load_win(uint32_t slot, const CUtensorMap* m, uint32_t w) {
  const uint32_t wy = (w * 57457u) >> 22, wx = w - wy * kNWX;
  mbar_expect(slot + kFull, kXBytes);
  asm volatile(
      "cp.async.bulk.tensor.5d.shared::cluster.global.mbarrier::complete_tx::bytes [%0], [%1, {%3,%4,%5,%3,%3}], [%2];" ::"r"(slot),
      "l"(m), "r"(slot + kFull), "r"(0), "r"(wx * 7), "r"(wy * 7)
      : "memory");
}
__device__ __forceinline__ void tma_prefetch_win(const CUtensorMap* m, uint32_t w, uint32_t t = 0) {
  const uint32_t wy = (w * 57457u) >> 22, wx = w - wy * kNWX;
  if (PM) asm volatile("cp.async.bulk.prefetch.tensor.3d.L2.global [%0, {%1,%2,%3}];" ::"l"(m + 1), "r"(wx * 168), "r"(wy * 7), "r"(t) : "memory");
  else asm volatile("cp.async.bulk.prefetch.tensor.5d.L2.global [%0, {%1,%2,%3,%1,%1}];" ::"l"(m), "r"(0), "r"(wx * 7), "r"(wy * 7) : "memory");
}
__device__ __forceinline__ void wg_fence() { asm volatile("wgmma.fence.sync.aligned;" ::: "memory"); }
__device__ __forceinline__ void wg_commit() { asm volatile("wgmma.commit_group.sync.aligned;" ::: "memory"); }
__device__ __forceinline__ void wg_wait() { asm volatile("wgmma.wait_group.sync.aligned 0;" ::: "memory"); }
template <int N>
__device__ __forceinline__ void pin(uint32_t* d) {
#pragma unroll
  for (int i = 0; i < N; i++) asm volatile("" : "+r"(d[i])::"memory");
}
__device__ __forceinline__ uint32_t fresh(uint32_t v) { asm volatile("" : "+r"(v)); return v; }
__device__ __forceinline__ float fresh(float v) { asm volatile("" : "+f"(v)); return v; }
template <int N>
__device__ __forceinline__ void launder(uint32_t* q) {
#pragma unroll
  for (int j = 0; j < N; j++) { uint32_t t; asm volatile("mov.b32 %0, %1;" : "=r"(t) : "r"(q[j])); q[j] = t; }
}
__device__ __forceinline__ void sfence(uint32_t& v) {
  asm volatile("{\n.reg .pred p;\nsetp.eq.u32 p, %1, 0x7fffffff;\n@p mov.u32 %0, %%clock;\n}" : "+r"(v) : "r"(gridDim.x) : "memory");
}
constexpr uint64_t mk_desc(uint32_t addr) { return ((uint64_t)0x80000020u << 32) | (addr >> 4) | (1u << 16); }

#define R4(d, i) "+r"(d[i]), "+r"(d[i + 1]), "+r"(d[i + 2]), "+r"(d[i + 3])
#define O4(d, i) "=r"(d[i]), "=r"(d[i + 1]), "=r"(d[i + 2]), "=r"(d[i + 3])
#define D26 "{%0,%1,%2,%3,%4,%5,%6,%7,%8,%9,%10,%11,%12,%13,%14,%15,%16,%17,%18,%19,%20,%21,%22,%23,%24,%25},"
#define D24 "{%0,%1,%2,%3,%4,%5,%6,%7,%8,%9,%10,%11,%12,%13,%14,%15,%16,%17,%18,%19,%20,%21,%22,%23},"
#define D14 "{%0,%1,%2,%3,%4,%5,%6,%7,%8,%9,%10,%11,%12,%13},"

template <int SC, int TB>
__device__ __forceinline__ void wgmma(uint32_t (&d)[24], const uint32_t* a, uint64_t db) {
  if (SC == 2)
    asm volatile("{\n.reg .pred p;\nsetp.eq.u32 p, %30, 0x7fffffff;\n"
                 "wgmma.mma_async.sync.aligned.m64n96k16.f16.f16.f16 " D24 "{%24,%25,%26,%27}, %28, p, 1, 1, %29;\n}"
                 : R4(d, 0), R4(d, 4), R4(d, 8), R4(d, 12), R4(d, 16), R4(d, 20)
                 : "r"(a[0]), "r"(a[1]), "r"(a[2]), "r"(a[3]), "l"(db), "n"(TB), "r"(gridDim.x));
  else if (SC)
    asm volatile("wgmma.mma_async.sync.aligned.m64n96k16.f16.f16.f16 " D24 "{%24,%25,%26,%27}, %28, 1, 1, 1, %29;"
                 : R4(d, 0), R4(d, 4), R4(d, 8), R4(d, 12), R4(d, 16), R4(d, 20)
                 : "r"(a[0]), "r"(a[1]), "r"(a[2]), "r"(a[3]), "l"(db), "n"(TB));
  else
    asm volatile("wgmma.mma_async.sync.aligned.m64n96k16.f16.f16.f16 " D24 "{%24,%25,%26,%27}, %28, 0, 1, 1, %29;"
                 : O4(d, 0), O4(d, 4), O4(d, 8), O4(d, 12), O4(d, 16), O4(d, 20)
                 : "r"(a[0]), "r"(a[1]), "r"(a[2]), "r"(a[3]), "l"(db), "n"(TB));
}
template <int SC, int TB>
__device__ __forceinline__ void wgmma(uint32_t (&d)[26], const uint32_t* a, uint64_t db) {
  if (SC)
    asm volatile("wgmma.mma_async.sync.aligned.m64n104k16.f16.f16.f16 " D26 "{%26,%27,%28,%29}, %30, 1, 1, 1, 0;"
                 : R4(d, 0), R4(d, 4), R4(d, 8), R4(d, 12), R4(d, 16), R4(d, 20), "+r"(d[24]), "+r"(d[25])
                 : "r"(a[0]), "r"(a[1]), "r"(a[2]), "r"(a[3]), "l"(db));
  else
    asm volatile("wgmma.mma_async.sync.aligned.m64n104k16.f16.f16.f16 " D26 "{%26,%27,%28,%29}, %30, 0, 1, 1, 0;"
                 : O4(d, 0), O4(d, 4), O4(d, 8), O4(d, 12), O4(d, 16), O4(d, 20), "=r"(d[24]), "=r"(d[25])
                 : "r"(a[0]), "r"(a[1]), "r"(a[2]), "r"(a[3]), "l"(db));
}
template <int SC, int TB>
__device__ __forceinline__ void wgmma(uint32_t (&d)[16], const uint32_t* a, uint64_t db) {
  if (SC)
    asm volatile("wgmma.mma_async.sync.aligned.m64n56k16.f16.f16.f16 " D14 "{%14,%15,%16,%17}, %18, 1, 1, 1, 0;"
                 : R4(d, 0), R4(d, 4), R4(d, 8), "+r"(d[12]), "+r"(d[13])
                 : "r"(a[0]), "r"(a[1]), "r"(a[2]), "r"(a[3]), "l"(db));
  else
    asm volatile("wgmma.mma_async.sync.aligned.m64n56k16.f16.f16.f16 " D14 "{%14,%15,%16,%17}, %18, 0, 1, 1, 0;"
                 : O4(d, 0), O4(d, 4), O4(d, 8), "=r"(d[12]), "=r"(d[13])
                 : "r"(a[0]), "r"(a[1]), "r"(a[2]), "r"(a[3]), "l"(db));
}
template <int SC, int OFF, int CH, int ND>
__device__ __forceinline__ void gemm(uint32_t (&d)[ND], const uint32_t* a, uint64_t db) {
  asm volatile("" : "+l"(db));
  wg_fence();
  wgmma<SC, 0>(d, a, db + OFF / 16);
#pragma unroll
  for (int k = 1; k < 6; k++) wgmma<1, 0>(d, a + 4 * k, db + (OFF + (k >> 1) * CH + (k & 1) * 32) / 16);
  wg_commit();
}
__device__ __forceinline__ void lds128(uint32_t* r, uint32_t a) {
  asm volatile("ld.shared.v4.b32 {%0,%1,%2,%3}, [%4];" : "=r"(r[0]), "=r"(r[1]), "=r"(r[2]), "=r"(r[3]) : "r"(a) : "memory");
}
__device__ __forceinline__ void ldsm4(uint32_t* r, uint32_t a) {
  asm volatile("ldmatrix.sync.aligned.m8n8.x4.shared.b16 {%0,%1,%2,%3}, [%4];"
               : "=r"(r[0]), "=r"(r[1]), "=r"(r[2]), "=r"(r[3]) : "r"(a) : "memory");
}
__device__ __forceinline__ void stsm4(uint32_t a, const uint32_t* r) {
  asm volatile("stmatrix.sync.aligned.m8n8.x4.shared.b16 [%0], {%1,%2,%3,%4};" ::"r"(a), "r"(r[0]), "r"(r[1]), "r"(r[2]), "r"(r[3])
               : "memory");
}
__device__ __forceinline__ void stg3(uint8_t* p, const uint32_t* r, uint32_t off) {
  asm volatile("{\n.reg .pred p;\nsetp.eq.u32 p, %13, 0;\n@p st.global" STH ".v4.b32 [%0], {%1,%2,%3,%4};\n"
               "@p st.global" STH ".v4.b32 [%0+64], {%5,%6,%7,%8};\n@p st.global" STH ".v4.b32 [%0+128], {%9,%10,%11,%12};\n}" ::"l"(p),
               "r"(r[0]), "r"(r[1]), "r"(r[2]), "r"(r[3]), "r"(r[4]), "r"(r[5]), "r"(r[6]), "r"(r[7]), "r"(r[8]), "r"(r[9]), "r"(r[10]), "r"(r[11]),
               "r"(off) : "memory");
}
__device__ __forceinline__ uint32_t pack_h2(float lo, float hi) {
  uint32_t r; asm("cvt.rn.f16x2.f32 %0, %1, %2;" : "=r"(r) : "f"(hi), "f"(lo)); return r;
}
__device__ __forceinline__ uint32_t pack_h2_sat(float lo, float hi) {
  uint32_t r; asm("cvt.rn.satfinite.f16x2.f32 %0, %1, %2;" : "=r"(r) : "f"(hi), "f"(lo)); return r;
}
__device__ __forceinline__ uint32_t pack_bf2(float lo, float hi) {
  uint32_t r; asm("cvt.rn.bf16x2.f32 %0, %1, %2;" : "=r"(r) : "f"(hi), "f"(lo)); return r;
}
__device__ __forceinline__ __half2 as_h2(uint32_t v) { return *reinterpret_cast<__half2*>(&v); }
__device__ __forceinline__ uint32_t as_u(__half2 v) { return *reinterpret_cast<uint32_t*>(&v); }
__device__ __forceinline__ float2 unpack_h2(uint32_t v) { return __half22float2(as_h2(v)); }
__device__ __forceinline__ float low_f(uint32_t v) { return __low2float(as_h2(v)); }
__device__ __forceinline__ uint32_t h2ex2(uint32_t v) { uint32_t r; asm("ex2.approx.f16x2 %0, %1;" : "=r"(r) : "r"(v)); return r; }
__device__ __forceinline__ uint32_t h2max(uint32_t a, uint32_t b) { return as_u(__hmax2(as_h2(a), as_h2(b))); }
__device__ __forceinline__ uint32_t h2add(uint32_t a, uint32_t b) { return as_u(__hadd2(as_h2(a), as_h2(b))); }
__device__ __forceinline__ uint32_t h2sub(uint32_t a, uint32_t b) { return as_u(__hsub2(as_h2(a), as_h2(b))); }
__device__ __forceinline__ uint32_t h2mul(uint32_t a, uint32_t b) { return as_u(__hmul2(as_h2(a), as_h2(b))); }
__device__ __forceinline__ uint32_t h2neg(uint32_t a) { return as_u(__hneg2(as_h2(a))); }
__device__ __forceinline__ uint32_t h2fma(uint32_t a, uint32_t b, uint32_t c) { return as_u(__hfma2(as_h2(a), as_h2(b), as_h2(c))); }
__device__ __forceinline__ uint32_t lo2(uint32_t v) { return as_u(__low2half2(as_h2(v))); }
__device__ __forceinline__ uint32_t hi2(uint32_t v) { return as_u(__high2half2(as_h2(v))); }
__device__ __forceinline__ uint32_t fold_add(uint32_t a, uint32_t b) { return h2add(__byte_perm(a, b, 0x5410), __byte_perm(a, b, 0x7632)); }
__device__ __forceinline__ uint32_t sel(uint32_t p, uint32_t a, uint32_t b) {
  uint32_t r; asm("{\n.reg .pred p;\nsetp.ne.u32 p, %3, 0;\nselp.b32 %0, %1, %2, p;\n}" : "=r"(r) : "r"(a), "r"(b), "r"(p)); return r;
}
__device__ __forceinline__ float sel4(uint32_t c, float a0, float a1, float a2, float a3) {
  return __uint_as_float(sel(c & 2, sel(c & 1, __float_as_uint(a3), __float_as_uint(a2)), sel(c & 1, __float_as_uint(a1), __float_as_uint(a0))));
}
__device__ __forceinline__ float rcp_fast(float v) { float r; asm("rcp.approx.ftz.f32 %0, %1;" : "=f"(r) : "f"(v)); return r; }
__device__ __forceinline__ float rsq_fast(float v) { float r; asm("rsqrt.approx.ftz.f32 %0, %1;" : "=f"(r) : "f"(v)); return r; }
__device__ __forceinline__ uint32_t shfl_x(uint32_t v, int m) { return __shfl_xor_sync(0xffffffffu, v, m); }
__device__ __forceinline__ uint32_t shfl_q(uint32_t v, int i) { return __shfl_sync(0xffffffffu, v, i, 4); }
__device__ __forceinline__ float quad_sum(float v) {
  v += __shfl_xor_sync(0xffffffffu, v, 1);
  return v + __shfl_xor_sync(0xffffffffu, v, 2);
}
__device__ __forceinline__ uint32_t score_scale(const float* p) { const float v = __ldcg(p); return pack_h2(v, v); }

constexpr float kEps96 = 1e-5f * 96.f * 96.f;
__device__ __forceinline__ float2 stat_f32(uint32_t e) {
  const float2 h = unpack_h2(e);
  return make_float2(__uint_as_float(sel(e & 0x8000u, (e << 16) & 0x7fff0000u, __float_as_uint(h.x))),
                     __uint_as_float(sel(e & 0x8000u, e & 0xffff0000u, __float_as_uint(h.y))));
}

struct Tile {
  uint32_t a;
  uint32_t next;
  uint32_t n;
  int live;
  uint32_t stat, wrap;
  uint32_t flag;
  uint32_t gate;
};
struct TPar { float kt, sgmin, outmax; };

__device__ __forceinline__ void load_rows(uint32_t* x0, uint32_t* x1, uint32_t a0, uint32_t a1) {
  a0 ^= (a0 >> 3) & 0x30; a1 ^= (a1 >> 3) & 0x30;
  lds128(x0, a0); lds128(x1, a1);
  lds128(x0 + 4, (a0 ^ 32) + kChunk); lds128(x1 + 4, (a1 ^ 32) + kChunk);
  lds128(x0 + 8, a0 + 2 * kChunk); lds128(x1 + 8, a1 + 2 * kChunk);
}
__device__ __forceinline__ void to_half(uint32_t (&z)[24], const uint32_t* x) {
#pragma unroll
  for (int j = 0; j < 24; j += 2) {
    const int o = j < 12 ? 2 * j : 2 * j - 23;
    uint32_t t;
    asm("cvt.rz.f16x2.f32 %0, %1, %2;" : "=r"(t) : "f"(__uint_as_float(x[j + 1])), "f"(__uint_as_float(x[j])));
    z[o] = pack_h2(__uint_as_float(x[j] << 16), __uint_as_float(x[j + 1] << 16));
    z[o + 2] = t & 0xfff8fff8u;
  }
}
__device__ __forceinline__ void load_general(uint32_t (&z)[24], uint32_t a0, float& ie0, float& ie1, float& m0, float& m1) {
  float acc[48];
  uint32_t x0[12], x1[12];
  load_rows(x0, x1, a0, a0 + kPlane);
#pragma unroll
  for (int j = 0; j < 12; j++) {
    acc[4 * j] = __uint_as_float(x0[j] << 16); acc[4 * j + 1] = __uint_as_float(x0[j] & 0xffff0000u);
    acc[4 * j + 2] = __uint_as_float(x1[j] << 16); acc[4 * j + 3] = __uint_as_float(x1[j] & 0xffff0000u);
  }
  float s[4], q[4];
#pragma unroll
  for (int e = 0; e < 4; e++) { s[e] = acc[e]; q[e] = acc[e] * acc[e]; }
#pragma unroll
  for (int j = 4; j < 48; j++) { s[j & 3] += acc[j]; q[j & 3] = fmaf(acc[j], acc[j], q[j & 3]); }
  const float s0 = quad_sum(s[0] + s[1]), s1 = quad_sum(s[2] + s[3]), q0 = quad_sum(q[0] + q[1]), q1 = quad_sum(q[2] + q[3]);
  const float u0 = rsq_fast(fmaxf(fmaf(-s0, s0, fmaf(q0, 96.f, kEps96)), kEps96));
  const float u1 = rsq_fast(fmaxf(fmaf(-s1, s1, fmaf(q1, 96.f, kEps96)), kEps96));
  const float n0 = -s0 * u0, n1 = -s1 * u1;
  ie0 = 96.f * u0; ie1 = 96.f * u1;
  m0 = s0 * (1.f / 96.f); m1 = s1 * (1.f / 96.f);
#pragma unroll
  for (int j = 0; j < 12; j++) {
    const int o = 8 * (j >> 1) + (j & 1);
    z[2 * j] = pack_h2(fmaf(acc[o], ie0, n0), fmaf(acc[o + 4], ie0, n0));
    z[2 * j + 1] = pack_h2(fmaf(acc[o + 2], ie1, n1), fmaf(acc[o + 6], ie1, n1));
  }
}
template <bool kDown>
__device__ __forceinline__ uint32_t sumsq2(const uint32_t* z) {
  uint32_t q0, q1;
#pragma unroll
  for (int j = 0; j < 12; j++) {
    const uint32_t u = kDown ? h2mul(z[2 * j], 0x1c001c00u) : z[2 * j], v = kDown ? h2mul(z[2 * j + 1], 0x1c001c00u) : z[2 * j + 1];
    q0 = j ? h2fma(u, u, q0) : h2mul(u, u); q1 = j ? h2fma(v, v, q1) : h2mul(v, v);
  }
  return fold_add(q0, q1);
}
template <bool kDown>
__device__ __forceinline__ float row_sumsq(const uint32_t* z0, const uint32_t* z1, uint32_t c) {
  const uint32_t a = sumsq2<kDown>(z0), b = sumsq2<kDown>(z1);
  uint32_t t = h2add(sel(c & 2, b, a), shfl_x(sel(c & 2, a, b), 2));
  t = h2add(t, shfl_x(t, 1));
  return low_f(sel(c & 1, t >> 16, t));
}
__device__ __forceinline__ void scores2(const uint32_t* q, const uint32_t* z0, const uint32_t* z1, uint32_t* f) {
  uint32_t d[8];
#pragma unroll
  for (int j = 0; j < 12; j++) {
    const uint32_t kk[4] = {z0[2 * j], z0[2 * j + 1], z1[2 * j], z1[2 * j + 1]};
#pragma unroll
    for (int e = 0; e < 4; e++) {
      d[e] = j ? h2fma(q[2 * j], kk[e], d[e]) : h2mul(q[2 * j], kk[e]);
      d[4 + e] = j ? h2fma(q[2 * j + 1], kk[e], d[4 + e]) : h2mul(q[2 * j + 1], kk[e]);
    }
  }
#pragma unroll
  for (int e = 0; e < 4; e++) f[e] = fold_add(d[2 * e], d[2 * e + 1]);
}
struct Xch { uint32_t keep[2], got[2]; };
__device__ __forceinline__ Xch pair_send(const uint32_t* a, const uint32_t* b, uint32_t c, int m) {
  Xch x;
#pragma unroll
  for (int e = 0; e < 2; e++) { x.keep[e] = fresh(sel(c & m, b[e], a[e])); x.got[e] = shfl_x(sel(c & m, a[e], b[e]), m); }
  return x;
}
__device__ __forceinline__ void pair_recv(uint32_t* k, const Xch& x) { k[0] = h2add(x.keep[0], x.got[0]); k[1] = h2add(x.keep[1], x.got[1]); }
__device__ __forceinline__ void mix2(uint32_t* y, const uint32_t* v, uint32_t c0, uint32_t c1) {
#pragma unroll
  for (int j = 0; j < 12; j++) {
    y[2 * j] = h2fma(v[2 * j + 1], hi2(c0), h2fma(v[2 * j], lo2(c0), y[2 * j]));
    y[2 * j + 1] = h2fma(v[2 * j + 1], hi2(c1), h2fma(v[2 * j], lo2(c1), y[2 * j + 1]));
  }
  pin<24>(y);
}
__device__ __forceinline__ void norm_store(uint32_t* y, uint32_t r0, uint32_t r1, uint32_t ma) {
#pragma unroll
  for (int j = 0; j < 12; j++) { y[2 * j] = h2fma(y[2 * j], lo2(r0), hi2(r0)); y[2 * j + 1] = h2fma(y[2 * j + 1], lo2(r1), hi2(r1)); }
  ma ^= (ma >> 3) & 0x30;
  const uint32_t mb = ma ^ 32;
  stsm4(ma, y); stsm4(mb, y + 4);
  stsm4(mb + kChunk, y + 8); stsm4(ma + kChunk, y + 12);
  stsm4(ma + 2 * kChunk, y + 16); stsm4(mb + 2 * kChunk, y + 20);
}

__device__ __forceinline__ void gate_open(uint32_t id) {
  asm volatile("{\n.reg .pred p;\nsetp.ne.u32 p, %0, 0;\n@p barrier.cta.arrive.aligned %0, 256;\n}" ::"r"(id) : "memory");
}

template <bool kDirect>
__device__ __forceinline__ bool temporal(uint64_t da, uint64_t db, const Tile& T, const TPar& P, bool scaled, uint32_t& lane, uint32_t lst) {
  const uint32_t c = lane;
  const uint32_t a0 = T.a + lane * 16 + (lane >= 4 * T.n ? T.next : 0);
  uint32_t z0[24], z1[24], q0[26], q1[24], v0[24], w1[26], nn = 0, ng = 0, ca0 = 0, ca1 = 0;
  uint32_t* const v1 = w1 + 2;
  float ie = 1.f, mm = 0.f;
  bool tiny = false;
  if (kDirect) {
    uint32_t x[48];
    load_rows(x, x + 12, a0, a0 + kPlane);
    load_rows(x + 24, x + 36, a0 + 2 * kPlane, a0 + 3 * kPlane);
    FT(0);
    to_half(z0, x);
    gemm<0, 0, kAtChunk>(q0, z0, da);
    FT(1);
    to_half(z1, x + 24);
    const uint32_t n0 = sumsq2<false>(z0), n1 = sumsq2<false>(z1);
    nn = fresh(sel(c & 2, n1, n0)); ng = shfl_x(sel(c & 2, n0, n1), 2);
    pin<24>(z1); FT(2);
  } else {
    float e[4], m[4];
    load_general(z0, a0, e[0], e[1], m[0], m[1]);
    pin<24>(z0); sfence(lane);
    load_general(z1, a0 + 2 * kPlane, e[2], e[3], m[2], m[3]);
    ie = sel4(c, e[0], e[1], e[2], e[3]);
    mm = sel4(c, m[0], m[1], m[2], m[3]);
    tiny = __any_sync(0xffffffffu, ie * P.kt > 400.f);
    if (tiny) {
      float u = 0.f;
#pragma unroll
      for (int r = 0; r < 4; r++) {
        float t = 0.f;
#pragma unroll
        for (int j = 0; j < 12; j++) { const float2 f = unpack_h2((r & 2 ? z1 : z0)[2 * j + (r & 1)]); t = fmaf(f.x, f.x, fmaf(f.y, f.y, t)); }
        u = fmaxf(u, quad_sum(t));
      }
      const float t = fminf(ie, 9.8f * rsq_fast(fmaxf(u, 2e-7f)) * rcp_fast(fresh(P.kt)));
      const uint32_t a = pack_h2(__fdividef(t, ie), 0.f);
      ca0 = __byte_perm(shfl_q(a, 0), shfl_q(a, 1), 0x5410); ca1 = __byte_perm(shfl_q(a, 2), shfl_q(a, 3), 0x5410);
      ie = t;
    }
    gemm<0, 0, kAtChunk>(q0, z0, da);
  }
  uint32_t f[4], k0[2], k1[2], sk[2];
  if (SG == 0) gate_open(T.gate);
  wg_wait(); pin<26>(q0);
  gemm<0, 0, kAtChunk>(q1, z1, DB ? db : da);
  if (SG == 1) gate_open(T.gate);
  FT(3);
  if (kDirect) { nn = h2add(nn, ng); ng = shfl_x(nn, 1); FT(4); }
  scores2(q0, z0, z1, f);
  const uint32_t nu0 = fresh(__byte_perm(q0[24], q0[25], 0x7632)), m01 = fresh(sel(c & 1, q0[25], q0[24]));
  Xch xc = pair_send(f, f + 2, c, 1);
  if (SG == 4) gate_open(T.gate);
  sfence(lane);
  wg_wait(); pin<24>(q1);
  gemm<0, kOffWt - 512, kAtChunk>(w1, z1, da);
  if (SG == 2) gate_open(T.gate);
  FT(5);
  pair_recv(k0, xc);
  float e2 = 0.f, lim = 0.f;
  if (kDirect) {
    nn = h2add(nn, ng);
    e2 = fresh(fmaf(low_f(sel(c & 1, nn >> 16, nn)), 1.f / 96.f, 1e-5f));
    lim = fresh(e2 <= 4.f ? fmaxf(0.5f * e2, 4e-4f) : __uint_as_float(0x7fffffffu));
  }
  scores2(q1, z0, z1, f);
  xc = pair_send(f, f + 2, c, 1);
  pin<2>(k0); sfence(lane);
  wg_wait(); pin<26>(w1);
  float mz = 0.f, d2 = 0.f;
  if (kDirect) {
    mz = low_f(sel(c & 2, sel(c & 1, w1[1], w1[0]), m01));
    d2 = fmaf(-mz, mz, e2);
    asm volatile("{\n.reg .pred p;\nsetp.lt.s32 p, %3, %4;\nsetp.ltu.and.f32 p, %1, %2, p;\n@p st.volatile.shared.f32 [%0], %2;\n}" ::"r"(T.flag), "f"(d2),
                 "f"(lim), "r"(lane), "r"(T.live) : "memory");
  }
  gemm<0, kOffWt, kAtChunk>(v0, z0, da);
  if (SG == 3) gate_open(T.gate);
  FT(6);
  uint32_t cw[8], mu;
  {
    uint32_t rc = 0, r0 = 0, r1 = 0;
    if (kDirect) {
      const float r = rsq_fast(d2);
      rc = pack_h2(r, r);
      r0 = __byte_perm(shfl_q(rc, 0), shfl_q(rc, 1), 0x5410); r1 = __byte_perm(shfl_q(rc, 2), shfl_q(rc, 3), 0x5410);
    }
    pair_recv(k1, xc);
    pair_recv(sk, pair_send(k0, k1, c, 2));
    if (kDirect) { sk[0] = h2mul(sk[0], r0); sk[1] = h2mul(sk[1], r1); }
    uint32_t mx = h2max(sk[0], sk[1]);
    mx = h2max(lo2(mx), hi2(mx));
    if (kDirect) {
      const uint32_t nm = h2mul(h2neg(mx), rc);
      sk[0] = h2fma(sk[0], rc, nm); sk[1] = h2fma(sk[1], rc, nm);
    } else {
      sk[0] = h2sub(sk[0], mx); sk[1] = h2sub(sk[1], mx);
      if (scaled) {
        const uint32_t cs = score_scale(&g_par.cS_t);
        sk[0] = h2mul(sk[0], cs); sk[1] = h2mul(sk[1], cs);
      }
    }
    sk[0] = h2ex2(sk[0]); sk[1] = h2ex2(sk[1]);
    const uint32_t sm = h2add(sk[0], sk[1]);
    const float iv = (kDirect ? P.kt : P.kt * ie) * rcp_fast(low_f(h2add(lo2(sm), hi2(sm))));
    const uint32_t inv = pack_h2(iv, iv);
    if (kDirect) { sk[0] = h2mul(sk[0], r0); sk[1] = h2mul(sk[1], r1); }
    sk[0] = h2mul(sk[0], inv); sk[1] = h2mul(sk[1], inv);
#pragma unroll
    for (int i = 0; i < 4; i++) { cw[2 * i] = shfl_q(sk[0], i); cw[2 * i + 1] = shfl_q(sk[1], i); }
    mu = h2fma(sk[1], __byte_perm(w1[0], w1[1], 0x7632), h2mul(sk[0], nu0));
    mu = h2add(lo2(mu), hi2(mu));
  }
  uint32_t bad = 0;
  if (kDirect) {
    mix2(z1, v1, cw[5], cw[7]);
    FT(7);
    wg_wait(); pin<24>(v0);
    mix2(z1, v0, cw[4], cw[6]);
    sfence(lane);
    bad = lds32(T.flag);
  } else {
    wg_wait(); pin<24>(v0);
    if (tiny) {
#pragma unroll
      for (int j = 0; j < 12; j++) {
        z0[2 * j] = h2mul(z0[2 * j], lo2(ca0)); z0[2 * j + 1] = h2mul(z0[2 * j + 1], hi2(ca0));
        z1[2 * j] = h2mul(z1[2 * j], lo2(ca1)); z1[2 * j + 1] = h2mul(z1[2 * j + 1], hi2(ca1));
      }
    }
    mix2(z1, v1, cw[5], cw[7]);
    mix2(z1, v0, cw[4], cw[6]);
  }
  mix2(z0, v1, cw[1], cw[3]);
  mix2(z0, v0, cw[0], cw[2]);
  float qq = row_sumsq<false>(z0, z1, c);
  if (__any_sync(0xffffffffu, (!(qq < 65000.f) & ((int)lane < T.live)) | (bad != 0))) {
    if (kDirect && __any_sync(0xffffffffu, bad != 0)) return false;
    const float q2 = row_sumsq<true>(z0, z1, c) * 65536.f;
    qq = qq < 65000.f ? qq : q2;
  }
  const float rf = kDirect ? rsq_fast(fmaxf(fmaf(-mz, mz, fmaf(qq, 1.f / 96.f, 1e-5f)), 1e-5f)) : rsq_fast(fmaf(qq, 1.f / 96.f, 1e-5f * ie * ie));
  const uint32_t rn = pack_h2_sat(rf, -mz * rf);
  uint32_t rr[4];
#pragma unroll
  for (int i = 0; i < 4; i++) rr[i] = shfl_q(rn, i);
  if (!L2P) lst = (lane & 7) * 64 + (lane & 8) * (kPlane / 8) + (lane & 16);
  const uint32_t ma = T.a + lst + ((lane & 7) >= T.n ? T.next : 0);
  norm_store(z0, rr[0], rr[1], ma);
  norm_store(z1, rr[2], rr[3], ma + 2 * kPlane);
  const float2 rm = unpack_h2(rn);
  const float sg = rcp_fast(kDirect ? rm.x : rm.x * ie);
  mm = kDirect ? fmaf(-rm.y, sg, low_f(mu)) : fmaf(low_f(mu) * rm.x, sg, mm);
  const bool ok = (sg >= P.sgmin) & (fmaf(sg, 9.8f, fabsf(mm)) < P.outmax);
  asm volatile("{\n.reg .pred p;\nsetp.lt.s32 p, %2, %3;\n@p st.shared.b32 [%0], %1;\n}" ::"r"(
                   T.stat + fresh((lane & 3) * (kSlot - 1) + lane + (lane >= 4 * T.n ? T.wrap : 0))),
               "r"(sel(ok, pack_h2(sg, mm), pack_bf2(sg, mm) | 0x8000u)), "r"(lane), "r"(T.live) : "memory");
  return true;
}

__device__ __forceinline__ void run_T(uint32_t ring, uint64_t d0, uint64_t d1, uint32_t nfull, uint32_t nrem, bool helper, int wg, int wp, uint32_t lane,
                                      const TPar& P, bool scaled, uint32_t pdir) {
  uint32_t lst = (lane & 7) * 64 + (lane & 8) * (kPlane / 8) + (lane & 16);
  if (L2P == 2) lst = __shfl_sync(0xffffffffu, lst, lane);
  uint32_t p0 = 32 * (wg & 1) + (helper ? 0 : 64) + 8 * wp;
  uint32_t npx = 49 * nfull, pstop = npx - 6 * 49 + 8 * wp;
  if (helper) pstop = 0;
  uint32_t pgap = 0;
  Tile T;
  T.flag = ring + wg * kSlot + kFlag;
  T.gate = helper && !(wg & 1) ? 0 : 5 + (wg & 1);
  while (true) {
    const uint32_t iw = (p0 * 21400u) >> 20, ow = p0 - 49 * iw;
    const uint32_t slot = ring + (iw & 3) * kSlot, dn = (iw & 3) == 3 ? -3 * kSlot : kSlot;
    if (wp == 3) TR(p0 >> 5, 1);
    if (GO == 0) asm volatile("{\n.reg .pred p;\nsetp.eq.u32 p, %1, 0;\n@p barrier.cta.sync.aligned %0, 256;\n}" ::"r"(6 - (wg & 1)), "r"((uint32_t)helper) : "memory");
    mbar_wait(slot + kFull, iw >> 2);
    if (ow > 41) mbar_wait(slot + dn + kFull, (iw + 1) >> 2);
    if (GO == 1) asm volatile("{\n.reg .pred p;\nsetp.eq.u32 p, %1, 0;\n@p barrier.cta.sync.aligned %0, 256;\n}" ::"r"(6 - (wg & 1)), "r"((uint32_t)helper) : "memory");
    if (wp == 3) TR(p0 >> 5, 2);
    T.a = slot + ow * 64; T.next = dn - kPlane; T.n = 49 - ow;
    T.live = 4 * (npx - p0);
    T.stat = ring + kXBytes + (p0 - 196 * (iw >> 2)) * 4; T.wrap = (iw & 3) == 3 ? -784 : 0;
    const bool direct = p0 >= pdir;
    bool done = false;
    if (direct) done = temporal<true>(d0, d1, T, P, false, lane, lst);
    if (!done) {
      Tile G = T;
      if (direct) {
        asm volatile("barrier.cta.sync.aligned %0, 128;" ::"r"(wg + 1) : "memory");
        asm volatile("st.shared.b32 [%0], %1;\nfence.acq_rel.cta;" ::"r"(T.flag), "r"(0) : "memory");
        G.gate = 0;
        pgap = p0 == pdir ? 4 * pgap + 64 : 0;
        pdir = p0 + 64 + pgap;
      }
      temporal<false>(d1, d0, G, P, scaled, lane, lst);
    }
    const uint32_t pn = __shfl_sync(0xffffffffu, p0 + 64, 0);
    bool last = false;
    if (pn >= pstop) {
      if (helper) last = true;
      else if (pstop < npx - 4 * 49) {
        if (((wg & 1) | wp | lane) == 0) {
          const uint32_t nb = gridDim.x, nwh = min(max((int)(2 * nrem - nb), (int)(nrem * NWH / 16)), nrem);
          const uint32_t r = DYN ? atomicAdd(&g_par.ticket, 1u) : blockIdx.x, j = r - nwh;
          sts32(ring + kExtra, r < nwh ? (nfull * nb + r) * 4 + 3 : j < 2 * (nrem - nwh) ? (nfull * nb + nwh + (j >> 1)) * 4 + 1 + (j & 1) : 0);
        }
        __syncwarp();
        pstop = npx - 2 * 49 + 8 * wp;
      } else if (pstop < npx) {
        if (__shfl_sync(0xffffffffu, lds32(ring + kExtra), 0)) npx += 49;
        pstop = npx + 8 * wp;
      } else last = true;
    }
    if (FV == 0) asm volatile("fence.proxy.async.shared::cta;" ::: "memory");
    if (FV == 1) asm volatile("fence.proxy.async::generic.release.sync_restrict::shared::cta.cluster;" ::: "memory");
    if (FV == 2) asm volatile("fence.proxy.async;" ::: "memory");
    __syncwarp();
    mbar_arrive(slot + kDone + (lane >= 4 * T.n ? dn : 0), lane & 3);
    __syncwarp();
    if (wp == 3) TR(p0 >> 5, 3);
    if (last) break;
    p0 = pn;
  }
}

struct Frame {
  bool light;
  uint32_t sta;
  uint32_t oo;
  uint32_t e0, e1;
};
__device__ __forceinline__ uint32_t frame_init(Frame& F, uint32_t ring, uint32_t t, int wp, int lane) {
  wp = (wp + t) & 3;
  F.light = wp == 3;
  F.sta = ring + t * kSlot + kXBytes + 64 * wp;
  const uint32_t r = 16 * wp + (lane >> 2);
  F.oo = ((r / 7) * (kW - 7) + r) * 192u + (lane & 3) * 16 + (((((r + 8) / 7 - r / 7) * (kW - 7) + 8) * 3u) << 20);
  F.e0 = F.e1 = 0x8000u;
  const uint32_t am = t * kPlane + wp * 1024 + ((lane * 65) & 0x3d0);
  return F.light && (lane & 15) ? kZero : am ^ ((am >> 3) & 0x30);
}
template <bool F>
__device__ __forceinline__ void load_frame(uint32_t (&v)[24], uint32_t ma, uint32_t slot, uint32_t& tid) {
  const uint32_t st = ma < kXBytes ? kChunk : 0, mb = ma ^ 32;
  uint32_t a[6] = {ma, mb, mb + st, ma + st, ma + 2 * st, mb + 2 * st};
  pin<6>(a);
  if (F) sfence(tid);
#pragma unroll
  for (int k = 0; k < 6; k++) ldsm4(v + 4 * k, slot + a[k]);
}
__device__ __forceinline__ uint32_t load_stats(Frame& F, uint32_t ia, uint32_t tid) {
  const uint32_t a = fresh(tid & (F.light ? 0 : 0x1c)), u = F.sta + ia * 196;
  F.e0 = lds32(a + u);
  F.e1 = lds32(a + fresh(u + (F.light ? 0 : 32)));
  return a;
}
__device__ __forceinline__ uint32_t is_wide(const Frame& F) {
  uint32_t r;
  asm volatile("{\n.reg .pred p;\n.reg .b32 t;\nlop3.b32 t, %1, %2, 0x8000, 0xa8;\nsetp.ne.u32 p, t, 0;\nvote.sync.ballot.b32 %0, p, 0xffffffff;\n}"
               : "=r"(r) : "r"(F.e0), "r"(F.e1));
  return r;
}
template <int OFF>
__device__ __forceinline__ void gemm_u(uint32_t (&u)[24], const uint32_t* s, uint64_t db) {
  constexpr uint32_t kMN = (((kChunk >> 4) - 1) << 16) + OFF / 16;
  asm volatile("" : "+l"(db));
  wg_fence();
  wgmma<2, 1>(u, s, db + kMN); wgmma<1, 1>(u, s + 4, db + kMN + 64); wgmma<1, 1>(u, s + 8, db + kMN + 128); wgmma<1, 1>(u, s + 12, db + kMN + 192);
  wg_commit();
}
__device__ __forceinline__ uint32_t key48(uint32_t (&s)[16], uint32_t tid) {
  return fresh(sel(tid & 3, 0xfc00fc00u, __byte_perm(s[12], s[13], 0x5410)));
}
__device__ __forceinline__ uint32_t amax3(uint32_t a, uint32_t b, uint32_t c) {
  return as_u(__hmax2(__hmax2(__habs2(as_h2(a)), __habs2(as_h2(b))), __habs2(as_h2(c))));
}
struct Quad { uint32_t v[4]; };
__device__ __forceinline__ Quad soft_exp(uint32_t (&s)[16], uint32_t& t, uint32_t (&v)[24], const Frame& F, float2& e) {
  const uint32_t am = h2max(h2max(h2max(amax3(s[0], s[1], s[2]), amax3(s[3], s[4], s[5])), amax3(s[6], s[7], s[8])), h2max(amax3(s[9], s[10], s[11]), t));
  e = make_float2(low_f(F.e0), low_f(F.e1));
  uint32_t rare, sp[NSP + 1];
#pragma unroll
  for (int j = 0; j < NSP; j++) sp[j] = fresh(h2ex2(s[j]));
  asm("{\n.reg .pred p, q;\n.reg .b32 t;\nlop3.b32 t, %2, %3, 0x8000, 0xa8;\nsetp.eq.u32 q, t, 0;\nmov.b32 t, 0x49004900;\n"
      "setp.le.and.f16x2 p|q, %1, t, q;\nand.pred p, p, q;\nselp.b32 %0, 0, 1, p;\n}" : "=r"(rare) : "r"(am), "r"(F.e0), "r"(F.e1));
  if (__any_sync(0xffffffffu, rare)) {
    const uint32_t x0 = h2max(h2max(h2max(s[0], s[2]), h2max(s[4], s[6])), h2max(s[8], s[10]));
    const uint32_t x1 = h2max(h2max(h2max(s[1], s[3]), h2max(s[5], s[7])), h2max(s[9], s[11]));
    uint32_t mx = h2max(h2max(__byte_perm(x0, x1, 0x5410), __byte_perm(x0, x1, 0x7632)), t);
    mx = h2max(mx, shfl_x(mx, 1));
    mx = h2max(mx, shfl_x(mx, 2));
#pragma unroll
    for (int j = 0; j < 6; j++) { s[2 * j] = h2sub(s[2 * j], lo2(mx)); s[2 * j + 1] = h2sub(s[2 * j + 1], hi2(mx)); }
    t = h2sub(t, mx);
    if (is_wide(F)) {
      const uint32_t cs = score_scale(&g_par.cS_s);
#pragma unroll
      for (int j = 0; j < 12; j++) s[j] = h2mul(s[j], cs);
      t = h2mul(t, cs);
      const float s0 = stat_f32(F.e0).x, s1 = stat_f32(F.e1).x;
      const float kb = __ldcg(&g_par.kb), ik = rcp_fast(__ldcg(&g_par.kappa));
      e.x = fmaxf(s0, kb); e.y = fmaxf(s1, kb);
      const uint32_t aw = pack_h2(__fdividef(s0, e.x), __fdividef(s1, e.y));
      e.x *= ik; e.y *= ik;
#pragma unroll
      for (int j = 0; j < 12; j++) { v[2 * j] = h2mul(v[2 * j], lo2(aw)); v[2 * j + 1] = h2mul(v[2 * j + 1], hi2(aw)); }
    }
#pragma unroll
    for (int j = 0; j < NSP; j++) sp[j] = h2ex2(s[j]);
  }
#pragma unroll
  for (int j = 0; j < 12; j++) s[j] = j < NSP ? sp[j] : h2ex2(s[j]);
  t = h2ex2(t);
  Quad q;
  q.v[0] = h2add(t, fold_add(h2add(h2add(h2add(s[0], s[2]), h2add(s[4], s[6])), h2add(s[8], s[10])),
                             h2add(h2add(h2add(s[1], s[3]), h2add(s[5], s[7])), h2add(s[9], s[11]))));
#pragma unroll
  for (int i = 1; i < 4; i++) q.v[i] = shfl_x(q.v[0], i);
  return q;
}
__device__ __forceinline__ void soft_norm(uint32_t (&s)[16], uint32_t& t, const Quad& q, const Frame& F, float2 e, uint32_t tid) {
  const float2 d = unpack_h2(h2add(h2add(q.v[0], q.v[1]), h2add(q.v[2], q.v[3])));
  const uint32_t cb = pack_h2(rcp_fast(d.x * e.x), rcp_fast(d.y * e.y)) & (sel(tid & 28, 0u, 0xffffu) | fresh(F.light ? 0u : 0xffffffffu));
#pragma unroll
  for (int j = 0; j < 6; j++) { s[2 * j] = h2mul(s[2 * j], lo2(cb)); s[2 * j + 1] = h2mul(s[2 * j + 1], hi2(cb)); }
  t = fresh(h2mul(t, cb));
  pin<12>(s);
}
__device__ __forceinline__ void soft_tail(uint32_t (&s)[16], uint32_t t) {
  s[12] = t & 0xffffu; s[13] = t >> 16;
  asm volatile("mov.b32 %0, 0;\nmov.b32 %1, 0;" : "=r"(s[14]), "=r"(s[15]));
}
template <int H>
__device__ __forceinline__ uint8_t* row_ptr(const Frame& F, uint8_t* o) {
  const uint32_t oo = fresh(F.oo);
  if (H) asm volatile("mad.wide.u32 %0, %1, 64, %0;" : "+l"(o) : "r"(oo >> 20));
  else { o += oo & 0xfffffu; asm volatile("" : "+l"(o)); }
  return o;
}
template <int H>
__device__ __forceinline__ void affine(uint32_t* r, const uint32_t (&v)[24], const Frame& F) {
  const uint32_t e = H ? F.e1 : F.e0;
#pragma unroll
  for (int j = 0; j < 12; j++) r[j] = h2fma(v[2 * j + H], lo2(e), hi2(e));
  pin<12>(r);
}
template <int H>
__device__ __forceinline__ void finish(uint32_t* r, const Frame& F, uint8_t*& o, uint32_t off, uint32_t a, uint32_t m, uint32_t& tid, uint32_t a2 = 0) {
  o = row_ptr<H>(F, o);
#pragma unroll
  for (int j = 0; j < 12; j += 2) { const float2 f = unpack_h2(r[j]), g = unpack_h2(r[j + 1]); r[j] = pack_bf2(f.x, g.x); r[j + 1] = pack_bf2(f.y, g.y); }
  pin<12>(r);
  if (SE) sfence(tid);
  stg3(o, r, off | (fresh(a) & m) | (a2 & 0x4000));
}
__device__ __forceinline__ void finish_wide(const uint32_t (&v)[24], const Frame& F, uint8_t* o, uint32_t tid) {
  const float kb = __ldcg(&g_par.kb);
#pragma unroll
  for (int h = 0; h < 2; h++) {
    const float2 z = stat_f32(h ? F.e1 : F.e0);
    const float w = fmaxf(z.x, kb);
    uint32_t r[12];
#pragma unroll
    for (int j = 0; j < 12; j += 2) {
      const float2 f = unpack_h2(v[2 * j + h]), g = unpack_h2(v[2 * j + 2 + h]);
      r[j] = pack_bf2(fmaf(f.x, w, z.y), fmaf(g.x, w, z.y)); r[j + 1] = pack_bf2(fmaf(f.y, w, z.y), fmaf(g.y, w, z.y));
    }
    o = h ? row_ptr<1>(F, o) : row_ptr<0>(F, o);
    stg3(o, r, F.light ? (h ? 1 : tid & 28) : 0);
  }
}
__device__ __forceinline__ uint32_t window_ahead(uint32_t ring, uint32_t i, uint32_t nfull, uint32_t w) {
  return i + 4 < nfull ? w + 4 * gridDim.x : i + 4 == nfull ? lds32(ring + kExtra) >> 2 : 0;
}

__device__ __forceinline__ void run_S(uint32_t ring, uint64_t d0, uint64_t d1, uint32_t frame, uint32_t nfull, uint32_t i0, uint32_t i1, uint32_t w, int sg, int wp, int lane,
                                      const CUtensorMap* tm, uint8_t* __restrict__ out) {
  Frame A, B;
  uint32_t tid = lane + (frame_init(A, ring, 2 * sg, wp, lane) << 4) + (frame_init(B, ring, 2 * sg + 1, wp, lane) << 16);
  uint32_t va[24], vb[24], x[24], sa[16], sc[16], r0[12], r1[12], ta, tb;
  Quad rs;
  float2 e;
#pragma unroll
  for (int j = 0; j < 24; j++) { vb[j] = 0; x[j] = 0; }
  out += sg * 2 * frame;
  uint8_t *ob = out, *o;
  const uint64_t dr = d0 + (uint32_t)(kWBytes / 16 + sg * (2 * kPlane / 16));
  uint32_t i = i0, slot = ring + (i & 3) * kSlot;
  mbar_wait(slot + kDone, i >> 2);
  load_frame<false>(va, (tid >> 4) & 0xfff0u, slot, tid);
  do {
    const uint32_t ia = i & 3;
    auto prefetch = [&] {
      if (PH || sg == 0) {
        if ((tid & 31) == 0) {
          const uint32_t wn = window_ahead(ring, i, nfull, w);
          if (wn) tma_prefetch_win(tm, wn, PH ? 2 * sg : 0);
        }
        __syncwarp();
      }
    };
    gemm<2, kOffAs, 6144>(x, va, d0);
    FS(0);
    const uint32_t wb = is_wide(B);
    if (wb && i != i0) finish_wide(vb, B, ob + frame, tid);
    affine<0>(r0, vb, B); affine<1>(r1, vb, B);
    const uint32_t lb = (tid >> 16) & 0xfff0u;
    load_frame<true>(vb, lb, slot, tid);
    const uint32_t g4 = load_stats(A, ia, tid);
    uint64_t dp = dr + ia * (kSlot / 16);
    asm volatile("" : "+l"(dp));
    FS(1);
    o = ob + frame;
    finish<0>(r0, B, o, wb, g4, B.light ? 28 : 0, tid, KA ? lb : 0);
    FS(2);
    wg_wait(); pin<24>(x); if (TM & 1) launder<24>(x);
    gemm<0, 0, kChunk>(sa, x, dp);
    if (!B.light) finish<1>(r1, B, o, wb, 0, 0, tid);
    else if (PF == 2) prefetch();
    ob = out + (size_t)((((w * 57457u) >> 22) * (7 * kW - 7 * kNWX) + w * 7) * 192u);
    FS(3);
    wg_wait(); pin<14>(sa);
    gemm<2, kOffAs, 6144>(x, vb, d1);
    FS(4);
    ta = key48(sa, tid);
    rs = soft_exp(sa, ta, va, A, e);
    FS(5);
    wg_wait(); pin<24>(x); if (TM & 2) launder<24>(x);
    gemm<0, kPlane, kChunk>(sc, x, dp);
    FS(6);
    load_stats(B, ia, tid);
    soft_norm(sa, ta, rs, A, e, tid);
    if (PF == 4 && A.light) prefetch();
    FS(7);
    wg_wait(); pin<14>(sc);
    tb = key48(sc, tid);
    sfence(tid);
    soft_tail(sa, ta);
    gemm_u<0>(x, sa, dp);
    FS(8);
    rs = soft_exp(sc, tb, vb, B, e);
    FS(9);
    wg_wait(); pin<24>(x); if (TM & 4) launder<24>(x);
    gemm<1, kOffWs, 6144>(va, x, d0);
    FS(10);
    soft_norm(sc, tb, rs, B, e, tid);
    soft_tail(sc, tb);
    const uint32_t wa = is_wide(A);
    if (PF == 6 && B.light) prefetch();
    FS(11);
    wg_wait(); pin<24>(va);
    gemm_u<kPlane>(x, sc, dp);
    FS(12);
    const uint32_t sn = ring + ((i + 1) & 3) * kSlot;
    const bool slow = mbar_pending_or(sn + kDone, (i + 1) >> 2, PW ? wa : wa | A.light);
    affine<0>(r0, va, A);
    o = ob;
    finish<0>(r0, A, o, wa, tid, A.light ? 28 : 0, tid);
    FS(13);
    wg_wait(); pin<24>(x); if (TM & 8) launder<24>(x);
    gemm<1, kOffWs, 6144>(vb, x, d1);
    FS(14);
    affine<1>(r1, va, A);
    if (wp == 2) TR(i + 1, 4 + 2 * sg);
    auto release = [&] {
        if ((tid & 31) == 0) {
          uint32_t old;
          asm volatile("atom.relaxed.cta.shared::cta.inc.u32 %0, [%1], 1;" : "=r"(old) : "r"(slot + kRel) : "memory");
          if (PF == 3 && !old && i + 5 < nfull) tma_prefetch_win(tm, w + 5 * gridDim.x);
          if (old) {
            const uint32_t wn = window_ahead(ring, i, nfull, w);
            if (PF == 1 && i + 5 < nfull) tma_prefetch_win(tm, w + 5 * gridDim.x);
            if (wn) tma_load_win(slot, tm, wn);
            else mbar_arrive(slot + kFull);
          }
        }
        __syncwarp();
    };
    if (PW == 1 && A.light) release();
    if (slow) {
      if (PW != 1 && A.light) release();
      if (wa) finish_wide(va, A, ob, tid);
      if (i + 1 < i1) mbar_wait(sn + kDone, (i + 1) >> 2);
    }
    if (wp == 2) TR(i + 1, 5 + 2 * sg);
    const uint32_t la = (tid >> 4) & 0xfff0u;
    load_frame<LF>(va, la, sn, tid);
    if (!A.light) finish<1>(r1, A, o, wa, la, 0x4000, tid);
    else if (PW == 2 && !slow) release();
    wg_wait(); pin<24>(vb);
    launder<24>(vb);
    launder<24>(va);
    slot = sn; w += gridDim.x;
  } while (++i < i1);
  const uint32_t wb = is_wide(B);
  if (wb) finish_wide(vb, B, ob + frame, tid);
  o = ob + frame;
  affine<0>(r0, vb, B); finish<0>(r0, B, o, wb, tid, B.light ? 28 : 0, tid);
  affine<1>(r1, vb, B); finish<1>(r1, B, o, B.light | wb, 0, 0, tid);
}

struct Maps { CUtensorMap load, prefetch; };
__global__ void __launch_bounds__(512, 1) swin_main(const __grid_constant__ Maps tms, uint8_t* __restrict__ out, const uint64_t d0,
                                                    const uint64_t d1, const uint32_t frame) {
  extern __shared__ __align__(1024) uint8_t smem[];
  const CUtensorMap& tm = tms.load;
  const uint32_t sb = CB ? 1024u : smem_u32(smem), ring = sb + kWBytes;
  const int tid = threadIdx.x;
  const int wg = __shfl_sync(0xffffffffu, tid >> 7, 0);
  const int wp = __shfl_sync(0xffffffffu, (tid >> 5) & 3, 0);
  const int lane = tid & 31;
  const uint32_t b = blockIdx.x, nb = gridDim.x;
  const uint32_t nfull = kNWIN / nb, nrem = kNWIN - nfull * nb;
  if (tid == 0) {
    if (smem_u32(smem) != 1024 || nfull > 700 || nfull < 12) __trap();
#pragma unroll
    for (int i = 0; i < 4; i++) {
      mbar_init(ring + i * kSlot + kFull, 1);
      mbar_init(ring + i * kSlot + kDone, 49);
      sts32(ring + i * kSlot + kRel, 0); sts32(ring + i * kSlot + kFlag, 0);
    }
    asm volatile("fence.mbarrier_init.release.cluster;" ::: "memory");
    for (int i = 0; i < 2; i++) tma_load_win(ring + i * kSlot, &tm, b + i * nb);
  }
  __syncwarp();
  if (wg == 1 || wg == 2)
    asm volatile("st.shared.v4.b32 [%0], {%1,%1,%1,%1};" ::"r"(ring + ((tid - 128) >> 6) * kSlot + kXBytes + (tid & 63) * 16), "r"(0) : "memory");
  __syncthreads();
  asm volatile("griddepcontrol.wait;" ::: "memory");
#pragma unroll
  for (int q = 0; q < kWBytes / 16 / 512; q++)
    asm volatile("cp.async.cg.shared.global [%0], [%1], 16;" ::"r"(sb + (tid + q * 512) * 16), "l"(g_wimg + tid + q * 512) : "memory");
  if (wg == 0 && wp < 3) {
    static_assert(kWBytes / 16 == 9 * 512 + 96, "weight copy split");
    const int e = tid + 9 * 512;
    asm volatile("cp.async.cg.shared.global [%0], [%1], 16;" ::"r"(sb + e * 16), "l"(g_wimg + e) : "memory");
  }
  const float4 p0 = __ldcg(reinterpret_cast<const float4*>(&g_par));
  const float kb = __ldcg(&g_par.kb);
  TPar P;
  P.kt = p0.z;
  P.sgmin = p0.y != 1.f || p0.w != 1.f ? 1e30f : fmaxf(0.0045f, kb * 0.011f);
  P.outmax = fmaf(kb, -627.2f, 60000.f);
  const bool scaled = __any_sync(0xffffffffu, p0.x != 1.f);
  const uint32_t pdir = __ballot_sync(0xffffffffu, scaled || !(P.kt <= 256.f));
  asm volatile("cp.async.wait_all;\nfence.proxy.async.shared::cta;" ::: "memory");
  __syncthreads();
  if (tid == 128) for (int i = 2; i < 4; i++) tma_load_win(ring + i * kSlot, &tm, b + i * nb);
  __syncwarp();
  const bool isT = wg < 2;
  run_T(ring, d0, d1, nfull, nrem, !isT, wg, wp, lane, P, scaled, pdir);
  const uint32_t ex = isT ? __shfl_sync(0xffffffffu, lds32(ring + kExtra), 0) : 3;
  if ((ex >> (wg & 1)) & 1) run_S(ring, d0, d1, frame, nfull, isT ? nfull : 0, nfull + isT, isT ? ex >> 2 : b, wg & 1, wp, lane, &tm, out);
}

__device__ __forceinline__ int ch_pos(int ch) { return 32 * (ch >> 5) + 16 * ((ch >> 2) & 1) + 8 * (ch & 1) + 2 * ((ch >> 3) & 3) + ((ch >> 1) & 1); }
__device__ __forceinline__ float pow2_ceil(float v) {
  return __uint_as_float((__float_as_uint(v) + 0x7fffffu) & 0x7f800000u);
}

constexpr int kPrepSplit = 12;
constexpr int kPrepThreads = 384;
__global__ void __launch_bounds__(kPrepThreads) swin_prep(const __nv_bfloat16* __restrict__ wqkv_t, const __nv_bfloat16* __restrict__ wo_t,
                                                          const __nv_bfloat16* __restrict__ wqkv_s, const __nv_bfloat16* __restrict__ wo_s) {
  asm volatile("griddepcontrol.launch_dependents;");
  __shared__ __align__(16) uint32_t raw[2][96][52];
  __shared__ __align__(16) uint32_t mu[3][52];
  __shared__ float nrm[12], nrm2[6], csum[6][9];
  const int mat = blockIdx.x / kPrepSplit, blk = blockIdx.x % kPrepSplit;
  const int tid = threadIdx.x, lane = tid & 31, warp = tid >> 5, g = lane >> 2, c = lane & 3;
  const __nv_bfloat16* wqkv = mat < 2 ? wqkv_t : wqkv_s;
  const __nv_bfloat16* wo = mat < 2 ? wo_t : wo_s;
  const bool isA = (mat & 1) == 0;
  {
    uint4 v[3], u[3];
#pragma unroll
    for (int q = 0; q < 3; q++) {
      const int e = tid + q * kPrepThreads, i = e / 12, c8 = (e % 12) * 8;
      v[q] = __ldg(reinterpret_cast<const uint4*>(wqkv + i * 288 + (isA ? 0 : 192) + c8));
      u[q] = __ldg(reinterpret_cast<const uint4*>(isA ? wqkv + i * 288 + 96 + c8 : wo + i * 96 + c8));
    }
#pragma unroll
    for (int q = 0; q < 3; q++) {
      const int e = tid + q * kPrepThreads, i = e / 12, c4 = (e % 12) * 4;
      *reinterpret_cast<uint4*>(&raw[0][i][c4]) = v[q];
      *reinterpret_cast<uint4*>(&raw[1][i][c4]) = u[q];
    }
  }
  __syncthreads();
  {
    const int m = warp / 6, cp = (warp % 6) * 8 + g;
    float s0 = 0.f, s1 = 0.f, q0 = 0.f, q1 = 0.f;
#pragma unroll
    for (int i = 0; i < 24; i++) {
      const uint32_t w = raw[m][4 * i + c][cp];
      const float lo = __uint_as_float(w << 16), hi = __uint_as_float(w & 0xffff0000u);
      s0 += lo; s1 += hi; q0 = fmaf(lo, lo, q0); q1 = fmaf(hi, hi, q1);
    }
    s0 = quad_sum(s0) * (1.f / 96.f); s1 = quad_sum(s1) * (1.f / 96.f); q0 = quad_sum(q0); q1 = quad_sum(q1);
    if (mat == 1 && m == 1) {
      float r0 = 0.f, r1 = 0.f;
#pragma unroll
      for (int i = 0; i < 12; i++) {
        const uint32_t w0 = raw[1][2 * cp][4 * i + c], w1 = raw[1][2 * cp + 1][4 * i + c];
        r0 += __uint_as_float(w0 << 16) + __uint_as_float(w0 & 0xffff0000u);
        r1 += __uint_as_float(w1 << 16) + __uint_as_float(w1 & 0xffff0000u);
      }
      r0 = quad_sum(r0) * (1.f / 96.f); r1 = quad_sum(r1) * (1.f / 96.f);
      s0 = r0; s1 = r1;
    }
    if (m == 1 && c == 0) {
      const uint32_t hi = mat == 3 ? 0u : pack_bf2(s0, s1);
      mu[0][cp] = hi;
      mu[1][cp] = mat == 3 ? 0u : pack_bf2(s0 - __uint_as_float(hi << 16), s1 - __uint_as_float(hi & 0xffff0000u));
      mu[2][cp] = 0u;
    }
    if (m == 0 || isA) {
      q0 = fmaxf(fmaf(-96.f * s0, s0, q0), 0.f) + q0 * 1e-6f;
      q1 = fmaxf(fmaf(-96.f * s1, s1, q1), 0.f) + q1 * 1e-6f;
    }
    const bool usemax = m == 1 && mat == 3;
    float t = usemax ? fmaxf(q0, q1) : q0 + q1;
#pragma unroll
    for (int o = 4; o < 32; o <<= 1) { const float z = __shfl_xor_sync(0xffffffffu, t, o); t = usemax ? fmaxf(t, z) : t + z; }
    if (lane == 0) nrm[warp] = t;
  }
  __syncthreads();
  if (warp >= 6) return;
  float d[4] = {0.f, 0.f, 0.f, 0.f}, e[4] = {0.f, 0.f, 0.f, 0.f}, v0, v1;
  {
    const uint32_t arow = smem_u32(&raw[0][16 * warp + (lane & 15)][(lane >> 4) * 4]);
    const uint32_t brow = isA ? smem_u32(&raw[1][blk * 8 + (lane & 7)][(lane >> 3) * 4]) : smem_u32(&raw[1][lane][blk * 4]);
    const uint32_t mrow = smem_u32(&mu[min(lane & 7, 2)][(lane >> 3) * 4]);
#pragma unroll
    for (int k2 = 0; k2 < 3; k2++) {
      uint32_t b[4], m[4];
      if (isA) ldsm4(b, brow + k2 * 64);
      else asm volatile("ldmatrix.sync.aligned.m8n8.x4.trans.shared.b16 {%0,%1,%2,%3}, [%4];"
                        : "=r"(b[0]), "=r"(b[1]), "=r"(b[2]), "=r"(b[3]) : "r"(brow + k2 * (32 * 208)) : "memory");
      ldsm4(m, mrow + k2 * 64);
#pragma unroll
      for (int hf = 0; hf < 2; hf++) {
        uint32_t a[4];
        ldsm4(a, arow + (2 * k2 + hf) * 32);
        asm volatile("mma.sync.aligned.m16n8k16.row.col.f32.bf16.bf16.f32 {%0,%1,%2,%3},{%4,%5,%6,%7},{%8,%9},{%0,%1,%2,%3};"
                     : "+f"(d[0]), "+f"(d[1]), "+f"(d[2]), "+f"(d[3])
                     : "r"(a[0]), "r"(a[1]), "r"(a[2]), "r"(a[3]), "r"(b[2 * hf]), "r"(b[2 * hf + 1]));
        asm volatile("mma.sync.aligned.m16n8k16.row.col.f32.bf16.bf16.f32 {%0,%1,%2,%3},{%4,%5,%6,%7},{%8,%9},{%0,%1,%2,%3};"
                     : "+f"(e[0]), "+f"(e[1]), "+f"(e[2]), "+f"(e[3])
                     : "r"(a[0]), "r"(a[1]), "r"(a[2]), "r"(a[3]), "r"(m[2 * hf]), "r"(m[2 * hf + 1]));
      }
    }
    v0 = __shfl_sync(0xffffffffu, e[0] + e[1], lane & ~3); v1 = __shfl_sync(0xffffffffu, e[2] + e[3], lane & ~3);
    d[0] -= v0; d[1] -= v0; d[2] -= v1; d[3] -= v1;
    float t0 = d[0] + d[2], t1 = d[1] + d[3], t2 = v0 + v1;
#pragma unroll
    for (int o = 4; o < 32; o <<= 1) {
      t0 += __shfl_xor_sync(0xffffffffu, t0, o); t1 += __shfl_xor_sync(0xffffffffu, t1, o); t2 += __shfl_xor_sync(0xffffffffu, t2, o);
    }
    if (g == 0) { csum[warp][2 * c] = t0; csum[warp][2 * c + 1] = t1; csum[warp][8] = t2; }
  }
  const float nl = nrm[0] + nrm[1] + nrm[2] + nrm[3] + nrm[4] + nrm[5];
  const float nr = mat == 3 ? fmaxf(fmaxf(fmaxf(nrm[6], nrm[7]), fmaxf(nrm[8], nrm[9])), fmaxf(nrm[10], nrm[11]))
                            : nrm[6] + nrm[7] + nrm[8] + nrm[9] + nrm[10] + nrm[11];
  const float bound = __fsqrt_rn(nl) * __fsqrt_rn(nr) * 1.01f;
  const float f = isA ? 0.14724448f : 1.f;
  float sc = pow2_ceil(fmaxf(bound * (isA ? 0.14724448f / 160.f : mat == 1 ? 1.f / 16.f : 1.f / 64.f), 1e-30f));
  if (isA) sc = fminf(fmaxf(sc, 1.f), 32768.f);
  if (mat == 3) {
    if (blk == 0 && tid == 0) { g_par.kb = sc; g_par.ticket = 0; }
    if (sc <= 1.f && sc >= 1.f / 1024.f) sc = 1.f;
  }
  const float mul = f * __uint_as_float(0x7f000000u - __float_as_uint(sc));
  if (blk == 0 && tid == 0) (mat == 0 ? g_par.cS_t : mat == 1 ? g_par.kt : mat == 2 ? g_par.cS_s : g_par.kappa) = sc;
  asm volatile("bar.sync 1, 192;" ::: "memory");
  float mean[2];
#pragma unroll
  for (int b = 0; b < 2; b++)
    mean[b] = (csum[0][2 * c + b] + csum[1][2 * c + b] + csum[2][2 * c + b] + csum[3][2 * c + b] + csum[4][2 * c + b] + csum[5][2 * c + b]) *
              (1.f / 96.f);
  uint8_t* img = reinterpret_cast<uint8_t*>(g_wimg) + (mat == 0 ? 0 : mat == 1 ? kOffWt : mat == 2 ? kOffAs : kOffWs);
  const float vmean = (csum[0][8] + csum[1][8] + csum[2][8] + csum[3][8] + csum[4][8] + csum[5][8]) * (1.f / 96.f);
  float off = 0.f;
  if (mat == 2) {
    float q2 = 0.f;
#pragma unroll
    for (int q = 0; q < 4; q++) q2 = fmaf(d[q] - mean[q & 1], d[q] - mean[q & 1], q2);
#pragma unroll
    for (int o = 16; o; o >>= 1) q2 += __shfl_xor_sync(0xffffffffu, q2, o);
    if (lane == 0) nrm2[warp] = q2;
    asm volatile("bar.sync 1, 192;" ::: "memory");
    q2 = nrm2[0] + nrm2[1] + nrm2[2] + nrm2[3] + nrm2[4] + nrm2[5];
    off = 1.5f * pow2_ceil(fmaxf(__fsqrt_rn(q2 * (1.f / 768.f)) * mul * 3.f, 1e-4f));
  }
#pragma unroll
  for (int q = 0; q < 4; q++) {
    const int kp = ch_pos(16 * warp + g + 8 * (q >> 1)), np = ch_pos(blk * 8 + 2 * c + (q & 1));
    const uint32_t ko = (kp >> 5) * (mat < 2 ? kAtChunk : 6144) + (kp & 31) * 2;
    uint32_t a = ko + np * 64;
    a ^= ((a >> 7) & 3) << 4;
    float o = (d[q] - mean[q & 1]) * mul;
    o = mat == 2 ? o + off : __uint_as_float((__float_as_uint(o) + 0x8000u) & 0xffff0000u);
    *reinterpret_cast<__half*>(img + a) = __float2half_rn(o);
    if (mat == 1 && blk == 0) {
      a = (kp >> 5) * kAtChunk + (kp & 31) * 2 + (96 + 2 * c + (q & 1)) * 64;
      a ^= ((a >> 7) & 3) << 4;
      *reinterpret_cast<__half*>(reinterpret_cast<uint8_t*>(g_wimg) + a) = __float2half_rn((q & 1) ? ((q >> 1 ? v1 : v0) - vmean) * mul : 1.f / 96.f);
    }
  }
}

typedef CUresult (*EncodeFn)(CUtensorMap*, CUtensorMapDataType, cuuint32_t, void*, const cuuint64_t*, const cuuint64_t*,
                             const cuuint32_t*, const cuuint32_t*, CUtensorMapInterleave, CUtensorMapSwizzle,
                             CUtensorMapL2promotion, CUtensorMapFloatOOBfill);

}

extern "C" void kernel_launch(void* const* d_in, const int* in_sizes, int n_in, void* d_out, int out_size) {
  (void)in_sizes; (void)n_in; (void)out_size;
  static EncodeFn enc = nullptr;
  static int nsm = 0;
  if (!enc) {
    void* fn = nullptr;
    cudaDriverEntryPointQueryResult qr;
    cudaGetDriverEntryPoint("cuTensorMapEncodeTiled", &fn, cudaEnableDefault, &qr);
    enc = reinterpret_cast<EncodeFn>(fn);
    int dev = 0;
    cudaGetDevice(&dev);
    cudaDeviceGetAttribute(&nsm, cudaDevAttrMultiProcessorCount, dev);
    cudaFuncSetAttribute(swin_main, cudaFuncAttributeMaxDynamicSharedMemorySize, kSmemBytes);
  }
  Maps tms;
  CUtensorMap& tm = tms.load;
  const cuuint64_t dims[5] = {32, kW, kH, kT, 3};
  const cuuint64_t strides[4] = {192, 192ull * kW, 192ull * kW * kH, 64};
  const cuuint32_t box[5] = {32, 7, 7, 4, 3};
  const cuuint32_t es[5] = {1, 1, 1, 1, 1};
  enc(&tm, CU_TENSOR_MAP_DATA_TYPE_BFLOAT16, 5, d_in[0], dims, strides, box, es, CU_TENSOR_MAP_INTERLEAVE_NONE,
      CU_TENSOR_MAP_SWIZZLE_64B, PROMO, CU_TENSOR_MAP_FLOAT_OOB_FILL_NONE);

  const cuuint64_t dims2[3] = {24ull * kW, kH, kT};
  const cuuint64_t strides2[2] = {192ull * kW, 192ull * kW * kH};
  const cuuint32_t box2[3] = {168, 7, PH ? 2 : 4};
  enc(&tms.prefetch, CU_TENSOR_MAP_DATA_TYPE_UINT64, 3, d_in[0], dims2, strides2, box2, es, CU_TENSOR_MAP_INTERLEAVE_NONE,
      CU_TENSOR_MAP_SWIZZLE_NONE, PROMO2, CU_TENSOR_MAP_FLOAT_OOB_FILL_NONE);

  cudaStream_t st = cudaStreamPerThread;
  swin_prep<<<4 * kPrepSplit, kPrepThreads, 0, st>>>(
      static_cast<const __nv_bfloat16*>(d_in[1]), static_cast<const __nv_bfloat16*>(d_in[2]),
      static_cast<const __nv_bfloat16*>(d_in[3]), static_cast<const __nv_bfloat16*>(d_in[4]));

  cudaLaunchConfig_t cfg = {};
  cfg.gridDim = dim3(nsm);
  cfg.blockDim = dim3(512);
  cfg.dynamicSmemBytes = kSmemBytes;
  cfg.stream = st;
  cudaLaunchAttribute at[1];
  at[0].id = cudaLaunchAttributeProgrammaticStreamSerialization;
  at[0].val.programmaticStreamSerializationAllowed = 1;
  cfg.attrs = at;
  cfg.numAttrs = 1;
  cudaLaunchKernelEx(&cfg, swin_main, tms, static_cast<uint8_t*>(d_out), mk_desc(1024), mk_desc(1024), (uint32_t)(kH * kW * 192));
}
```

```cpp
#include <cuda_runtime.h>
#include <cuda.h>
#include <cuda_bf16.h>
#include <cuda_fp16.h>
#include <stdint.h>

namespace {

constexpr int kH = 511, kW = 511, kT = 4;
constexpr int kNWX = 73, kNWIN = 73 * 73;
constexpr int kChunk = 12544;
constexpr int kPlane = 3136;
constexpr int kXBytes = 37632;
constexpr int kZero = kXBytes + 896, kFull = kXBytes + 1024, kDone = kFull + 8, kRel = kFull + 16, kFlag = kFull + 20, kExtra = kFull + 24;
constexpr int kSlot = 38912;
constexpr int kWMat = 18432;
constexpr int kAtChunk = 200 * 64;
constexpr int kOffWt = 104 * 64;
constexpr int kOffAs = 3 * kAtChunk, kOffWs = kOffAs + kWMat;
constexpr int kWBytes = kOffWs + kWMat;
constexpr int kSmemBytes = kWBytes + 4 * kSlot;

struct Params {
  float cS_t, cS_s;
  float kt;
  float kappa;
  float kb;
  uint32_t ticket;
};

__device__ uint4 g_wimg[kWBytes / 16];
__device__ __align__(16) Params g_par;

__device__ __forceinline__ uint32_t smem_u32(const void* p) { return (uint32_t)__cvta_generic_to_shared(p); }
__device__ __forceinline__ void mbar_init(uint32_t a, int c) { asm volatile("mbarrier.init.shared::cta.b64 [%0], %1;" ::"r"(a), "r"(c)); }
__device__ __forceinline__ void mbar_expect(uint32_t a, int bytes) {
  asm volatile("mbarrier.arrive.expect_tx.shared::cta.b64 _, [%0], %1;" ::"r"(a), "r"(bytes) : "memory");
}
__device__ __forceinline__ void mbar_arrive(uint32_t a, uint32_t off = 0) {
  asm volatile("{\n.reg .pred p;\nsetp.eq.u32 p, %1, 0;\n@p mbarrier.arrive.shared::cta.b64 _, [%0];\n}" ::"r"(a), "r"(off) : "memory");
}
__device__ __forceinline__ void mbar_wait(uint32_t a, uint32_t par) {
  asm volatile(
      "{\n.reg .pred p;\n.reg .u32 n;\n"
      "mbarrier.try_wait.parity.shared::cta.b64 p, [%0], %1;\n"
      "@p bra.uni WDONE;\n"
      "mov.u32 n, 0;\n"
      "WLOOP:\n"
      "mbarrier.try_wait.parity.shared::cta.b64 p, [%0], %1;\n"
      "@p bra.uni WDONE;\n"
      "add.u32 n, n, 1;\n"
      "setp.lt.u32 p, n, 0x100000;\n"
      "@p bra.uni WLOOP;\n"
      "trap;\n"
      "WDONE:\n}" ::"r"(a), "r"(par & 1) : "memory");
}
__device__ __forceinline__ bool mbar_pending_or(uint32_t a, uint32_t par, uint32_t c) {
  uint32_t r;
  asm volatile("{\n.reg .pred p;\nmbarrier.test_wait.parity.shared::cta.b64 p, [%1], %2;\nsetp.ne.or.u32 p, %3, 0, !p;\n"
               "vote.sync.any.pred p, p, 0xffffffff;\nselp.b32 %0, 1, 0, p;\n}" : "=r"(r) : "r"(a), "r"(par & 1), "r"(c) : "memory");
  return r;
}
__device__ __forceinline__ uint32_t lds32(uint32_t a) {
  uint32_t v; asm volatile("ld.shared.b32 %0, [%1];" : "=r"(v) : "r"(a) : "memory"); return v;
}
__device__ __forceinline__ void sts32(uint32_t a, uint32_t v) { asm volatile("st.shared.b32 [%0], %1;" ::"r"(a), "r"(v) : "memory"); }
__device__ __forceinline__ void tma_load_win(uint32_t slot, const CUtensorMap* m, uint32_t w) {
  const uint32_t wy = (w * 57457u) >> 22, wx = w - wy * kNWX;
  mbar_expect(slot + kFull, kXBytes);
  asm volatile(
      "cp.async.bulk.tensor.5d.shared::cluster.global.mbarrier::complete_tx::bytes [%0], [%1, {%3,%4,%5,%3,%3}], [%2];" ::"r"(slot),
      "l"(m), "r"(slot + kFull), "r"(0), "r"(wx * 7), "r"(wy * 7)
      : "memory");
}
__device__ __forceinline__ void tma_prefetch_win(const CUtensorMap* m, uint32_t w) {
  const uint32_t wy = (w * 57457u) >> 22, wx = w - wy * kNWX;
  asm volatile("cp.async.bulk.prefetch.tensor.3d.L2.global [%0, {%1,%2,%3}];" ::"l"(m + 1), "r"(wx * 168), "r"(wy * 7), "r"(0) : "memory");
}
__device__ __forceinline__ void wg_fence() { asm volatile("wgmma.fence.sync.aligned;" ::: "memory"); }
__device__ __forceinline__ void wg_commit() { asm volatile("wgmma.commit_group.sync.aligned;" ::: "memory"); }
__device__ __forceinline__ void wg_wait() { asm volatile("wgmma.wait_group.sync.aligned 0;" ::: "memory"); }
template <int N>
__device__ __forceinline__ void pin(uint32_t* d) {
#pragma unroll
  for (int i = 0; i < N; i++) asm volatile("" : "+r"(d[i])::"memory");
}
__device__ __forceinline__ uint32_t fresh(uint32_t v) { asm volatile("" : "+r"(v)); return v; }
__device__ __forceinline__ float fresh(float v) { asm volatile("" : "+f"(v)); return v; }
template <int N>
__device__ __forceinline__ void launder(uint32_t* q) {
#pragma unroll
  for (int j = 0; j < N; j++) { uint32_t t; asm volatile("mov.b32 %0, %1;" : "=r"(t) : "r"(q[j])); q[j] = t; }
}
__device__ __forceinline__ void sfence(uint32_t& v) {
  asm volatile("{\n.reg .pred p;\nsetp.eq.u32 p, %1, 0x7fffffff;\n@p mov.u32 %0, %%clock;\n}" : "+r"(v) : "r"(gridDim.x) : "memory");
}
constexpr uint64_t mk_desc(uint32_t addr) { return ((uint64_t)0x80000020u << 32) | (addr >> 4) | (1u << 16); }

#define R4(d, i) "+r"(d[i]), "+r"(d[i + 1]), "+r"(d[i + 2]), "+r"(d[i + 3])
#define O4(d, i) "=r"(d[i]), "=r"(d[i + 1]), "=r"(d[i + 2]), "=r"(d[i + 3])
#define D26 "{%0,%1,%2,%3,%4,%5,%6,%7,%8,%9,%10,%11,%12,%13,%14,%15,%16,%17,%18,%19,%20,%21,%22,%23,%24,%25},"
#define D24 "{%0,%1,%2,%3,%4,%5,%6,%7,%8,%9,%10,%11,%12,%13,%14,%15,%16,%17,%18,%19,%20,%21,%22,%23},"
#define D14 "{%0,%1,%2,%3,%4,%5,%6,%7,%8,%9,%10,%11,%12,%13},"

template <int SC, int TB>
__device__ __forceinline__ void wgmma(uint32_t (&d)[24], const uint32_t* a, uint64_t db) {
  if (SC == 2)
    asm volatile("{\n.reg .pred p;\nsetp.eq.u32 p, %30, 0x7fffffff;\n"
                 "wgmma.mma_async.sync.aligned.m64n96k16.f16.f16.f16 " D24 "{%24,%25,%26,%27}, %28, p, 1, 1, %29;\n}"
                 : R4(d, 0), R4(d, 4), R4(d, 8), R4(d, 12), R4(d, 16), R4(d, 20)
                 : "r"(a[0]), "r"(a[1]), "r"(a[2]), "r"(a[3]), "l"(db), "n"(TB), "r"(gridDim.x));
  else if (SC)
    asm volatile("wgmma.mma_async.sync.aligned.m64n96k16.f16.f16.f16 " D24 "{%24,%25,%26,%27}, %28, 1, 1, 1, %29;"
                 : R4(d, 0), R4(d, 4), R4(d, 8), R4(d, 12), R4(d, 16), R4(d, 20)
                 : "r"(a[0]), "r"(a[1]), "r"(a[2]), "r"(a[3]), "l"(db), "n"(TB));
  else
    asm volatile("wgmma.mma_async.sync.aligned.m64n96k16.f16.f16.f16 " D24 "{%24,%25,%26,%27}, %28, 0, 1, 1, %29;"
                 : O4(d, 0), O4(d, 4), O4(d, 8), O4(d, 12), O4(d, 16), O4(d, 20)
                 : "r"(a[0]), "r"(a[1]), "r"(a[2]), "r"(a[3]), "l"(db), "n"(TB));
}
template <int SC, int TB>
__device__ __forceinline__ void wgmma(uint32_t (&d)[26], const uint32_t* a, uint64_t db) {
  if (SC)
    asm volatile("wgmma.mma_async.sync.aligned.m64n104k16.f16.f16.f16 " D26 "{%26,%27,%28,%29}, %30, 1, 1, 1, 0;"
                 : R4(d, 0), R4(d, 4), R4(d, 8), R4(d, 12), R4(d, 16), R4(d, 20), "+r"(d[24]), "+r"(d[25])
                 : "r"(a[0]), "r"(a[1]), "r"(a[2]), "r"(a[3]), "l"(db));
  else
    asm volatile("wgmma.mma_async.sync.aligned.m64n104k16.f16.f16.f16 " D26 "{%26,%27,%28,%29}, %30, 0, 1, 1, 0;"
                 : O4(d, 0), O4(d, 4), O4(d, 8), O4(d, 12), O4(d, 16), O4(d, 20), "=r"(d[24]), "=r"(d[25])
                 : "r"(a[0]), "r"(a[1]), "r"(a[2]), "r"(a[3]), "l"(db));
}
template <int SC, int TB>
__device__ __forceinline__ void wgmma(uint32_t (&d)[16], const uint32_t* a, uint64_t db) {
  if (SC)
    asm volatile("wgmma.mma_async.sync.aligned.m64n56k16.f16.f16.f16 " D14 "{%14,%15,%16,%17}, %18, 1, 1, 1, 0;"
                 : R4(d, 0), R4(d, 4), R4(d, 8), "+r"(d[12]), "+r"(d[13])
                 : "r"(a[0]), "r"(a[1]), "r"(a[2]), "r"(a[3]), "l"(db));
  else
    asm volatile("wgmma.mma_async.sync.aligned.m64n56k16.f16.f16.f16 " D14 "{%14,%15,%16,%17}, %18, 0, 1, 1, 0;"
                 : O4(d, 0), O4(d, 4), O4(d, 8), "=r"(d[12]), "=r"(d[13])
                 : "r"(a[0]), "r"(a[1]), "r"(a[2]), "r"(a[3]), "l"(db));
}
template <int SC, int OFF, int CH, int ND>
__device__ __forceinline__ void gemm(uint32_t (&d)[ND], const uint32_t* a, uint64_t db) {
  asm volatile("" : "+l"(db));
  wg_fence();
  wgmma<SC, 0>(d, a, db + OFF / 16);
#pragma unroll
  for (int k = 1; k < 6; k++) wgmma<1, 0>(d, a + 4 * k, db + (OFF + (k >> 1) * CH + (k & 1) * 32) / 16);
  wg_commit();
}
__device__ __forceinline__ void lds128(uint32_t* r, uint32_t a) {
  asm volatile("ld.shared.v4.b32 {%0,%1,%2,%3}, [%4];" : "=r"(r[0]), "=r"(r[1]), "=r"(r[2]), "=r"(r[3]) : "r"(a) : "memory");
}
__device__ __forceinline__ void ldsm4(uint32_t* r, uint32_t a) {
  asm volatile("ldmatrix.sync.aligned.m8n8.x4.shared.b16 {%0,%1,%2,%3}, [%4];"
               : "=r"(r[0]), "=r"(r[1]), "=r"(r[2]), "=r"(r[3]) : "r"(a) : "memory");
}
__device__ __forceinline__ void stsm4(uint32_t a, const uint32_t* r) {
  asm volatile("stmatrix.sync.aligned.m8n8.x4.shared.b16 [%0], {%1,%2,%3,%4};" ::"r"(a), "r"(r[0]), "r"(r[1]), "r"(r[2]), "r"(r[3])
               : "memory");
}
__device__ __forceinline__ void stg3(uint8_t* p, const uint32_t* r, uint32_t off) {
  asm volatile("{\n.reg .pred p;\nsetp.eq.u32 p, %13, 0;\n@p st.global.v4.b32 [%0], {%1,%2,%3,%4};\n"
               "@p st.global.v4.b32 [%0+64], {%5,%6,%7,%8};\n@p st.global.v4.b32 [%0+128], {%9,%10,%11,%12};\n}" ::"l"(p),
               "r"(r[0]), "r"(r[1]), "r"(r[2]), "r"(r[3]), "r"(r[4]), "r"(r[5]), "r"(r[6]), "r"(r[7]), "r"(r[8]), "r"(r[9]), "r"(r[10]), "r"(r[11]),
               "r"(off) : "memory");
}
__device__ __forceinline__ uint32_t pack_h2(float lo, float hi) {
  uint32_t r; asm("cvt.rn.f16x2.f32 %0, %1, %2;" : "=r"(r) : "f"(hi), "f"(lo)); return r;
}
__device__ __forceinline__ uint32_t pack_h2_sat(float lo, float hi) {
  uint32_t r; asm("cvt.rn.satfinite.f16x2.f32 %0, %1, %2;" : "=r"(r) : "f"(hi), "f"(lo)); return r;
}
__device__ __forceinline__ uint32_t pack_bf2(float lo, float hi) {
  uint32_t r; asm("cvt.rn.bf16x2.f32 %0, %1, %2;" : "=r"(r) : "f"(hi), "f"(lo)); return r;
}
__device__ __forceinline__ __half2 as_h2(uint32_t v) { return *reinterpret_cast<__half2*>(&v); }
__device__ __forceinline__ uint32_t as_u(__half2 v) { return *reinterpret_cast<uint32_t*>(&v); }
__device__ __forceinline__ float2 unpack_h2(uint32_t v) { return __half22float2(as_h2(v)); }
__device__ __forceinline__ float low_f(uint32_t v) { return __low2float(as_h2(v)); }
__device__ __forceinline__ uint32_t h2ex2(uint32_t v) { uint32_t r; asm("ex2.approx.f16x2 %0, %1;" : "=r"(r) : "r"(v)); return r; }
__device__ __forceinline__ uint32_t h2max(uint32_t a, uint32_t b) { return as_u(__hmax2(as_h2(a), as_h2(b))); }
__device__ __forceinline__ uint32_t h2add(uint32_t a, uint32_t b) { return as_u(__hadd2(as_h2(a), as_h2(b))); }
__device__ __forceinline__ uint32_t h2sub(uint32_t a, uint32_t b) { return as_u(__hsub2(as_h2(a), as_h2(b))); }
__device__ __forceinline__ uint32_t h2mul(uint32_t a, uint32_t b) { return as_u(__hmul2(as_h2(a), as_h2(b))); }
__device__ __forceinline__ uint32_t h2neg(uint32_t a) { return as_u(__hneg2(as_h2(a))); }
__device__ __forceinline__ uint32_t h2fma(uint32_t a, uint32_t b, uint32_t c) { return as_u(__hfma2(as_h2(a), as_h2(b), as_h2(c))); }
__device__ __forceinline__ uint32_t lo2(uint32_t v) { return as_u(__low2half2(as_h2(v))); }
__device__ __forceinline__ uint32_t hi2(uint32_t v) { return as_u(__high2half2(as_h2(v))); }
__device__ __forceinline__ uint32_t fold_add(uint32_t a, uint32_t b) { return h2add(__byte_perm(a, b, 0x5410), __byte_perm(a, b, 0x7632)); }
__device__ __forceinline__ uint32_t sel(uint32_t p, uint32_t a, uint32_t b) {
  uint32_t r; asm("{\n.reg .pred p;\nsetp.ne.u32 p, %3, 0;\nselp.b32 %0, %1, %2, p;\n}" : "=r"(r) : "r"(a), "r"(b), "r"(p)); return r;
}
__device__ __forceinline__ float sel4(uint32_t c, float a0, float a1, float a2, float a3) {
  return __uint_as_float(sel(c & 2, sel(c & 1, __float_as_uint(a3), __float_as_uint(a2)), sel(c & 1, __float_as_uint(a1), __float_as_uint(a0))));
}
__device__ __forceinline__ float rcp_fast(float v) { float r; asm("rcp.approx.ftz.f32 %0, %1;" : "=f"(r) : "f"(v)); return r; }
__device__ __forceinline__ float rsq_fast(float v) { float r; asm("rsqrt.approx.ftz.f32 %0, %1;" : "=f"(r) : "f"(v)); return r; }
__device__ __forceinline__ uint32_t shfl_x(uint32_t v, int m) { return __shfl_xor_sync(0xffffffffu, v, m); }
__device__ __forceinline__ uint32_t shfl_q(uint32_t v, int i) { return __shfl_sync(0xffffffffu, v, i, 4); }
__device__ __forceinline__ float quad_sum(float v) {
  v += __shfl_xor_sync(0xffffffffu, v, 1);
  return v + __shfl_xor_sync(0xffffffffu, v, 2);
}
__device__ __forceinline__ uint32_t score_scale(const float* p) { const float v = __ldcg(p); return pack_h2(v, v); }

constexpr float kEps96 = 1e-5f * 96.f * 96.f;
__device__ __forceinline__ float2 stat_f32(uint32_t e) {
  const float2 h = unpack_h2(e);
  return make_float2(__uint_as_float(sel(e & 0x8000u, (e << 16) & 0x7fff0000u, __float_as_uint(h.x))),
                     __uint_as_float(sel(e & 0x8000u, e & 0xffff0000u, __float_as_uint(h.y))));
}

struct Tile {
  uint32_t ring, a;
  uint32_t next;
  uint32_t n;
  int live;
  uint32_t stat, wrap;
  uint32_t flag;
  uint32_t gate;
};
struct TPar { float kt, sgmin, outmax; };

__device__ __forceinline__ uint32_t swz(uint32_t r, int t) { return fresh(r ^ (((r >> 3) + 8 * t) & 0x30)); }
__device__ __forceinline__ void load_rows(uint32_t* x0, uint32_t* x1, uint32_t ring, uint32_t r, int t) {
  const uint32_t a0 = swz(r, t), a1 = swz(r, t + 1), u0 = ring + t * kPlane, u1 = u0 + kPlane;
  lds128(x0, a0 + u0); lds128(x1, a1 + u1);
  lds128(x0 + 4, fresh(a0 ^ 32) + (u0 + kChunk)); lds128(x1 + 4, fresh(a1 ^ 32) + (u1 + kChunk));
  lds128(x0 + 8, a0 + (u0 + 2 * kChunk)); lds128(x1 + 8, a1 + (u1 + 2 * kChunk));
}
__device__ __forceinline__ void to_half(uint32_t (&z)[24], const uint32_t* x) {
#pragma unroll
  for (int j = 0; j < 24; j += 2) {
    const int o = j < 12 ? 2 * j : 2 * j - 23;
    uint32_t t;
    asm("cvt.rz.f16x2.f32 %0, %1, %2;" : "=r"(t) : "f"(__uint_as_float(x[j + 1])), "f"(__uint_as_float(x[j])));
    z[o] = pack_h2(__uint_as_float(x[j] << 16), __uint_as_float(x[j + 1] << 16));
    z[o + 2] = t & 0xfff8fff8u;
  }
}
__device__ __forceinline__ void load_general(uint32_t (&z)[24], uint32_t ring, uint32_t r, int t, float& ie0, float& ie1, float& m0, float& m1) {
  float acc[48];
  uint32_t x0[12], x1[12];
  load_rows(x0, x1, ring, r, t);
#pragma unroll
  for (int j = 0; j < 12; j++) {
    acc[4 * j] = __uint_as_float(x0[j] << 16); acc[4 * j + 1] = __uint_as_float(x0[j] & 0xffff0000u);
    acc[4 * j + 2] = __uint_as_float(x1[j] << 16); acc[4 * j + 3] = __uint_as_float(x1[j] & 0xffff0000u);
  }
  float s[4], q[4];
#pragma unroll
  for (int e = 0; e < 4; e++) { s[e] = acc[e]; q[e] = acc[e] * acc[e]; }
#pragma unroll
  for (int j = 4; j < 48; j++) { s[j & 3] += acc[j]; q[j & 3] = fmaf(acc[j], acc[j], q[j & 3]); }
  const float s0 = quad_sum(s[0] + s[1]), s1 = quad_sum(s[2] + s[3]), q0 = quad_sum(q[0] + q[1]), q1 = quad_sum(q[2] + q[3]);
  const float u0 = rsq_fast(fmaxf(fmaf(-s0, s0, fmaf(q0, 96.f, kEps96)), kEps96));
  const float u1 = rsq_fast(fmaxf(fmaf(-s1, s1, fmaf(q1, 96.f, kEps96)), kEps96));
  const float n0 = -s0 * u0, n1 = -s1 * u1;
  ie0 = 96.f * u0; ie1 = 96.f * u1;
  m0 = s0 * (1.f / 96.f); m1 = s1 * (1.f / 96.f);
#pragma unroll
  for (int j = 0; j < 12; j++) {
    const int o = 8 * (j >> 1) + (j & 1);
    z[2 * j] = pack_h2(fmaf(acc[o], ie0, n0), fmaf(acc[o + 4], ie0, n0));
    z[2 * j + 1] = pack_h2(fmaf(acc[o + 2], ie1, n1), fmaf(acc[o + 6], ie1, n1));
  }
}
template <bool kDown>
__device__ __forceinline__ uint32_t sumsq2(const uint32_t* z) {
  uint32_t q0, q1;
#pragma unroll
  for (int j = 0; j < 12; j++) {
    const uint32_t u = kDown ? h2mul(z[2 * j], 0x1c001c00u) : z[2 * j], v = kDown ? h2mul(z[2 * j + 1], 0x1c001c00u) : z[2 * j + 1];
    q0 = j ? h2fma(u, u, q0) : h2mul(u, u); q1 = j ? h2fma(v, v, q1) : h2mul(v, v);
  }
  return fold_add(q0, q1);
}
template <bool kDown>
__device__ __forceinline__ float row_sumsq(const uint32_t* z0, const uint32_t* z1, uint32_t c) {
  const uint32_t a = sumsq2<kDown>(z0), b = sumsq2<kDown>(z1);
  uint32_t t = h2add(sel(c & 2, b, a), shfl_x(sel(c & 2, a, b), 2));
  t = h2add(t, shfl_x(t, 1));
  return low_f(sel(c & 1, t >> 16, t));
}
__device__ __forceinline__ void scores2(const uint32_t* q, const uint32_t* z0, const uint32_t* z1, uint32_t* f) {
  uint32_t d[8];
#pragma unroll
  for (int j = 0; j < 12; j++) {
    const uint32_t kk[4] = {z0[2 * j], z0[2 * j + 1], z1[2 * j], z1[2 * j + 1]};
#pragma unroll
    for (int e = 0; e < 4; e++) {
      d[e] = j ? h2fma(q[2 * j], kk[e], d[e]) : h2mul(q[2 * j], kk[e]);
      d[4 + e] = j ? h2fma(q[2 * j + 1], kk[e], d[4 + e]) : h2mul(q[2 * j + 1], kk[e]);
    }
  }
#pragma unroll
  for (int e = 0; e < 4; e++) f[e] = fold_add(d[2 * e], d[2 * e + 1]);
}
struct Xch { uint32_t keep[2], got[2]; };
__device__ __forceinline__ Xch pair_send(const uint32_t* a, const uint32_t* b, uint32_t c, int m) {
  Xch x;
#pragma unroll
  for (int e = 0; e < 2; e++) { x.keep[e] = fresh(sel(c & m, b[e], a[e])); x.got[e] = shfl_x(sel(c & m, a[e], b[e]), m); }
  return x;
}
__device__ __forceinline__ void pair_recv(uint32_t* k, const Xch& x) { k[0] = h2add(x.keep[0], x.got[0]); k[1] = h2add(x.keep[1], x.got[1]); }
__device__ __forceinline__ void mix2(uint32_t* y, const uint32_t* v, uint32_t c0, uint32_t c1) {
#pragma unroll
  for (int j = 0; j < 12; j++) {
    y[2 * j] = h2fma(v[2 * j + 1], hi2(c0), h2fma(v[2 * j], lo2(c0), y[2 * j]));
    y[2 * j + 1] = h2fma(v[2 * j + 1], hi2(c1), h2fma(v[2 * j], lo2(c1), y[2 * j + 1]));
  }
  pin<24>(y);
}
__device__ __forceinline__ void norm_store(uint32_t* y, uint32_t r0, uint32_t r1, uint32_t r, int t) {
#pragma unroll
  for (int j = 0; j < 12; j++) { y[2 * j] = h2fma(y[2 * j], lo2(r0), hi2(r0)); y[2 * j + 1] = h2fma(y[2 * j + 1], lo2(r1), hi2(r1)); }
  const uint32_t ma = swz(r, t), mb = fresh(ma ^ 32), u = t * kPlane;
  stsm4(ma + u, y); stsm4(mb + u, y + 4);
  stsm4(mb + (u + kChunk), y + 8); stsm4(ma + (u + kChunk), y + 12);
  stsm4(ma + (u + 2 * kChunk), y + 16); stsm4(mb + (u + 2 * kChunk), y + 20);
}

template <bool kAlways>
__device__ __forceinline__ void gate_open(uint32_t id) {
  if (kAlways) asm volatile("barrier.cta.arrive.aligned %0, 256;" ::"r"(id) : "memory");
  else asm volatile("{\n.reg .pred p;\nsetp.ne.u32 p, %0, 0;\n@p barrier.cta.arrive.aligned %0, 256;\n}" ::"r"(id) : "memory");
}

struct TState { uint32_t z0[24], z1[24], mu, bad; float ie, mm, mz, qq; };
template <bool kDirect>
__device__ __forceinline__ void temporal(TState& S, uint64_t da, const Tile& T, const TPar& P, bool scaled, uint32_t lane, uint32_t& lst) {
  uint32_t (&z0)[24] = S.z0, (&z1)[24] = S.z1;
  const uint32_t c = lane;
  const uint32_t a0 = T.a + lane * 16 + (lane >= 4 * T.n ? T.next : 0);
  uint32_t q0[26], q1[24], v0[24], w1[26], nn = 0, ng = 0, ca0 = 0, ca1 = 0;
  uint32_t* const v1 = w1 + 2;
  float ie = 1.f, mm = 0.f;
  bool tiny = false;
  if (kDirect) {
    uint32_t x[48];
    load_rows(x, x + 12, T.ring, a0, 0);
    load_rows(x + 24, x + 36, T.ring, a0, 2);
    to_half(z0, x);
    gemm<0, 0, kAtChunk>(q0, z0, da);
    sfence(lst);
    to_half(z1, x + 24);
    const uint32_t n0 = sumsq2<false>(z0), n1 = sumsq2<false>(z1);
    nn = fresh(sel(c & 2, n1, n0)); ng = shfl_x(sel(c & 2, n0, n1), 2);
    pin<24>(z1); sfence(lst);
  } else {
    float e[4], m[4];
    load_general(z0, T.ring, a0, 0, e[0], e[1], m[0], m[1]);
    pin<24>(z0); sfence(lst);
    load_general(z1, T.ring, a0, 2, e[2], e[3], m[2], m[3]);
    ie = sel4(c, e[0], e[1], e[2], e[3]);
    mm = sel4(c, m[0], m[1], m[2], m[3]);
    tiny = __any_sync(0xffffffffu, ie * P.kt > 400.f);
    if (tiny) {
      float u = 0.f;
#pragma unroll
      for (int r = 0; r < 4; r++) {
        float t = 0.f;
#pragma unroll
        for (int j = 0; j < 12; j++) { const float2 f = unpack_h2((r & 2 ? z1 : z0)[2 * j + (r & 1)]); t = fmaf(f.x, f.x, fmaf(f.y, f.y, t)); }
        u = fmaxf(u, quad_sum(t));
      }
      const float t = fminf(ie, 9.8f * rsq_fast(fmaxf(u, 2e-7f)) * rcp_fast(fresh(P.kt)));
      const uint32_t a = pack_h2(__fdividef(t, ie), 0.f);
      ca0 = __byte_perm(shfl_q(a, 0), shfl_q(a, 1), 0x5410); ca1 = __byte_perm(shfl_q(a, 2), shfl_q(a, 3), 0x5410);
      ie = t;
    }
    gemm<0, 0, kAtChunk>(q0, z0, da);
  }
  uint32_t f[4], k0[2], k1[2], sk[2];
  wg_wait(); pin<26>(q0);
  gemm<0, 0, kAtChunk>(q1, z1, da);
  gate_open<kDirect>(T.gate);
  sfence(lst);
  if (kDirect) { nn = h2add(nn, ng); ng = shfl_x(nn, 1); sfence(lst); }
  scores2(q0, z0, z1, f);
  const uint32_t nu0 = fresh(__byte_perm(q0[24], q0[25], 0x7632)), m01 = fresh(sel(c & 1, q0[25], q0[24]));
  Xch xc = pair_send(f, f + 2, c, 1);
  sfence(lst);
  wg_wait(); pin<24>(q1);
  gemm<0, kOffWt - 512, kAtChunk>(w1, z1, da);
  sfence(lst);
  pair_recv(k0, xc);
  float e2 = 0.f, lim = 0.f;
  if (kDirect) {
    nn = h2add(nn, ng);
    e2 = fresh(fmaf(low_f(sel(c & 1, nn >> 16, nn)), 1.f / 96.f, 1e-5f));
    lim = fresh(e2 <= 4.f ? fmaxf(0.5f * e2, 4e-4f) : __uint_as_float(0x7fffffffu));
  }
  scores2(q1, z0, z1, f);
  xc = pair_send(f, f + 2, c, 1);
  pin<2>(k0); sfence(lst);
  wg_wait(); pin<26>(w1);
  float mz = 0.f, d2 = 0.f;
  if (kDirect) {
    mz = low_f(sel(c & 2, sel(c & 1, w1[1], w1[0]), m01));
    d2 = fmaf(-mz, mz, e2);
    asm volatile("{\n.reg .pred p;\nsetp.lt.s32 p, %3, %4;\nsetp.ltu.and.f32 p, %1, %2, p;\n@p st.volatile.shared.f32 [%0], %2;\n}" ::"r"(T.flag), "f"(d2),
                 "f"(lim), "r"(lane), "r"(T.live) : "memory");
  }
  gemm<0, kOffWt, kAtChunk>(v0, z0, da);
  sfence(lst);
  uint32_t cw[8], mu;
  {
    uint32_t rc = 0, r0 = 0, r1 = 0;
    if (kDirect) {
      const float r = rsq_fast(d2);
      rc = pack_h2(r, r);
      r0 = __byte_perm(shfl_q(rc, 0), shfl_q(rc, 1), 0x5410); r1 = __byte_perm(shfl_q(rc, 2), shfl_q(rc, 3), 0x5410);
    }
    pair_recv(k1, xc);
    pair_recv(sk, pair_send(k0, k1, c, 2));
    if (kDirect) { sk[0] = h2mul(sk[0], r0); sk[1] = h2mul(sk[1], r1); }
    uint32_t mx = h2max(sk[0], sk[1]);
    mx = h2max(lo2(mx), hi2(mx));
    if (kDirect) {
      const uint32_t nm = h2mul(h2neg(mx), rc);
      sk[0] = h2fma(sk[0], rc, nm); sk[1] = h2fma(sk[1], rc, nm);
    } else {
      sk[0] = h2sub(sk[0], mx); sk[1] = h2sub(sk[1], mx);
      if (scaled) {
        const uint32_t cs = score_scale(&g_par.cS_t);
        sk[0] = h2mul(sk[0], cs); sk[1] = h2mul(sk[1], cs);
      }
    }
    sk[0] = h2ex2(sk[0]); sk[1] = h2ex2(sk[1]);
    const uint32_t sm = h2add(sk[0], sk[1]);
    const float iv = (kDirect ? P.kt : P.kt * ie) * rcp_fast(low_f(h2add(lo2(sm), hi2(sm))));
    const uint32_t inv = pack_h2(iv, iv);
    if (kDirect) { sk[0] = h2mul(sk[0], r0); sk[1] = h2mul(sk[1], r1); }
    sk[0] = h2mul(sk[0], inv); sk[1] = h2mul(sk[1], inv);
#pragma unroll
    for (int i = 0; i < 4; i++) { cw[2 * i] = shfl_q(sk[0], i); cw[2 * i + 1] = shfl_q(sk[1], i); }
    mu = h2fma(sk[1], __byte_perm(w1[0], w1[1], 0x7632), h2mul(sk[0], nu0));
    mu = h2add(lo2(mu), hi2(mu));
  }
  uint32_t bad = 0;
  if (kDirect) {
    mix2(z1, v1, cw[5], cw[7]);
    sfence(lst);
    wg_wait(); pin<24>(v0);
    mix2(z1, v0, cw[4], cw[6]);
    sfence(lst);
    bad = lds32(T.flag);
  } else {
    wg_wait(); pin<24>(v0);
    if (tiny) {
#pragma unroll
      for (int j = 0; j < 12; j++) {
        z0[2 * j] = h2mul(z0[2 * j], lo2(ca0)); z0[2 * j + 1] = h2mul(z0[2 * j + 1], hi2(ca0));
        z1[2 * j] = h2mul(z1[2 * j], lo2(ca1)); z1[2 * j + 1] = h2mul(z1[2 * j + 1], hi2(ca1));
      }
    }
    mix2(z1, v1, cw[5], cw[7]);
    mix2(z1, v0, cw[4], cw[6]);
  }
  mix2(z0, v1, cw[1], cw[3]);
  mix2(z0, v0, cw[0], cw[2]);
  S.qq = row_sumsq<false>(z0, z1, c);
  S.mu = mu; S.bad = bad; S.ie = ie; S.mm = mm; S.mz = mz;
}
__device__ __forceinline__ bool irregular(const TState& S, const Tile& T, uint32_t lane) {
  return __any_sync(0xffffffffu, (!(S.qq < 65000.f) & ((int)lane < T.live)) | (S.bad != 0));
}
__device__ __forceinline__ void resum(TState& S, uint32_t lane) {
  const float q2 = row_sumsq<true>(S.z0, S.z1, lane) * 65536.f;
  S.qq = S.qq < 65000.f ? S.qq : q2;
}
template <bool kDirect>
__device__ __forceinline__ void temporal_out(TState& S, const Tile& T, const TPar& P, uint32_t lane, uint32_t lst) {
  uint32_t (&z0)[24] = S.z0, (&z1)[24] = S.z1;
  const uint32_t mu = S.mu;
  const float ie = S.ie, mz = S.mz, qq = S.qq;
  float mm = S.mm;
  const float rf = kDirect ? rsq_fast(fmaxf(fmaf(-mz, mz, fmaf(qq, 1.f / 96.f, 1e-5f)), 1e-5f)) : rsq_fast(fmaf(qq, 1.f / 96.f, 1e-5f * ie * ie));
  const uint32_t rn = pack_h2_sat(rf, -mz * rf);
  uint32_t rr[4];
#pragma unroll
  for (int i = 0; i < 4; i++) rr[i] = shfl_q(rn, i);
  lane = fresh(lane);
  const uint32_t ma = fresh(T.ring + T.a) + lst + ((lane & 7) >= T.n ? T.next : 0);
  norm_store(z0, rr[0], rr[1], ma, 0);
  const float2 rm = unpack_h2(rn);
  const float sg = rcp_fast(kDirect ? rm.x : rm.x * ie);
  mm = kDirect ? fmaf(-rm.y, sg, low_f(mu)) : fmaf(low_f(mu) * rm.x, sg, mm);
  const bool ok = (sg >= P.sgmin) & (fmaf(sg, 9.8f, fabsf(mm)) < P.outmax);
  asm volatile("{\n.reg .pred p;\nsetp.lt.s32 p, %2, %3;\n@p st.shared.b32 [%0], %1;\n}" ::"r"(
                   T.stat + fresh((lane & 3) * (kSlot - 1) + lane + (lane >= 4 * T.n ? T.wrap : 0))),
               "r"(sel(ok, pack_h2(sg, mm), pack_bf2(sg, mm) | 0x8000u)), "r"(lane), "r"(T.live) : "memory");
  norm_store(z1, rr[2], rr[3], ma, 2);
}

__device__ __forceinline__ void run_T(uint32_t ring, uint64_t d0, uint64_t d1, uint32_t nfull, uint32_t nrem, bool helper, int wg, int wp, uint32_t lane,
                                      const TPar& P, bool scaled, uint32_t pdir) {
  uint32_t lst = (lane & 7) * 64 + (lane & 8) * (kPlane / 8) + (lane & 16);
  uint32_t p0 = 32 * (wg & 1) + (helper ? 0 : 64) + 8 * wp;
  uint32_t npx = 49 * nfull, pstop = npx - 6 * 49 + 8 * wp;
  if (helper) pstop = 0;
  uint32_t pgap = 0;
  Tile T;
  T.ring = ring;
  T.flag = ring + wg * kSlot + kFlag;
  T.gate = wg == 3 ? 6 : 5 + wg;
  while (true) {
    const uint32_t iw = (p0 * 21400u) >> 20, ow = p0 - 49 * iw;
    const uint32_t slot = ring + (iw & 3) * kSlot, dn = (iw & 3) == 3 ? -3 * kSlot : kSlot;
    asm volatile("{\n.reg .pred p;\nsetp.eq.u32 p, %1, 0;\n@p barrier.cta.sync.aligned %0, 256;\n}" ::"r"(6 - (wg & 1)), "r"((uint32_t)helper) : "memory");
    mbar_wait(slot + kFull, iw >> 2);
    if (ow > 41) mbar_wait(slot + dn + kFull, (iw + 1) >> 2);
    T.a = (iw & 3) * kSlot + ow * 64; T.next = dn - kPlane; T.n = 49 - ow;
    T.live = 4 * (npx - p0);
    T.stat = ring + kXBytes + (p0 - 196 * (iw >> 2)) * 4; T.wrap = (iw & 3) == 3 ? -784 : 0;
    lane = fresh(lane);
    {
      TState S;
      Tile G = T;
      if (p0 >= pdir) {
        temporal<true>(S, d0, T, P, false, lane, lst);
        if (irregular(S, T, lane)) {
          if (__any_sync(0xffffffffu, S.bad != 0)) goto redo;
          resum(S, lane);
        }
        temporal_out<true>(S, T, P, lane, lst);
        goto stored;
      redo:
        asm volatile("barrier.cta.sync.aligned %0, 128;" ::"r"(wg + 1) : "memory");
        asm volatile("st.shared.b32 [%0], %1;\nfence.acq_rel.cta;" ::"r"(T.flag), "r"(0) : "memory");
        G.gate = 0;
        pgap = p0 == pdir ? 4 * pgap + 64 : 0;
        pdir = p0 + 64 + pgap;
      }
      temporal<false>(S, d1, G, P, scaled, lane, lst);
      if (irregular(S, T, lane)) resum(S, lane);
      temporal_out<false>(S, T, P, lane, lst);
    }
  stored:
    const uint32_t pn = __shfl_sync(0xffffffffu, p0 + 64, 0);
    bool last = false;
    if (pn >= pstop) {
      if (helper) last = true;
      else if (pstop < npx - 4 * 49) {
        if (((wg & 1) | wp | lane) == 0) {
          const uint32_t nb = gridDim.x, nwh = min(max((int)(2 * nrem - nb), (int)(nrem / 2)), nrem);
          const uint32_t r = atomicAdd(&g_par.ticket, 1u), j = r - nwh;
          sts32(ring + kExtra, r < nwh ? (nfull * nb + r) * 4 + 3 : j < 2 * (nrem - nwh) ? (nfull * nb + nwh + (j >> 1)) * 4 + 1 + (j & 1) : 0);
        }
        __syncwarp();
        pstop = npx - 2 * 49 + 8 * wp;
      } else if (pstop < npx) {
        if (__shfl_sync(0xffffffffu, lds32(ring + kExtra), 0)) npx += 49;
        pstop = npx + 8 * wp;
      } else last = true;
    }
    asm volatile("fence.proxy.async.shared::cta;" ::: "memory");
    __syncwarp();
    mbar_arrive(slot + kDone + (lane >= 4 * T.n ? dn : 0), lane & 3);
    __syncwarp();
    if (last) break;
    p0 = pn;
  }
}

struct Frame {
  bool light;
  uint32_t sta;
  uint32_t oo;
  uint32_t e0, e1;
};
__device__ __forceinline__ uint32_t frame_init(Frame& F, uint32_t ring, uint32_t t, int wp, int lane) {
  wp = (wp + t) & 3;
  F.light = wp == 3;
  F.sta = ring + t * kSlot + kXBytes + 64 * wp;
  const uint32_t r = 16 * wp + (lane >> 2);
  F.oo = ((r / 7) * (kW - 7) + r) * 192u + (lane & 3) * 16 + (((((r + 8) / 7 - r / 7) * (kW - 7) + 8) * 3u) << 20);
  F.e0 = F.e1 = 0x8000u;
  const uint32_t am = t * kPlane + wp * 1024 + ((lane * 65) & 0x3d0);
  return F.light && (lane & 15) ? kZero : am ^ ((am >> 3) & 0x30);
}
template <bool F>
__device__ __forceinline__ void load_frame(uint32_t (&v)[24], uint32_t ma, uint32_t slot, uint32_t& tid) {
  const uint32_t st = ma < kXBytes ? kChunk : 0, mb = ma ^ 32;
  uint32_t a[6] = {ma, mb, mb + st, ma + st, ma + 2 * st, mb + 2 * st};
  pin<6>(a);
  if (F) sfence(tid);
#pragma unroll
  for (int k = 0; k < 6; k++) ldsm4(v + 4 * k, slot + a[k]);
}
__device__ __forceinline__ uint32_t load_stats(Frame& F, uint32_t ia, uint32_t tid) {
  const uint32_t a = fresh(tid & (F.light ? 0 : 0x1c)), u = F.sta + ia * 196;
  F.e0 = lds32(a + u);
  F.e1 = lds32(a + fresh(u + (F.light ? 0 : 32)));
  return a;
}
__device__ __forceinline__ uint32_t is_wide(const Frame& F) {
  uint32_t r;
  asm volatile("{\n.reg .pred p;\n.reg .b32 t;\nlop3.b32 t, %1, %2, 0x8000, 0xa8;\nsetp.ne.u32 p, t, 0;\nvote.sync.ballot.b32 %0, p, 0xffffffff;\n}"
               : "=r"(r) : "r"(F.e0), "r"(F.e1));
  return r;
}
template <int OFF>
__device__ __forceinline__ void gemm_u(uint32_t (&u)[24], const uint32_t* s, uint64_t db) {
  constexpr uint32_t kMN = (((kChunk >> 4) - 1) << 16) + OFF / 16;
  asm volatile("" : "+l"(db));
  wg_fence();
  wgmma<2, 1>(u, s, db + kMN); wgmma<1, 1>(u, s + 4, db + kMN + 64); wgmma<1, 1>(u, s + 8, db + kMN + 128); wgmma<1, 1>(u, s + 12, db + kMN + 192);
  wg_commit();
}
__device__ __forceinline__ uint32_t key48(uint32_t (&s)[16], uint32_t tid) {
  return fresh(sel(tid & 3, 0xfc00fc00u, __byte_perm(s[12], s[13], 0x5410)));
}
__device__ __forceinline__ uint32_t amax3(uint32_t a, uint32_t b, uint32_t c) {
  return as_u(__hmax2(__hmax2(__habs2(as_h2(a)), __habs2(as_h2(b))), __habs2(as_h2(c))));
}
struct Quad { uint32_t v[4]; };
__device__ __forceinline__ Quad soft_exp(uint32_t (&s)[16], uint32_t& t, uint32_t (&v)[24], const Frame& F, float2& e) {
  const uint32_t am = h2max(h2max(h2max(amax3(s[0], s[1], s[2]), amax3(s[3], s[4], s[5])), amax3(s[6], s[7], s[8])), h2max(amax3(s[9], s[10], s[11]), t));
  e = make_float2(low_f(F.e0), low_f(F.e1));
  uint32_t rare, sp[4];
#pragma unroll
  for (int j = 0; j < 4; j++) sp[j] = fresh(h2ex2(s[j]));
  asm("{\n.reg .pred p, q;\n.reg .b32 t;\nlop3.b32 t, %2, %3, 0x8000, 0xa8;\nsetp.eq.u32 q, t, 0;\nmov.b32 t, 0x49004900;\n"
      "setp.le.and.f16x2 p|q, %1, t, q;\nand.pred p, p, q;\nselp.b32 %0, 0, 1, p;\n}" : "=r"(rare) : "r"(am), "r"(F.e0), "r"(F.e1));
  if (__any_sync(0xffffffffu, rare)) {
    const uint32_t x0 = h2max(h2max(h2max(s[0], s[2]), h2max(s[4], s[6])), h2max(s[8], s[10]));
    const uint32_t x1 = h2max(h2max(h2max(s[1], s[3]), h2max(s[5], s[7])), h2max(s[9], s[11]));
    uint32_t mx = h2max(h2max(__byte_perm(x0, x1, 0x5410), __byte_perm(x0, x1, 0x7632)), t);
    mx = h2max(mx, shfl_x(mx, 1));
    mx = h2max(mx, shfl_x(mx, 2));
#pragma unroll
    for (int j = 0; j < 6; j++) { s[2 * j] = h2sub(s[2 * j], lo2(mx)); s[2 * j + 1] = h2sub(s[2 * j + 1], hi2(mx)); }
    t = h2sub(t, mx);
    if (is_wide(F)) {
      const uint32_t cs = score_scale(&g_par.cS_s);
#pragma unroll
      for (int j = 0; j < 12; j++) s[j] = h2mul(s[j], cs);
      t = h2mul(t, cs);
      const float s0 = stat_f32(F.e0).x, s1 = stat_f32(F.e1).x;
      const float kb = __ldcg(&g_par.kb), ik = rcp_fast(__ldcg(&g_par.kappa));
      e.x = fmaxf(s0, kb); e.y = fmaxf(s1, kb);
      const uint32_t aw = pack_h2(__fdividef(s0, e.x), __fdividef(s1, e.y));
      e.x *= ik; e.y *= ik;
#pragma unroll
      for (int j = 0; j < 12; j++) { v[2 * j] = h2mul(v[2 * j], lo2(aw)); v[2 * j + 1] = h2mul(v[2 * j + 1], hi2(aw)); }
    }
#pragma unroll
    for (int j = 0; j < 4; j++) sp[j] = h2ex2(s[j]);
  }
#pragma unroll
  for (int j = 0; j < 12; j++) s[j] = j < 4 ? sp[j] : h2ex2(s[j]);
  t = h2ex2(t);
  Quad q;
  q.v[0] = h2add(t, fold_add(h2add(h2add(h2add(s[0], s[2]), h2add(s[4], s[6])), h2add(s[8], s[10])),
                             h2add(h2add(h2add(s[1], s[3]), h2add(s[5], s[7])), h2add(s[9], s[11]))));
#pragma unroll
  for (int i = 1; i < 4; i++) q.v[i] = shfl_x(q.v[0], i);
  return q;
}
__device__ __forceinline__ void soft_norm(uint32_t (&s)[16], uint32_t& t, const Quad& q, const Frame& F, float2 e, uint32_t tid) {
  const float2 d = unpack_h2(h2add(h2add(q.v[0], q.v[1]), h2add(q.v[2], q.v[3])));
  const uint32_t cb = pack_h2(rcp_fast(d.x * e.x), rcp_fast(d.y * e.y)) & (sel(tid & 28, 0u, 0xffffu) | fresh(F.light ? 0u : 0xffffffffu));
#pragma unroll
  for (int j = 0; j < 6; j++) { s[2 * j] = h2mul(s[2 * j], lo2(cb)); s[2 * j + 1] = h2mul(s[2 * j + 1], hi2(cb)); }
  t = fresh(h2mul(t, cb));
  pin<12>(s);
}
__device__ __forceinline__ void soft_tail(uint32_t (&s)[16], uint32_t t) {
  s[12] = t & 0xffffu; s[13] = t >> 16;
  asm volatile("mov.b32 %0, 0;\nmov.b32 %1, 0;" : "=r"(s[14]), "=r"(s[15]));
}
template <int H>
__device__ __forceinline__ uint8_t* row_ptr(const Frame& F, uint8_t* o) {
  const uint32_t oo = fresh(F.oo);
  if (H) asm volatile("mad.wide.u32 %0, %1, 64, %0;" : "+l"(o) : "r"(oo >> 20));
  else { o += oo & 0xfffffu; asm volatile("" : "+l"(o)); }
  return o;
}
template <int H>
__device__ __forceinline__ void affine(uint32_t* r, const uint32_t (&v)[24], const Frame& F) {
  const uint32_t e = H ? F.e1 : F.e0;
#pragma unroll
  for (int j = 0; j < 12; j++) r[j] = h2fma(v[2 * j + H], lo2(e), hi2(e));
  pin<12>(r);
}
template <int H>
__device__ __forceinline__ void finish(uint32_t* r, const Frame& F, uint8_t*& o, uint32_t off, uint32_t a, uint32_t m, uint32_t& tid) {
  o = row_ptr<H>(F, o);
#pragma unroll
  for (int j = 0; j < 12; j += 2) { const float2 f = unpack_h2(r[j]), g = unpack_h2(r[j + 1]); r[j] = pack_bf2(f.x, g.x); r[j + 1] = pack_bf2(f.y, g.y); }
  pin<12>(r);
  sfence(tid);
  stg3(o, r, off | (fresh(a) & m));
}
__device__ __forceinline__ void finish_wide(const uint32_t (&v)[24], const Frame& F, uint8_t* o, uint32_t tid) {
  const float kb = __ldcg(&g_par.kb);
#pragma unroll
  for (int h = 0; h < 2; h++) {
    const float2 z = stat_f32(h ? F.e1 : F.e0);
    const float w = fmaxf(z.x, kb);
    uint32_t r[12];
#pragma unroll
    for (int j = 0; j < 12; j += 2) {
      const float2 f = unpack_h2(v[2 * j + h]), g = unpack_h2(v[2 * j + 2 + h]);
      r[j] = pack_bf2(fmaf(f.x, w, z.y), fmaf(g.x, w, z.y)); r[j + 1] = pack_bf2(fmaf(f.y, w, z.y), fmaf(g.y, w, z.y));
    }
    o = h ? row_ptr<1>(F, o) : row_ptr<0>(F, o);
    stg3(o, r, F.light ? (h ? 1 : tid & 28) : 0);
  }
}
__device__ __forceinline__ uint32_t window_ahead(uint32_t ring, uint32_t i, uint32_t nfull, uint32_t w) {
  return i + 4 < nfull ? w + 4 * gridDim.x : i + 4 == nfull ? lds32(ring + kExtra) >> 2 : 0;
}

__device__ __forceinline__ void run_S(uint32_t ring, uint64_t d0, uint64_t d1, uint32_t frame, uint32_t nfull, uint32_t i0, uint32_t i1, uint32_t w, int sg, int wp, int lane,
                                      const CUtensorMap* tm, uint8_t* __restrict__ out) {
  Frame A, B;
  uint32_t tid = lane + (frame_init(A, ring, 2 * sg, wp, lane) << 4) + (frame_init(B, ring, 2 * sg + 1, wp, lane) << 16);
  uint32_t va[24], vb[24], x[24], sa[16], sc[16], r0[12], r1[12], ta, tb;
  Quad rs;
  float2 e;
#pragma unroll
  for (int j = 0; j < 24; j++) { vb[j] = 0; x[j] = 0; }
  out += sg * 2 * frame;
  uint8_t *ob = out, *o;
  const uint64_t dr = d0 + (uint32_t)(kWBytes / 16 + sg * (2 * kPlane / 16));
  uint32_t i = i0, slot = ring + (i & 3) * kSlot;
  mbar_wait(slot + kDone, i >> 2);
  load_frame<false>(va, (tid >> 4) & 0xfff0u, slot, tid);
  do {
    const uint32_t ia = i & 3;
    gemm<2, kOffAs, 6144>(x, va, d0);
    const uint32_t wb = is_wide(B);
    if (wb && i != i0) finish_wide(vb, B, ob + frame, tid);
    affine<0>(r0, vb, B); affine<1>(r1, vb, B);
    load_frame<true>(vb, (tid >> 16) & 0xfff0u, slot, tid);
    const uint32_t g4 = load_stats(A, ia, tid);
    uint64_t dp = dr + ia * (kSlot / 16);
    asm volatile("" : "+l"(dp));
    o = ob + frame;
    finish<0>(r0, B, o, wb, g4, B.light ? 28 : 0, tid);
    sfence(tid);
    wg_wait(); pin<24>(x);
    gemm<0, 0, kChunk>(sa, x, dp);
    if (!B.light) finish<1>(r1, B, o, wb, 0, 0, tid);
    else if (sg == 0) {
      if ((tid & 31) == 0) {
        const uint32_t wn = window_ahead(ring, i, nfull, w);
        if (wn) tma_prefetch_win(tm, wn);
      }
      __syncwarp();
    }
    ob = out + (size_t)((((w * 57457u) >> 22) * (7 * kW - 7 * kNWX) + w * 7) * 192u);
    sfence(tid);
    wg_wait(); pin<14>(sa);
    gemm<2, kOffAs, 6144>(x, vb, d1);
    ta = key48(sa, tid);
    rs = soft_exp(sa, ta, va, A, e);
    sfence(tid);
    wg_wait(); pin<24>(x);
    gemm<0, kPlane, kChunk>(sc, x, dp);
    sfence(tid);
    load_stats(B, ia, tid);
    soft_norm(sa, ta, rs, A, e, tid);
    sfence(tid);
    wg_wait(); pin<14>(sc);
    tb = key48(sc, tid);
    sfence(tid);
    soft_tail(sa, ta);
    gemm_u<0>(x, sa, dp);
    rs = soft_exp(sc, tb, vb, B, e);
    sfence(tid);
    wg_wait(); pin<24>(x);
    gemm<1, kOffWs, 6144>(va, x, d0);
    sfence(tid);
    soft_norm(sc, tb, rs, B, e, tid);
    soft_tail(sc, tb);
    const uint32_t wa = is_wide(A);
    sfence(tid);
    wg_wait(); pin<24>(va);
    gemm_u<kPlane>(x, sc, dp);
    sfence(tid);
    const uint32_t sn = ring + ((i + 1) & 3) * kSlot;
    const bool slow = mbar_pending_or(sn + kDone, (i + 1) >> 2, wa | A.light);
    affine<0>(r0, va, A);
    o = ob;
    finish<0>(r0, A, o, wa, tid, A.light ? 28 : 0, tid);
    sfence(tid);
    wg_wait(); pin<24>(x);
    gemm<1, kOffWs, 6144>(vb, x, d1);
    sfence(tid);
    affine<1>(r1, va, A);
    if (slow) {
      if (A.light) {
        if ((tid & 31) == 0) {
          uint32_t old;
          asm volatile("atom.relaxed.cta.shared::cta.inc.u32 %0, [%1], 1;" : "=r"(old) : "r"(slot + kRel) : "memory");
          if (old) {
            const uint32_t wn = window_ahead(ring, i, nfull, w);
            if (wn) tma_load_win(slot, tm, wn);
            else mbar_arrive(slot + kFull);
          }
        }
        __syncwarp();
      }
      if (wa) finish_wide(va, A, ob, tid);
      if (i + 1 < i1) mbar_wait(sn + kDone, (i + 1) >> 2);
    }
    const uint32_t la = (tid >> 4) & 0xfff0u;
    load_frame<false>(va, la, sn, tid);
    if (!A.light) finish<1>(r1, A, o, wa, la, 0x4000, tid);
    wg_wait(); pin<24>(vb);
    launder<24>(vb);
    launder<24>(va);
    slot = sn; w += gridDim.x;
  } while (++i < i1);
  const uint32_t wb = is_wide(B);
  if (wb) finish_wide(vb, B, ob + frame, tid);
  o = ob + frame;
  affine<0>(r0, vb, B); finish<0>(r0, B, o, wb, tid, B.light ? 28 : 0, tid);
  affine<1>(r1, vb, B); finish<1>(r1, B, o, B.light | wb, 0, 0, tid);
}

struct Maps { CUtensorMap load, prefetch; };
__global__ void __launch_bounds__(512, 1) swin_main(const __grid_constant__ Maps tms, uint8_t* __restrict__ out, const uint64_t d0,
                                                    const uint64_t d1, const uint32_t frame) {
  extern __shared__ __align__(1024) uint8_t smem[];
  const CUtensorMap& tm = tms.load;
  const uint32_t sb = smem_u32(smem), ring = sb + kWBytes;
  const int tid = threadIdx.x;
  const int wg = __shfl_sync(0xffffffffu, tid >> 7, 0);
  const int wp = __shfl_sync(0xffffffffu, (tid >> 5) & 3, 0);
  const int lane = tid & 31;
  const uint32_t b = blockIdx.x, nb = gridDim.x;
  const uint32_t nfull = kNWIN / nb, nrem = kNWIN - nfull * nb;
  if (tid == 0) {
    if (sb != 1024 || nfull > 700 || nfull < 12) __trap();
#pragma unroll
    for (int i = 0; i < 4; i++) {
      mbar_init(ring + i * kSlot + kFull, 1);
      mbar_init(ring + i * kSlot + kDone, 49);
      sts32(ring + i * kSlot + kRel, 0); sts32(ring + i * kSlot + kFlag, 0);
    }
    asm volatile("fence.mbarrier_init.release.cluster;" ::: "memory");
    for (int i = 0; i < 2; i++) tma_load_win(ring + i * kSlot, &tm, b + i * nb);
  }
  __syncwarp();
  if (wg == 1 || wg == 2)
    asm volatile("st.shared.v4.b32 [%0], {%1,%1,%1,%1};" ::"r"(ring + ((tid - 128) >> 6) * kSlot + kXBytes + (tid & 63) * 16), "r"(0) : "memory");
  __syncthreads();
  asm volatile("griddepcontrol.wait;" ::: "memory");
#pragma unroll
  for (int q = 0; q < kWBytes / 16 / 512; q++)
    asm volatile("cp.async.cg.shared.global [%0], [%1], 16;" ::"r"(sb + (tid + q * 512) * 16), "l"(g_wimg + tid + q * 512) : "memory");
  if (wg == 0 && wp < 3) {
    static_assert(kWBytes / 16 == 9 * 512 + 96, "weight copy split");
    const int e = tid + 9 * 512;
    asm volatile("cp.async.cg.shared.global [%0], [%1], 16;" ::"r"(sb + e * 16), "l"(g_wimg + e) : "memory");
  }
  const float4 p0 = __ldcg(reinterpret_cast<const float4*>(&g_par));
  const float kb = __ldcg(&g_par.kb);
  TPar P;
  P.kt = p0.z;
  P.sgmin = p0.y != 1.f || p0.w != 1.f ? 1e30f : fmaxf(0.0045f, kb * 0.011f);
  P.outmax = fmaf(kb, -627.2f, 60000.f);
  const bool scaled = __any_sync(0xffffffffu, p0.x != 1.f);
  const uint32_t pdir = __ballot_sync(0xffffffffu, scaled || !(P.kt <= 256.f));
  asm volatile("cp.async.wait_all;\nfence.proxy.async.shared::cta;" ::: "memory");
  __syncthreads();
  if (tid == 128) for (int i = 2; i < 4; i++) tma_load_win(ring + i * kSlot, &tm, b + i * nb);
  __syncwarp();
  const bool isT = wg < 2;
  run_T(ring, d0, d1, nfull, nrem, !isT, wg, wp, lane, P, scaled, pdir);
  const uint32_t ex = isT ? __shfl_sync(0xffffffffu, lds32(ring + kExtra), 0) : 3;
  if ((ex >> (wg & 1)) & 1) run_S(ring, d0, d1, frame, nfull, isT ? nfull : 0, nfull + isT, isT ? ex >> 2 : b, wg & 1, wp, lane, &tm, out);
}

__device__ __forceinline__ int ch_pos(int ch) { return 32 * (ch >> 5) + 16 * ((ch >> 2) & 1) + 8 * (ch & 1) + 2 * ((ch >> 3) & 3) + ((ch >> 1) & 1); }
__device__ __forceinline__ float pow2_ceil(float v) {
  return __uint_as_float((__float_as_uint(v) + 0x7fffffu) & 0x7f800000u);
}

constexpr int kPrepSplit = 12;
constexpr int kPrepThreads = 384;
__global__ void __launch_bounds__(kPrepThreads) swin_prep(const __nv_bfloat16* __restrict__ wqkv_t, const __nv_bfloat16* __restrict__ wo_t,
                                                          const __nv_bfloat16* __restrict__ wqkv_s, const __nv_bfloat16* __restrict__ wo_s) {
  asm volatile("griddepcontrol.launch_dependents;");
  __shared__ __align__(16) uint32_t raw[2][96][52];
  __shared__ __align__(16) uint32_t mu[3][52];
  __shared__ float nrm[12], nrm2[6], csum[6][9];
  const int mat = blockIdx.x / kPrepSplit, blk = blockIdx.x % kPrepSplit;
  const int tid = threadIdx.x, lane = tid & 31, warp = tid >> 5, g = lane >> 2, c = lane & 3;
  const __nv_bfloat16* wqkv = mat < 2 ? wqkv_t : wqkv_s;
  const __nv_bfloat16* wo = mat < 2 ? wo_t : wo_s;
  const bool isA = (mat & 1) == 0;
  {
    uint4 v[3], u[3];
#pragma unroll
    for (int q = 0; q < 3; q++) {
      const int e = tid + q * kPrepThreads, i = e / 12, c8 = (e % 12) * 8;
      v[q] = __ldg(reinterpret_cast<const uint4*>(wqkv + i * 288 + (isA ? 0 : 192) + c8));
      u[q] = __ldg(reinterpret_cast<const uint4*>(isA ? wqkv + i * 288 + 96 + c8 : wo + i * 96 + c8));
    }
#pragma unroll
    for (int q = 0; q < 3; q++) {
      const int e = tid + q * kPrepThreads, i = e / 12, c4 = (e % 12) * 4;
      *reinterpret_cast<uint4*>(&raw[0][i][c4]) = v[q];
      *reinterpret_cast<uint4*>(&raw[1][i][c4]) = u[q];
    }
  }
  __syncthreads();
  {
    const int m = warp / 6, cp = (warp % 6) * 8 + g;
    float s0 = 0.f, s1 = 0.f, q0 = 0.f, q1 = 0.f;
#pragma unroll
    for (int i = 0; i < 24; i++) {
      const uint32_t w = raw[m][4 * i + c][cp];
      const float lo = __uint_as_float(w << 16), hi = __uint_as_float(w & 0xffff0000u);
      s0 += lo; s1 += hi; q0 = fmaf(lo, lo, q0); q1 = fmaf(hi, hi, q1);
    }
    s0 = quad_sum(s0) * (1.f / 96.f); s1 = quad_sum(s1) * (1.f / 96.f); q0 = quad_sum(q0); q1 = quad_sum(q1);
    if (mat == 1 && m == 1) {
      float r0 = 0.f, r1 = 0.f;
#pragma unroll
      for (int i = 0; i < 12; i++) {
        const uint32_t w0 = raw[1][2 * cp][4 * i + c], w1 = raw[1][2 * cp + 1][4 * i + c];
        r0 += __uint_as_float(w0 << 16) + __uint_as_float(w0 & 0xffff0000u);
        r1 += __uint_as_float(w1 << 16) + __uint_as_float(w1 & 0xffff0000u);
      }
      r0 = quad_sum(r0) * (1.f / 96.f); r1 = quad_sum(r1) * (1.f / 96.f);
      s0 = r0; s1 = r1;
    }
    if (m == 1 && c == 0) {
      const uint32_t hi = mat == 3 ? 0u : pack_bf2(s0, s1);
      mu[0][cp] = hi;
      mu[1][cp] = mat == 3 ? 0u : pack_bf2(s0 - __uint_as_float(hi << 16), s1 - __uint_as_float(hi & 0xffff0000u));
      mu[2][cp] = 0u;
    }
    if (m == 0 || isA) {
      q0 = fmaxf(fmaf(-96.f * s0, s0, q0), 0.f) + q0 * 1e-6f;
      q1 = fmaxf(fmaf(-96.f * s1, s1, q1), 0.f) + q1 * 1e-6f;
    }
    const bool usemax = m == 1 && mat == 3;
    float t = usemax ? fmaxf(q0, q1) : q0 + q1;
#pragma unroll
    for (int o = 4; o < 32; o <<= 1) { const float z = __shfl_xor_sync(0xffffffffu, t, o); t = usemax ? fmaxf(t, z) : t + z; }
    if (lane == 0) nrm[warp] = t;
  }
  __syncthreads();
  if (warp >= 6) return;
  float d[4] = {0.f, 0.f, 0.f, 0.f}, e[4] = {0.f, 0.f, 0.f, 0.f}, v0, v1;
  {
    const uint32_t arow = smem_u32(&raw[0][16 * warp + (lane & 15)][(lane >> 4) * 4]);
    const uint32_t brow = isA ? smem_u32(&raw[1][blk * 8 + (lane & 7)][(lane >> 3) * 4]) : smem_u32(&raw[1][lane][blk * 4]);
    const uint32_t mrow = smem_u32(&mu[min(lane & 7, 2)][(lane >> 3) * 4]);
#pragma unroll
    for (int k2 = 0; k2 < 3; k2++) {
      uint32_t b[4], m[4];
      if (isA) ldsm4(b, brow + k2 * 64);
      else asm volatile("ldmatrix.sync.aligned.m8n8.x4.trans.shared.b16 {%0,%1,%2,%3}, [%4];"
                        : "=r"(b[0]), "=r"(b[1]), "=r"(b[2]), "=r"(b[3]) : "r"(brow + k2 * (32 * 208)) : "memory");
      ldsm4(m, mrow + k2 * 64);
#pragma unroll
      for (int hf = 0; hf < 2; hf++) {
        uint32_t a[4];
        ldsm4(a, arow + (2 * k2 + hf) * 32);
        asm volatile("mma.sync.aligned.m16n8k16.row.col.f32.bf16.bf16.f32 {%0,%1,%2,%3},{%4,%5,%6,%7},{%8,%9},{%0,%1,%2,%3};"
                     : "+f"(d[0]), "+f"(d[1]), "+f"(d[2]), "+f"(d[3])
                     : "r"(a[0]), "r"(a[1]), "r"(a[2]), "r"(a[3]), "r"(b[2 * hf]), "r"(b[2 * hf + 1]));
        asm volatile("mma.sync.aligned.m16n8k16.row.col.f32.bf16.bf16.f32 {%0,%1,%2,%3},{%4,%5,%6,%7},{%8,%9},{%0,%1,%2,%3};"
                     : "+f"(e[0]), "+f"(e[1]), "+f"(e[2]), "+f"(e[3])
                     : "r"(a[0]), "r"(a[1]), "r"(a[2]), "r"(a[3]), "r"(m[2 * hf]), "r"(m[2 * hf + 1]));
      }
    }
    v0 = __shfl_sync(0xffffffffu, e[0] + e[1], lane & ~3); v1 = __shfl_sync(0xffffffffu, e[2] + e[3], lane & ~3);
    d[0] -= v0; d[1] -= v0; d[2] -= v1; d[3] -= v1;
    float t0 = d[0] + d[2], t1 = d[1] + d[3], t2 = v0 + v1;
#pragma unroll
    for (int o = 4; o < 32; o <<= 1) {
      t0 += __shfl_xor_sync(0xffffffffu, t0, o); t1 += __shfl_xor_sync(0xffffffffu, t1, o); t2 += __shfl_xor_sync(0xffffffffu, t2, o);
    }
    if (g == 0) { csum[warp][2 * c] = t0; csum[warp][2 * c + 1] = t1; csum[warp][8] = t2; }
  }
  const float nl = nrm[0] + nrm[1] + nrm[2] + nrm[3] + nrm[4] + nrm[5];
  const float nr = mat == 3 ? fmaxf(fmaxf(fmaxf(nrm[6], nrm[7]), fmaxf(nrm[8], nrm[9])), fmaxf(nrm[10], nrm[11]))
                            : nrm[6] + nrm[7] + nrm[8] + nrm[9] + nrm[10] + nrm[11];
  const float bound = __fsqrt_rn(nl) * __fsqrt_rn(nr) * 1.01f;
  const float f = isA ? 0.14724448f : 1.f;
  float sc = pow2_ceil(fmaxf(bound * (isA ? 0.14724448f / 160.f : mat == 1 ? 1.f / 16.f : 1.f / 64.f), 1e-30f));
  if (isA) sc = fminf(fmaxf(sc, 1.f), 32768.f);
  if (mat == 3) {
    if (blk == 0 && tid == 0) { g_par.kb = sc; g_par.ticket = 0; }
    if (sc <= 1.f && sc >= 1.f / 1024.f) sc = 1.f;
  }
  const float mul = f * __uint_as_float(0x7f000000u - __float_as_uint(sc));
  if (blk == 0 && tid == 0) (mat == 0 ? g_par.cS_t : mat == 1 ? g_par.kt : mat == 2 ? g_par.cS_s : g_par.kappa) = sc;
  asm volatile("bar.sync 1, 192;" ::: "memory");
  float mean[2];
#pragma unroll
  for (int b = 0; b < 2; b++)
    mean[b] = (csum[0][2 * c + b] + csum[1][2 * c + b] + csum[2][2 * c + b] + csum[3][2 * c + b] + csum[4][2 * c + b] + csum[5][2 * c + b]) *
              (1.f / 96.f);
  uint8_t* img = reinterpret_cast<uint8_t*>(g_wimg) + (mat == 0 ? 0 : mat == 1 ? kOffWt : mat == 2 ? kOffAs : kOffWs);
  const float vmean = (csum[0][8] + csum[1][8] + csum[2][8] + csum[3][8] + csum[4][8] + csum[5][8]) * (1.f / 96.f);
  float off = 0.f;
  if (mat == 2) {
    float q2 = 0.f;
#pragma unroll
    for (int q = 0; q < 4; q++) q2 = fmaf(d[q] - mean[q & 1], d[q] - mean[q & 1], q2);
#pragma unroll
    for (int o = 16; o; o >>= 1) q2 += __shfl_xor_sync(0xffffffffu, q2, o);
    if (lane == 0) nrm2[warp] = q2;
    asm volatile("bar.sync 1, 192;" ::: "memory");
    q2 = nrm2[0] + nrm2[1] + nrm2[2] + nrm2[3] + nrm2[4] + nrm2[5];
    off = 1.5f * pow2_ceil(fmaxf(__fsqrt_rn(q2 * (1.f / 768.f)) * mul * 3.f, 1e-4f));
  }
#pragma unroll
  for (int q = 0; q < 4; q++) {
    const int kp = ch_pos(16 * warp + g + 8 * (q >> 1)), np = ch_pos(blk * 8 + 2 * c + (q & 1));
    const uint32_t ko = (kp >> 5) * (mat < 2 ? kAtChunk : 6144) + (kp & 31) * 2;
    uint32_t a = ko + np * 64;
    a ^= ((a >> 7) & 3) << 4;
    float o = (d[q] - mean[q & 1]) * mul;
    o = mat == 2 ? o + off : __uint_as_float((__float_as_uint(o) + 0x8000u) & 0xffff0000u);
    *reinterpret_cast<__half*>(img + a) = __float2half_rn(o);
    if (mat == 1 && blk == 0) {
      a = (kp >> 5) * kAtChunk + (kp & 31) * 2 + (96 + 2 * c + (q & 1)) * 64;
      a ^= ((a >> 7) & 3) << 4;
      *reinterpret_cast<__half*>(reinterpret_cast<uint8_t*>(g_wimg) + a) = __float2half_rn((q & 1) ? ((q >> 1 ? v1 : v0) - vmean) * mul : 1.f / 96.f);
    }
  }
}

typedef CUresult (*EncodeFn)(CUtensorMap*, CUtensorMapDataType, cuuint32_t, void*, const cuuint64_t*, const cuuint64_t*,
                             const cuuint32_t*, const cuuint32_t*, CUtensorMapInterleave, CUtensorMapSwizzle,
                             CUtensorMapL2promotion, CUtensorMapFloatOOBfill);

}

extern "C" void kernel_launch(void* const* d_in, const int* in_sizes, int n_in, void* d_out, int out_size) {
  (void)in_sizes; (void)n_in; (void)out_size;
  static EncodeFn enc = nullptr;
  static int nsm = 0;
  if (!enc) {
    void* fn = nullptr;
    cudaDriverEntryPointQueryResult qr;
    cudaGetDriverEntryPoint("cuTensorMapEncodeTiled", &fn, cudaEnableDefault, &qr);
    enc = reinterpret_cast<EncodeFn>(fn);
    int dev = 0;
    cudaGetDevice(&dev);
    cudaDeviceGetAttribute(&nsm, cudaDevAttrMultiProcessorCount, dev);
    cudaFuncSetAttribute(swin_main, cudaFuncAttributeMaxDynamicSharedMemorySize, kSmemBytes);
  }
  Maps tms;
  CUtensorMap& tm = tms.load;
  const cuuint64_t dims[5] = {32, kW, kH, kT, 3};
  const cuuint64_t strides[4] = {192, 192ull * kW, 192ull * kW * kH, 64};
  const cuuint32_t box[5] = {32, 7, 7, 4, 3};
  const cuuint32_t es[5] = {1, 1, 1, 1, 1};
  enc(&tm, CU_TENSOR_MAP_DATA_TYPE_BFLOAT16, 5, d_in[0], dims, strides, box, es, CU_TENSOR_MAP_INTERLEAVE_NONE,
      CU_TENSOR_MAP_SWIZZLE_64B, CU_TENSOR_MAP_L2_PROMOTION_L2_128B, CU_TENSOR_MAP_FLOAT_OOB_FILL_NONE);

  const cuuint64_t dims2[3] = {24ull * kW, kH, kT};
  const cuuint64_t strides2[2] = {192ull * kW, 192ull * kW * kH};
  const cuuint32_t box2[3] = {168, 7, 4};
  enc(&tms.prefetch, CU_TENSOR_MAP_DATA_TYPE_UINT64, 3, d_in[0], dims2, strides2, box2, es, CU_TENSOR_MAP_INTERLEAVE_NONE,
      CU_TENSOR_MAP_SWIZZLE_NONE, CU_TENSOR_MAP_L2_PROMOTION_L2_128B, CU_TENSOR_MAP_FLOAT_OOB_FILL_NONE);

  cudaStream_t st = cudaStreamPerThread;
  swin_prep<<<4 * kPrepSplit, kPrepThreads, 0, st>>>(
      static_cast<const __nv_bfloat16*>(d_in[1]), static_cast<const __nv_bfloat16*>(d_in[2]),
      static_cast<const __nv_bfloat16*>(d_in[3]), static_cast<const __nv_bfloat16*>(d_in[4]));

  cudaLaunchConfig_t cfg = {};
  cfg.gridDim = dim3(nsm);
  cfg.blockDim = dim3(512);
  cfg.dynamicSmemBytes = kSmemBytes;
  cfg.stream = st;
  cudaLaunchAttribute at[1];
  at[0].id = cudaLaunchAttributeProgrammaticStreamSerialization;
  at[0].val.programmaticStreamSerializationAllowed = 1;
  cfg.attrs = at;
  cfg.numAttrs = 1;
  cudaLaunchKernelEx(&cfg, swin_main, tms, static_cast<uint8_t*>(d_out), mk_desc(1024), mk_desc(1024), (uint32_t)(kH * kW * 192));
}
```

```cpp
#include <cuda_runtime.h>
#include <cuda.h>
#include <cuda_bf16.h>
#include <cuda_fp16.h>
#include <stdint.h>

namespace {

constexpr int kH = 511, kW = 511, kT = 4;
constexpr int kNWX = 73, kNWIN = 73 * 73;
constexpr int kChunk = 12544;
constexpr int kPlane = 3136;
constexpr int kXBytes = 37632;
constexpr int kZero = kXBytes + 896, kFull = kXBytes + 1024, kDone = kFull + 8, kRel = kFull + 16, kFlag = kFull + 20, kExtra = kFull + 24;
constexpr int kSlot = 38912;
constexpr int kWMat = 18432;
constexpr int kAtChunk = 200 * 64;
constexpr int kOffWt = 104 * 64;
constexpr int kOffAs = 3 * kAtChunk, kOffWs = kOffAs + kWMat;
constexpr int kWBytes = kOffWs + kWMat;
constexpr int kSmemBytes = kWBytes + 4 * kSlot;

struct Params {
  float cS_t, cS_s;
  float kt;
  float kappa;
  float kb;
  uint32_t ticket;
};

__device__ uint4 g_wimg[kWBytes / 16];
__device__ __align__(16) Params g_par;

__device__ __forceinline__ uint32_t smem_u32(const void* p) { return (uint32_t)__cvta_generic_to_shared(p); }
__device__ __forceinline__ void mbar_init(uint32_t a, int c) { asm volatile("mbarrier.init.shared::cta.b64 [%0], %1;" ::"r"(a), "r"(c)); }
__device__ __forceinline__ void mbar_expect(uint32_t a, int bytes) {
  asm volatile("mbarrier.arrive.expect_tx.shared::cta.b64 _, [%0], %1;" ::"r"(a), "r"(bytes) : "memory");
}
__device__ __forceinline__ void mbar_arrive(uint32_t a, uint32_t off = 0) {
  asm volatile("{\n.reg .pred p;\nsetp.eq.u32 p, %1, 0;\n@p mbarrier.arrive.shared::cta.b64 _, [%0];\n}" ::"r"(a), "r"(off) : "memory");
}
__device__ __forceinline__ void mbar_wait(uint32_t a, uint32_t par) {
  asm volatile(
      "{\n.reg .pred p;\n.reg .u32 n;\n"
      "mbarrier.try_wait.parity.shared::cta.b64 p, [%0], %1;\n"
      "@p bra.uni WDONE;\n"
      "mov.u32 n, 0;\n"
      "WLOOP:\n"
      "mbarrier.try_wait.parity.shared::cta.b64 p, [%0], %1;\n"
      "@p bra.uni WDONE;\n"
      "add.u32 n, n, 1;\n"
      "setp.lt.u32 p, n, 0x100000;\n"
      "@p bra.uni WLOOP;\n"
      "trap;\n"
      "WDONE:\n}" ::"r"(a), "r"(par & 1) : "memory");
}
__device__ __forceinline__ bool mbar_pending_or(uint32_t a, uint32_t par, uint32_t c) {
  uint32_t r;
  asm volatile("{\n.reg .pred p;\nmbarrier.test_wait.parity.shared::cta.b64 p, [%1], %2;\nsetp.ne.or.u32 p, %3, 0, !p;\n"
               "vote.sync.any.pred p, p, 0xffffffff;\nselp.b32 %0, 1, 0, p;\n}" : "=r"(r) : "r"(a), "r"(par & 1), "r"(c) : "memory");
  return r;
}
__device__ __forceinline__ uint32_t lds32(uint32_t a) {
  uint32_t v; asm volatile("ld.shared.b32 %0, [%1];" : "=r"(v) : "r"(a) : "memory"); return v;
}
__device__ __forceinline__ void sts32(uint32_t a, uint32_t v) { asm volatile("st.shared.b32 [%0], %1;" ::"r"(a), "r"(v) : "memory"); }
__device__ __forceinline__ void tma_load_win(uint32_t slot, const CUtensorMap* m, uint32_t w) {
  const uint32_t wy = (w * 57457u) >> 22, wx = w - wy * kNWX;
  mbar_expect(slot + kFull, kXBytes);
  asm volatile(
      "cp.async.bulk.tensor.5d.shared::cluster.global.mbarrier::complete_tx::bytes [%0], [%1, {%3,%4,%5,%3,%3}], [%2];" ::"r"(slot),
      "l"(m), "r"(slot + kFull), "r"(0), "r"(wx * 7), "r"(wy * 7)
      : "memory");
}
__device__ __forceinline__ void tma_prefetch_win(const CUtensorMap* m, uint32_t w) {
  const uint32_t wy = (w * 57457u) >> 22, wx = w - wy * kNWX;
  asm volatile("cp.async.bulk.prefetch.tensor.3d.L2.global [%0, {%1,%2,%3}];" ::"l"(m + 1), "r"(wx * 168), "r"(wy * 7), "r"(0) : "memory");
}
__device__ __forceinline__ void wg_fence() { asm volatile("wgmma.fence.sync.aligned;" ::: "memory"); }
__device__ __forceinline__ void wg_commit() { asm volatile("wgmma.commit_group.sync.aligned;" ::: "memory"); }
__device__ __forceinline__ void wg_wait() { asm volatile("wgmma.wait_group.sync.aligned 0;" ::: "memory"); }
template <int N>
__device__ __forceinline__ void pin(uint32_t* d) {
#pragma unroll
  for (int i = 0; i < N; i++) asm volatile("" : "+r"(d[i])::"memory");
}
__device__ __forceinline__ uint32_t fresh(uint32_t v) { asm volatile("" : "+r"(v)); return v; }
__device__ __forceinline__ float fresh(float v) { asm volatile("" : "+f"(v)); return v; }
template <int N>
__device__ __forceinline__ void launder(uint32_t* q) {
#pragma unroll
  for (int j = 0; j < N; j++) { uint32_t t; asm volatile("mov.b32 %0, %1;" : "=r"(t) : "r"(q[j])); q[j] = t; }
}
__device__ __forceinline__ void sfence(uint32_t& v) {
  asm volatile("{\n.reg .pred p;\nsetp.eq.u32 p, %1, 0x7fffffff;\n@p mov.u32 %0, %%clock;\n}" : "+r"(v) : "r"(gridDim.x) : "memory");
}
constexpr uint64_t mk_desc(uint32_t addr) { return ((uint64_t)0x80000020u << 32) | (addr >> 4) | (1u << 16); }

#define R4(d, i) "+r"(d[i]), "+r"(d[i + 1]), "+r"(d[i + 2]), "+r"(d[i + 3])
#define O4(d, i) "=r"(d[i]), "=r"(d[i + 1]), "=r"(d[i + 2]), "=r"(d[i + 3])
#define D26 "{%0,%1,%2,%3,%4,%5,%6,%7,%8,%9,%10,%11,%12,%13,%14,%15,%16,%17,%18,%19,%20,%21,%22,%23,%24,%25},"
#define D24 "{%0,%1,%2,%3,%4,%5,%6,%7,%8,%9,%10,%11,%12,%13,%14,%15,%16,%17,%18,%19,%20,%21,%22,%23},"
#define D14 "{%0,%1,%2,%3,%4,%5,%6,%7,%8,%9,%10,%11,%12,%13},"

template <int SC, int TB>
__device__ __forceinline__ void wgmma(uint32_t (&d)[24], const uint32_t* a, uint64_t db) {
  if (SC == 2)
    asm volatile("{\n.reg .pred p;\nsetp.eq.u32 p, %30, 0x7fffffff;\n"
                 "wgmma.mma_async.sync.aligned.m64n96k16.f16.f16.f16 " D24 "{%24,%25,%26,%27}, %28, p, 1, 1, %29;\n}"
                 : R4(d, 0), R4(d, 4), R4(d, 8), R4(d, 12), R4(d, 16), R4(d, 20)
                 : "r"(a[0]), "r"(a[1]), "r"(a[2]), "r"(a[3]), "l"(db), "n"(TB), "r"(gridDim.x));
  else if (SC)
    asm volatile("wgmma.mma_async.sync.aligned.m64n96k16.f16.f16.f16 " D24 "{%24,%25,%26,%27}, %28, 1, 1, 1, %29;"
                 : R4(d, 0), R4(d, 4), R4(d, 8), R4(d, 12), R4(d, 16), R4(d, 20)
                 : "r"(a[0]), "r"(a[1]), "r"(a[2]), "r"(a[3]), "l"(db), "n"(TB));
  else
    asm volatile("wgmma.mma_async.sync.aligned.m64n96k16.f16.f16.f16 " D24 "{%24,%25,%26,%27}, %28, 0, 1, 1, %29;"
                 : O4(d, 0), O4(d, 4), O4(d, 8), O4(d, 12), O4(d, 16), O4(d, 20)
                 : "r"(a[0]), "r"(a[1]), "r"(a[2]), "r"(a[3]), "l"(db), "n"(TB));
}
template <int SC, int TB>
__device__ __forceinline__ void wgmma(uint32_t (&d)[26], const uint32_t* a, uint64_t db) {
  if (SC)
    asm volatile("wgmma.mma_async.sync.aligned.m64n104k16.f16.f16.f16 " D26 "{%26,%27,%28,%29}, %30, 1, 1, 1, 0;"
                 : R4(d, 0), R4(d, 4), R4(d, 8), R4(d, 12), R4(d, 16), R4(d, 20), "+r"(d[24]), "+r"(d[25])
                 : "r"(a[0]), "r"(a[1]), "r"(a[2]), "r"(a[3]), "l"(db));
  else
    asm volatile("wgmma.mma_async.sync.aligned.m64n104k16.f16.f16.f16 " D26 "{%26,%27,%28,%29}, %30, 0, 1, 1, 0;"
                 : O4(d, 0), O4(d, 4), O4(d, 8), O4(d, 12), O4(d, 16), O4(d, 20), "=r"(d[24]), "=r"(d[25])
                 : "r"(a[0]), "r"(a[1]), "r"(a[2]), "r"(a[3]), "l"(db));
}
template <int SC, int TB>
__device__ __forceinline__ void wgmma(uint32_t (&d)[16], const uint32_t* a, uint64_t db) {
  if (SC)
    asm volatile("wgmma.mma_async.sync.aligned.m64n56k16.f16.f16.f16 " D14 "{%14,%15,%16,%17}, %18, 1, 1, 1, 0;"
                 : R4(d, 0), R4(d, 4), R4(d, 8), "+r"(d[12]), "+r"(d[13])
                 : "r"(a[0]), "r"(a[1]), "r"(a[2]), "r"(a[3]), "l"(db));
  else
    asm volatile("wgmma.mma_async.sync.aligned.m64n56k16.f16.f16.f16 " D14 "{%14,%15,%16,%17}, %18, 0, 1, 1, 0;"
                 : O4(d, 0), O4(d, 4), O4(d, 8), "=r"(d[12]), "=r"(d[13])
                 : "r"(a[0]), "r"(a[1]), "r"(a[2]), "r"(a[3]), "l"(db));
}
template <int SC, int OFF, int CH, int ND>
__device__ __forceinline__ void gemm(uint32_t (&d)[ND], const uint32_t* a, uint64_t db) {
  asm volatile("" : "+l"(db));
  wg_fence();
  wgmma<SC, 0>(d, a, db + OFF / 16);
#pragma unroll
  for (int k = 1; k < 6; k++) wgmma<1, 0>(d, a + 4 * k, db + (OFF + (k >> 1) * CH + (k & 1) * 32) / 16);
  wg_commit();
}
__device__ __forceinline__ void lds128(uint32_t* r, uint32_t a) {
  asm volatile("ld.shared.v4.b32 {%0,%1,%2,%3}, [%4];" : "=r"(r[0]), "=r"(r[1]), "=r"(r[2]), "=r"(r[3]) : "r"(a) : "memory");
}
__device__ __forceinline__ void ldsm4(uint32_t* r, uint32_t a) {
  asm volatile("ldmatrix.sync.aligned.m8n8.x4.shared.b16 {%0,%1,%2,%3}, [%4];"
               : "=r"(r[0]), "=r"(r[1]), "=r"(r[2]), "=r"(r[3]) : "r"(a) : "memory");
}
__device__ __forceinline__ void stsm4(uint32_t a, const uint32_t* r) {
  asm volatile("stmatrix.sync.aligned.m8n8.x4.shared.b16 [%0], {%1,%2,%3,%4};" ::"r"(a), "r"(r[0]), "r"(r[1]), "r"(r[2]), "r"(r[3])
               : "memory");
}
__device__ __forceinline__ void stg3(uint8_t* p, const uint32_t* r, uint32_t off) {
  asm volatile("{\n.reg .pred p;\nsetp.eq.u32 p, %13, 0;\n@p st.global.v4.b32 [%0], {%1,%2,%3,%4};\n"
               "@p st.global.v4.b32 [%0+64], {%5,%6,%7,%8};\n@p st.global.v4.b32 [%0+128], {%9,%10,%11,%12};\n}" ::"l"(p),
               "r"(r[0]), "r"(r[1]), "r"(r[2]), "r"(r[3]), "r"(r[4]), "r"(r[5]), "r"(r[6]), "r"(r[7]), "r"(r[8]), "r"(r[9]), "r"(r[10]), "r"(r[11]),
               "r"(off) : "memory");
}
__device__ __forceinline__ uint32_t pack_h2(float lo, float hi) {
  uint32_t r; asm("cvt.rn.f16x2.f32 %0, %1, %2;" : "=r"(r) : "f"(hi), "f"(lo)); return r;
}
__device__ __forceinline__ uint32_t pack_h2_sat(float lo, float hi) {
  uint32_t r; asm("cvt.rn.satfinite.f16x2.f32 %0, %1, %2;" : "=r"(r) : "f"(hi), "f"(lo)); return r;
}
__device__ __forceinline__ uint32_t pack_bf2(float lo, float hi) {
  uint32_t r; asm("cvt.rn.bf16x2.f32 %0, %1, %2;" : "=r"(r) : "f"(hi), "f"(lo)); return r;
}
__device__ __forceinline__ __half2 as_h2(uint32_t v) { return *reinterpret_cast<__half2*>(&v); }
__device__ __forceinline__ uint32_t as_u(__half2 v) { return *reinterpret_cast<uint32_t*>(&v); }
__device__ __forceinline__ float2 unpack_h2(uint32_t v) { return __half22float2(as_h2(v)); }
__device__ __forceinline__ float low_f(uint32_t v) { return __low2float(as_h2(v)); }
__device__ __forceinline__ uint32_t h2ex2(uint32_t v) { uint32_t r; asm("ex2.approx.f16x2 %0, %1;" : "=r"(r) : "r"(v)); return r; }
__device__ __forceinline__ uint32_t h2max(uint32_t a, uint32_t b) { return as_u(__hmax2(as_h2(a), as_h2(b))); }
__device__ __forceinline__ uint32_t h2add(uint32_t a, uint32_t b) { return as_u(__hadd2(as_h2(a), as_h2(b))); }
__device__ __forceinline__ uint32_t h2sub(uint32_t a, uint32_t b) { return as_u(__hsub2(as_h2(a), as_h2(b))); }
__device__ __forceinline__ uint32_t h2mul(uint32_t a, uint32_t b) { return as_u(__hmul2(as_h2(a), as_h2(b))); }
__device__ __forceinline__ uint32_t h2neg(uint32_t a) { return as_u(__hneg2(as_h2(a))); }
__device__ __forceinline__ uint32_t h2fma(uint32_t a, uint32_t b, uint32_t c) { return as_u(__hfma2(as_h2(a), as_h2(b), as_h2(c))); }
__device__ __forceinline__ uint32_t lo2(uint32_t v) { return as_u(__low2half2(as_h2(v))); }
__device__ __forceinline__ uint32_t hi2(uint32_t v) { return as_u(__high2half2(as_h2(v))); }
__device__ __forceinline__ uint32_t fold_add(uint32_t a, uint32_t b) { return h2add(__byte_perm(a, b, 0x5410), __byte_perm(a, b, 0x7632)); }
__device__ __forceinline__ uint32_t sel(uint32_t p, uint32_t a, uint32_t b) {
  uint32_t r; asm("{\n.reg .pred p;\nsetp.ne.u32 p, %3, 0;\nselp.b32 %0, %1, %2, p;\n}" : "=r"(r) : "r"(a), "r"(b), "r"(p)); return r;
}
__device__ __forceinline__ float sel4(uint32_t c, float a0, float a1, float a2, float a3) {
  return __uint_as_float(sel(c & 2, sel(c & 1, __float_as_uint(a3), __float_as_uint(a2)), sel(c & 1, __float_as_uint(a1), __float_as_uint(a0))));
}
__device__ __forceinline__ float rcp_fast(float v) { float r; asm("rcp.approx.ftz.f32 %0, %1;" : "=f"(r) : "f"(v)); return r; }
__device__ __forceinline__ float rsq_fast(float v) { float r; asm("rsqrt.approx.ftz.f32 %0, %1;" : "=f"(r) : "f"(v)); return r; }
__device__ __forceinline__ uint32_t shfl_x(uint32_t v, int m) { return __shfl_xor_sync(0xffffffffu, v, m); }
__device__ __forceinline__ uint32_t shfl_q(uint32_t v, int i) { return __shfl_sync(0xffffffffu, v, i, 4); }
__device__ __forceinline__ float quad_sum(float v) {
  v += __shfl_xor_sync(0xffffffffu, v, 1);
  return v + __shfl_xor_sync(0xffffffffu, v, 2);
}
__device__ __forceinline__ uint32_t score_scale(const float* p) { const float v = __ldcg(p); return pack_h2(v, v); }

constexpr float kEps96 = 1e-5f * 96.f * 96.f;
__device__ __forceinline__ float2 stat_f32(uint32_t e) {
  const float2 h = unpack_h2(e);
  return make_float2(__uint_as_float(sel(e & 0x8000u, (e << 16) & 0x7fff0000u, __float_as_uint(h.x))),
                     __uint_as_float(sel(e & 0x8000u, e & 0xffff0000u, __float_as_uint(h.y))));
}

struct Tile {
  uint32_t ring, a;
  uint32_t next;
  uint32_t n;
  int live;
  uint32_t stat, wrap;
  uint32_t flag;
  uint32_t gate;
};
struct TPar { float kt, sgmin, outmax; };

__device__ __forceinline__ uint32_t swz(uint32_t r, int t) { return fresh(r ^ (((r >> 3) + 8 * t) & 0x30)); }
__device__ __forceinline__ void load_rows(uint32_t* x0, uint32_t* x1, uint32_t ring, uint32_t r, int t) {
  const uint32_t a0 = swz(r, t), a1 = swz(r, t + 1), u0 = ring + t * kPlane, u1 = u0 + kPlane;
  lds128(x0, a0 + u0); lds128(x1, a1 + u1);
  lds128(x0 + 4, fresh(a0 ^ 32) + (u0 + kChunk)); lds128(x1 + 4, fresh(a1 ^ 32) + (u1 + kChunk));
  lds128(x0 + 8, a0 + (u0 + 2 * kChunk)); lds128(x1 + 8, a1 + (u1 + 2 * kChunk));
}
__device__ __forceinline__ void to_half(uint32_t (&z)[24], const uint32_t* x) {
#pragma unroll
  for (int j = 0; j < 24; j += 2) {
    const int o = j < 12 ? 2 * j : 2 * j - 23;
    uint32_t t;
    asm("cvt.rz.f16x2.f32 %0, %1, %2;" : "=r"(t) : "f"(__uint_as_float(x[j + 1])), "f"(__uint_as_float(x[j])));
    z[o] = pack_h2(__uint_as_float(x[j] << 16), __uint_as_float(x[j + 1] << 16));
    z[o + 2] = t & 0xfff8fff8u;
  }
}
__device__ __forceinline__ void load_general(uint32_t (&z)[24], uint32_t ring, uint32_t r, int t, float& ie0, float& ie1, float& m0, float& m1) {
  float acc[48];
  uint32_t x0[12], x1[12];
  load_rows(x0, x1, ring, r, t);
#pragma unroll
  for (int j = 0; j < 12; j++) {
    acc[4 * j] = __uint_as_float(x0[j] << 16); acc[4 * j + 1] = __uint_as_float(x0[j] & 0xffff0000u);
    acc[4 * j + 2] = __uint_as_float(x1[j] << 16); acc[4 * j + 3] = __uint_as_float(x1[j] & 0xffff0000u);
  }
  float s[4], q[4];
#pragma unroll
  for (int e = 0; e < 4; e++) { s[e] = acc[e]; q[e] = acc[e] * acc[e]; }
#pragma unroll
  for (int j = 4; j < 48; j++) { s[j & 3] += acc[j]; q[j & 3] = fmaf(acc[j], acc[j], q[j & 3]); }
  const float s0 = quad_sum(s[0] + s[1]), s1 = quad_sum(s[2] + s[3]), q0 = quad_sum(q[0] + q[1]), q1 = quad_sum(q[2] + q[3]);
  const float u0 = rsq_fast(fmaxf(fmaf(-s0, s0, fmaf(q0, 96.f, kEps96)), kEps96));
  const float u1 = rsq_fast(fmaxf(fmaf(-s1, s1, fmaf(q1, 96.f, kEps96)), kEps96));
  const float n0 = -s0 * u0, n1 = -s1 * u1;
  ie0 = 96.f * u0; ie1 = 96.f * u1;
  m0 = s0 * (1.f / 96.f); m1 = s1 * (1.f / 96.f);
#pragma unroll
  for (int j = 0; j < 12; j++) {
    const int o = 8 * (j >> 1) + (j & 1);
    z[2 * j] = pack_h2(fmaf(acc[o], ie0, n0), fmaf(acc[o + 4], ie0, n0));
    z[2 * j + 1] = pack_h2(fmaf(acc[o + 2], ie1, n1), fmaf(acc[o + 6], ie1, n1));
  }
}
template <bool kDown>
__device__ __forceinline__ uint32_t sumsq2(const uint32_t* z) {
  uint32_t q0, q1;
#pragma unroll
  for (int j = 0; j < 12; j++) {
    const uint32_t u = kDown ? h2mul(z[2 * j], 0x1c001c00u) : z[2 * j], v = kDown ? h2mul(z[2 * j + 1], 0x1c001c00u) : z[2 * j + 1];
    q0 = j ? h2fma(u, u, q0) : h2mul(u, u); q1 = j ? h2fma(v, v, q1) : h2mul(v, v);
  }
  return fold_add(q0, q1);
}
template <bool kDown>
__device__ __forceinline__ float row_sumsq(const uint32_t* z0, const uint32_t* z1, uint32_t c) {
  const uint32_t a = sumsq2<kDown>(z0), b = sumsq2<kDown>(z1);
  uint32_t t = h2add(sel(c & 2, b, a), shfl_x(sel(c & 2, a, b), 2));
  t = h2add(t, shfl_x(t, 1));
  return low_f(sel(c & 1, t >> 16, t));
}
__device__ __forceinline__ void scores2(const uint32_t* q, const uint32_t* z0, const uint32_t* z1, uint32_t* f) {
  uint32_t d[8];
#pragma unroll
  for (int j = 0; j < 12; j++) {
    const uint32_t kk[4] = {z0[2 * j], z0[2 * j + 1], z1[2 * j], z1[2 * j + 1]};
#pragma unroll
    for (int e = 0; e < 4; e++) {
      d[e] = j ? h2fma(q[2 * j], kk[e], d[e]) : h2mul(q[2 * j], kk[e]);
      d[4 + e] = j ? h2fma(q[2 * j + 1], kk[e], d[4 + e]) : h2mul(q[2 * j + 1], kk[e]);
    }
  }
#pragma unroll
  for (int e = 0; e < 4; e++) f[e] = fold_add(d[2 * e], d[2 * e + 1]);
}
struct Xch { uint32_t keep[2], got[2]; };
__device__ __forceinline__ Xch pair_send(const uint32_t* a, const uint32_t* b, uint32_t c, int m) {
  Xch x;
#pragma unroll
  for (int e = 0; e < 2; e++) { x.keep[e] = fresh(sel(c & m, b[e], a[e])); x.got[e] = shfl_x(sel(c & m, a[e], b[e]), m); }
  return x;
}
__device__ __forceinline__ void pair_recv(uint32_t* k, const Xch& x) { k[0] = h2add(x.keep[0], x.got[0]); k[1] = h2add(x.keep[1], x.got[1]); }
__device__ __forceinline__ void mix2(uint32_t* y, const uint32_t* v, uint32_t c0, uint32_t c1) {
#pragma unroll
  for (int j = 0; j < 12; j++) {
    y[2 * j] = h2fma(v[2 * j + 1], hi2(c0), h2fma(v[2 * j], lo2(c0), y[2 * j]));
    y[2 * j + 1] = h2fma(v[2 * j + 1], hi2(c1), h2fma(v[2 * j], lo2(c1), y[2 * j + 1]));
  }
  pin<24>(y);
}
__device__ __forceinline__ void norm_store(uint32_t* y, uint32_t r0, uint32_t r1, uint32_t r, int t) {
#pragma unroll
  for (int j = 0; j < 12; j++) { y[2 * j] = h2fma(y[2 * j], lo2(r0), hi2(r0)); y[2 * j + 1] = h2fma(y[2 * j + 1], lo2(r1), hi2(r1)); }
  const uint32_t ma = swz(r, t), mb = fresh(ma ^ 32), u = t * kPlane;
  stsm4(ma + u, y); stsm4(mb + u, y + 4);
  stsm4(mb + (u + kChunk), y + 8); stsm4(ma + (u + kChunk), y + 12);
  stsm4(ma + (u + 2 * kChunk), y + 16); stsm4(mb + (u + 2 * kChunk), y + 20);
}

template <bool kAlways>
__device__ __forceinline__ void gate_open(uint32_t id) {
  if (kAlways) asm volatile("barrier.cta.arrive.aligned %0, 256;" ::"r"(id) : "memory");
  else asm volatile("{\n.reg .pred p;\nsetp.ne.u32 p, %0, 0;\n@p barrier.cta.arrive.aligned %0, 256;\n}" ::"r"(id) : "memory");
}

struct TState { uint32_t z0[24], z1[24], mu, bad; float ie, mm, mz, qq; };
template <bool kDirect>
__device__ __forceinline__ void temporal(TState& S, uint64_t da, const Tile& T, const TPar& P, bool scaled, uint32_t lane, uint32_t& lst) {
  uint32_t (&z0)[24] = S.z0, (&z1)[24] = S.z1;
  const uint32_t c = lane;
  const uint32_t a0 = T.a + lane * 16 + (lane >= 4 * T.n ? T.next : 0);
  uint32_t q0[26], q1[24], v0[24], w1[26], nn = 0, ng = 0, ca0 = 0, ca1 = 0;
  uint32_t* const v1 = w1 + 2;
  float ie = 1.f, mm = 0.f;
  bool tiny = false;
  if (kDirect) {
    uint32_t x[48];
    load_rows(x, x + 12, T.ring, a0, 0);
    load_rows(x + 24, x + 36, T.ring, a0, 2);
    to_half(z0, x);
    gemm<0, 0, kAtChunk>(q0, z0, da);
    sfence(lst);
    to_half(z1, x + 24);
    const uint32_t n0 = sumsq2<false>(z0), n1 = sumsq2<false>(z1);
    nn = fresh(sel(c & 2, n1, n0)); ng = shfl_x(sel(c & 2, n0, n1), 2);
    pin<24>(z1); sfence(lst);
  } else {
    float e[4], m[4];
    load_general(z0, T.ring, a0, 0, e[0], e[1], m[0], m[1]);
    pin<24>(z0); sfence(lst);
    load_general(z1, T.ring, a0, 2, e[2], e[3], m[2], m[3]);
    ie = sel4(c, e[0], e[1], e[2], e[3]);
    mm = sel4(c, m[0], m[1], m[2], m[3]);
    tiny = __any_sync(0xffffffffu, ie * P.kt > 400.f);
    if (tiny) {
      float u = 0.f;
#pragma unroll
      for (int r = 0; r < 4; r++) {
        float t = 0.f;
#pragma unroll
        for (int j = 0; j < 12; j++) { const float2 f = unpack_h2((r & 2 ? z1 : z0)[2 * j + (r & 1)]); t = fmaf(f.x, f.x, fmaf(f.y, f.y, t)); }
        u = fmaxf(u, quad_sum(t));
      }
      const float t = fminf(ie, 9.8f * rsq_fast(fmaxf(u, 2e-7f)) * rcp_fast(fresh(P.kt)));
      const uint32_t a = pack_h2(__fdividef(t, ie), 0.f);
      ca0 = __byte_perm(shfl_q(a, 0), shfl_q(a, 1), 0x5410); ca1 = __byte_perm(shfl_q(a, 2), shfl_q(a, 3), 0x5410);
      ie = t;
    }
    gemm<0, 0, kAtChunk>(q0, z0, da);
  }
  uint32_t f[4], k0[2], k1[2], sk[2];
  wg_wait(); pin<26>(q0);
  gemm<0, 0, kAtChunk>(q1, z1, da);
  gate_open<kDirect>(T.gate);
  sfence(lst);
  if (kDirect) { nn = h2add(nn, ng); ng = shfl_x(nn, 1); sfence(lst); }
  scores2(q0, z0, z1, f);
  const uint32_t nu0 = fresh(__byte_perm(q0[24], q0[25], 0x7632)), m01 = fresh(sel(c & 1, q0[25], q0[24]));
  Xch xc = pair_send(f, f + 2, c, 1);
  sfence(lst);
  wg_wait(); pin<24>(q1);
  gemm<0, kOffWt - 512, kAtChunk>(w1, z1, da);
  sfence(lst);
  pair_recv(k0, xc);
  float e2 = 0.f, lim = 0.f;
  if (kDirect) {
    nn = h2add(nn, ng);
    e2 = fresh(fmaf(low_f(sel(c & 1, nn >> 16, nn)), 1.f / 96.f, 1e-5f));
    lim = fresh(e2 <= 4.f ? fmaxf(0.5f * e2, 4e-4f) : __uint_as_float(0x7fffffffu));
  }
  scores2(q1, z0, z1, f);
  xc = pair_send(f, f + 2, c, 1);
  pin<2>(k0); sfence(lst);
  wg_wait(); pin<26>(w1);
  float mz = 0.f, d2 = 0.f;
  if (kDirect) {
    mz = low_f(sel(c & 2, sel(c & 1, w1[1], w1[0]), m01));
    d2 = fmaf(-mz, mz, e2);
    asm volatile("{\n.reg .pred p;\nsetp.lt.s32 p, %3, %4;\nsetp.ltu.and.f32 p, %1, %2, p;\n@p st.volatile.shared.f32 [%0], %2;\n}" ::"r"(T.flag), "f"(d2),
                 "f"(lim), "r"(lane), "r"(T.live) : "memory");
  }
  gemm<0, kOffWt, kAtChunk>(v0, z0, da);
  sfence(lst);
  uint32_t cw[8], mu;
  {
    uint32_t rc = 0, r0 = 0, r1 = 0;
    if (kDirect) {
      const float r = rsq_fast(d2);
      rc = pack_h2(r, r);
      r0 = __byte_perm(shfl_q(rc, 0), shfl_q(rc, 1), 0x5410); r1 = __byte_perm(shfl_q(rc, 2), shfl_q(rc, 3), 0x5410);
    }
    pair_recv(k1, xc);
    pair_recv(sk, pair_send(k0, k1, c, 2));
    if (kDirect) { sk[0] = h2mul(sk[0], r0); sk[1] = h2mul(sk[1], r1); }
    uint32_t mx = h2max(sk[0], sk[1]);
    mx = h2max(lo2(mx), hi2(mx));
    if (kDirect) {
      const uint32_t nm = h2mul(h2neg(mx), rc);
      sk[0] = h2fma(sk[0], rc, nm); sk[1] = h2fma(sk[1], rc, nm);
    } else {
      sk[0] = h2sub(sk[0], mx); sk[1] = h2sub(sk[1], mx);
      if (scaled) {
        const uint32_t cs = score_scale(&g_par.cS_t);
        sk[0] = h2mul(sk[0], cs); sk[1] = h2mul(sk[1], cs);
      }
    }
    sk[0] = h2ex2(sk[0]); sk[1] = h2ex2(sk[1]);
    const uint32_t sm = h2add(sk[0], sk[1]);
    const float iv = (kDirect ? P.kt : P.kt * ie) * rcp_fast(low_f(h2add(lo2(sm), hi2(sm))));
    const uint32_t inv = pack_h2(iv, iv);
    if (kDirect) { sk[0] = h2mul(sk[0], r0); sk[1] = h2mul(sk[1], r1); }
    sk[0] = h2mul(sk[0], inv); sk[1] = h2mul(sk[1], inv);
#pragma unroll
    for (int i = 0; i < 4; i++) { cw[2 * i] = shfl_q(sk[0], i); cw[2 * i + 1] = shfl_q(sk[1], i); }
    mu = h2fma(sk[1], __byte_perm(w1[0], w1[1], 0x7632), h2mul(sk[0], nu0));
    mu = h2add(lo2(mu), hi2(mu));
  }
  uint32_t bad = 0;
  if (kDirect) {
    mix2(z1, v1, cw[5], cw[7]);
    sfence(lst);
    wg_wait(); pin<24>(v0);
    mix2(z1, v0, cw[4], cw[6]);
    sfence(lst);
    bad = lds32(T.flag);
  } else {
    wg_wait(); pin<24>(v0);
    if (tiny) {
#pragma unroll
      for (int j = 0; j < 12; j++) {
        z0[2 * j] = h2mul(z0[2 * j], lo2(ca0)); z0[2 * j + 1] = h2mul(z0[2 * j + 1], hi2(ca0));
        z1[2 * j] = h2mul(z1[2 * j], lo2(ca1)); z1[2 * j + 1] = h2mul(z1[2 * j + 1], hi2(ca1));
      }
    }
    mix2(z1, v1, cw[5], cw[7]);
    mix2(z1, v0, cw[4], cw[6]);
  }
  mix2(z0, v1, cw[1], cw[3]);
  mix2(z0, v0, cw[0], cw[2]);
  S.qq = row_sumsq<false>(z0, z1, c);
  S.mu = mu; S.bad = bad; S.ie = ie; S.mm = mm; S.mz = mz;
}
__device__ __forceinline__ bool irregular(const TState& S, const Tile& T, uint32_t lane) {
  return __any_sync(0xffffffffu, (!(S.qq < 65000.f) & ((int)lane < T.live)) | (S.bad != 0));
}
__device__ __forceinline__ void resum(TState& S, uint32_t lane) {
  const float q2 = row_sumsq<true>(S.z0, S.z1, lane) * 65536.f;
  S.qq = S.qq < 65000.f ? S.qq : q2;
}
template <bool kDirect>
__device__ __forceinline__ void temporal_out(TState& S, const Tile& T, const TPar& P, uint32_t lane, uint32_t lst) {
  uint32_t (&z0)[24] = S.z0, (&z1)[24] = S.z1;
  const uint32_t mu = S.mu;
  const float ie = S.ie, mz = S.mz, qq = S.qq;
  float mm = S.mm;
  const float rf = kDirect ? rsq_fast(fmaxf(fmaf(-mz, mz, fmaf(qq, 1.f / 96.f, 1e-5f)), 1e-5f)) : rsq_fast(fmaf(qq, 1.f / 96.f, 1e-5f * ie * ie));
  const uint32_t rn = pack_h2_sat(rf, -mz * rf);
  uint32_t rr[4];
#pragma unroll
  for (int i = 0; i < 4; i++) rr[i] = shfl_q(rn, i);
  lane = fresh(lane);
  const uint32_t ma = fresh(T.ring + T.a) + lst + ((lane & 7) >= T.n ? T.next : 0);
  norm_store(z0, rr[0], rr[1], ma, 0);
  const float2 rm = unpack_h2(rn);
  const float sg = rcp_fast(kDirect ? rm.x : rm.x * ie);
  mm = kDirect ? fmaf(-rm.y, sg, low_f(mu)) : fmaf(low_f(mu) * rm.x, sg, mm);
  const bool ok = (sg >= P.sgmin) & (fmaf(sg, 9.8f, fabsf(mm)) < P.outmax);
  asm volatile("{\n.reg .pred p;\nsetp.lt.s32 p, %2, %3;\n@p st.shared.b32 [%0], %1;\n}" ::"r"(
                   T.stat + fresh((lane & 3) * (kSlot - 1) + lane + (lane >= 4 * T.n ? T.wrap : 0))),
               "r"(sel(ok, pack_h2(sg, mm), pack_bf2(sg, mm) | 0x8000u)), "r"(lane), "r"(T.live) : "memory");
  norm_store(z1, rr[2], rr[3], ma, 2);
}

__device__ __forceinline__ void run_T(uint32_t ring, uint64_t d0, uint64_t d1, uint32_t nfull, uint32_t nrem, bool helper, int wg, int wp, uint32_t lane,
                                      const TPar& P, bool scaled, uint32_t pdir) {
  uint32_t lst = (lane & 7) * 64 + (lane & 8) * (kPlane / 8) + (lane & 16);
  uint32_t p0 = 32 * (wg & 1) + (helper ? 0 : 64) + 8 * wp;
  uint32_t npx = 49 * nfull, pstop = npx - 6 * 49 + 8 * wp;
  if (helper) pstop = 0;
  uint32_t pgap = 0;
  Tile T;
  T.ring = ring;
  T.flag = ring + wg * kSlot + kFlag;
  T.gate = wg == 3 ? 6 : 5 + wg;
  while (true) {
    const uint32_t iw = (p0 * 21400u) >> 20, ow = p0 - 49 * iw;
    const uint32_t slot = ring + (iw & 3) * kSlot, dn = (iw & 3) == 3 ? -3 * kSlot : kSlot;
    asm volatile("{\n.reg .pred p;\nsetp.eq.u32 p, %1, 0;\n@p barrier.cta.sync.aligned %0, 256;\n}" ::"r"(6 - (wg & 1)), "r"((uint32_t)helper) : "memory");
    mbar_wait(slot + kFull, iw >> 2);
    if (ow > 41) mbar_wait(slot + dn + kFull, (iw + 1) >> 2);
    T.a = (iw & 3) * kSlot + ow * 64; T.next = dn - kPlane; T.n = 49 - ow;
    T.live = 4 * (npx - p0);
    T.stat = ring + kXBytes + (p0 - 196 * (iw >> 2)) * 4; T.wrap = (iw & 3) == 3 ? -784 : 0;
    lane = fresh(lane);
    {
      TState S;
      Tile G = T;
      if (p0 >= pdir) {
        temporal<true>(S, d0, T, P, false, lane, lst);
        if (irregular(S, T, lane)) {
          if (__any_sync(0xffffffffu, S.bad != 0)) goto redo;
          resum(S, lane);
        }
        temporal_out<true>(S, T, P, lane, lst);
        goto stored;
      redo:
        asm volatile("barrier.cta.sync.aligned %0, 128;" ::"r"(wg + 1) : "memory");
        asm volatile("st.shared.b32 [%0], %1;\nfence.acq_rel.cta;" ::"r"(T.flag), "r"(0) : "memory");
        G.gate = 0;
        pgap = p0 == pdir ? 4 * pgap + 64 : 0;
        pdir = p0 + 64 + pgap;
      }
      temporal<false>(S, d1, G, P, scaled, lane, lst);
      if (irregular(S, T, lane)) resum(S, lane);
      temporal_out<false>(S, T, P, lane, lst);
    }
  stored:
    const uint32_t pn = __shfl_sync(0xffffffffu, p0 + 64, 0);
    bool last = false;
    if (pn >= pstop) {
      if (helper) last = true;
      else if (pstop < npx - 4 * 49) {
        if (((wg & 1) | wp | lane) == 0) {
          const uint32_t nb = gridDim.x, nwh = min(max((int)(2 * nrem - nb), (int)(nrem / 2)), nrem);
          const uint32_t r = atomicAdd(&g_par.ticket, 1u), j = r - nwh;
          sts32(ring + kExtra, r < nwh ? (nfull * nb + r) * 4 + 3 : j < 2 * (nrem - nwh) ? (nfull * nb + nwh + (j >> 1)) * 4 + 1 + (j & 1) : 0);
        }
        __syncwarp();
        pstop = npx - 2 * 49 + 8 * wp;
      } else if (pstop < npx) {
        if (__shfl_sync(0xffffffffu, lds32(ring + kExtra), 0)) npx += 49;
        pstop = npx + 8 * wp;
      } else last = true;
    }
    asm volatile("fence.proxy.async.shared::cta;" ::: "memory");
    __syncwarp();
    mbar_arrive(slot + kDone + (lane >= 4 * T.n ? dn : 0), lane & 3);
    __syncwarp();
    if (last) break;
    p0 = pn;
  }
}

struct Frame {
  bool light;
  uint32_t sta;
  uint32_t oo;
  uint32_t e0, e1;
};
__device__ __forceinline__ uint32_t frame_init(Frame& F, uint32_t ring, uint32_t t, int wp, int lane) {
  wp = (wp + t) & 3;
  F.light = wp == 3;
  F.sta = ring + t * kSlot + kXBytes + 64 * wp;
  const uint32_t r = 16 * wp + (lane >> 2);
  F.oo = ((r / 7) * (kW - 7) + r) * 192u + (lane & 3) * 16 + (((((r + 8) / 7 - r / 7) * (kW - 7) + 8) * 3u) << 20);
  F.e0 = F.e1 = 0x8000u;
  const uint32_t am = t * kPlane + wp * 1024 + ((lane * 65) & 0x3d0);
  return F.light && (lane & 15) ? kZero : am ^ ((am >> 3) & 0x30);
}
template <bool F>
__device__ __forceinline__ void load_frame(uint32_t (&v)[24], uint32_t ma, uint32_t slot, uint32_t& tid) {
  const uint32_t st = ma < kXBytes ? kChunk : 0, mb = ma ^ 32;
  uint32_t a[6] = {ma, mb, mb + st, ma + st, ma + 2 * st, mb + 2 * st};
  pin<6>(a);
  if (F) sfence(tid);
#pragma unroll
  for (int k = 0; k < 6; k++) ldsm4(v + 4 * k, slot + a[k]);
}
__device__ __forceinline__ uint32_t load_stats(Frame& F, uint32_t ia, uint32_t tid) {
  const uint32_t a = fresh(tid & (F.light ? 0 : 0x1c)), u = F.sta + ia * 196;
  F.e0 = lds32(a + u);
  F.e1 = lds32(a + fresh(u + (F.light ? 0 : 32)));
  return a;
}
__device__ __forceinline__ uint32_t is_wide(const Frame& F) {
  uint32_t r;
  asm volatile("{\n.reg .pred p;\n.reg .b32 t;\nlop3.b32 t, %1, %2, 0x8000, 0xa8;\nsetp.ne.u32 p, t, 0;\nvote.sync.ballot.b32 %0, p, 0xffffffff;\n}"
               : "=r"(r) : "r"(F.e0), "r"(F.e1));
  return r;
}
template <int OFF>
__device__ __forceinline__ void gemm_u(uint32_t (&u)[24], const uint32_t* s, uint64_t db) {
  constexpr uint32_t kMN = (((kChunk >> 4) - 1) << 16) + OFF / 16;
  asm volatile("" : "+l"(db));
  wg_fence();
  wgmma<2, 1>(u, s, db + kMN); wgmma<1, 1>(u, s + 4, db + kMN + 64); wgmma<1, 1>(u, s + 8, db + kMN + 128); wgmma<1, 1>(u, s + 12, db + kMN + 192);
  wg_commit();
}
__device__ __forceinline__ uint32_t key48(uint32_t (&s)[16], uint32_t tid) {
  return fresh(sel(tid & 3, 0xfc00fc00u, __byte_perm(s[12], s[13], 0x5410)));
}
__device__ __forceinline__ uint32_t amax3(uint32_t a, uint32_t b, uint32_t c) {
  return as_u(__hmax2(__hmax2(__habs2(as_h2(a)), __habs2(as_h2(b))), __habs2(as_h2(c))));
}
struct Quad { uint32_t v[4]; };
__device__ __forceinline__ Quad soft_exp(uint32_t (&s)[16], uint32_t& t, uint32_t (&v)[24], const Frame& F, float2& e) {
  const uint32_t am = h2max(h2max(h2max(amax3(s[0], s[1], s[2]), amax3(s[3], s[4], s[5])), amax3(s[6], s[7], s[8])), h2max(amax3(s[9], s[10], s[11]), t));
  e = make_float2(low_f(F.e0), low_f(F.e1));
  uint32_t rare, sp[4];
#pragma unroll
  for (int j = 0; j < 4; j++) sp[j] = fresh(h2ex2(s[j]));
  asm("{\n.reg .pred p, q;\n.reg .b32 t;\nlop3.b32 t, %2, %3, 0x8000, 0xa8;\nsetp.eq.u32 q, t, 0;\nmov.b32 t, 0x49004900;\n"
      "setp.le.and.f16x2 p|q, %1, t, q;\nand.pred p, p, q;\nselp.b32 %0, 0, 1, p;\n}" : "=r"(rare) : "r"(am), "r"(F.e0), "r"(F.e1));
  if (__any_sync(0xffffffffu, rare)) {
    const uint32_t x0 = h2max(h2max(h2max(s[0], s[2]), h2max(s[4], s[6])), h2max(s[8], s[10]));
    const uint32_t x1 = h2max(h2max(h2max(s[1], s[3]), h2max(s[5], s[7])), h2max(s[9], s[11]));
    uint32_t mx = h2max(h2max(__byte_perm(x0, x1, 0x5410), __byte_perm(x0, x1, 0x7632)), t);
    mx = h2max(mx, shfl_x(mx, 1));
    mx = h2max(mx, shfl_x(mx, 2));
#pragma unroll
    for (int j = 0; j < 6; j++) { s[2 * j] = h2sub(s[2 * j], lo2(mx)); s[2 * j + 1] = h2sub(s[2 * j + 1], hi2(mx)); }
    t = h2sub(t, mx);
    if (is_wide(F)) {
      const uint32_t cs = score_scale(&g_par.cS_s);
#pragma unroll
      for (int j = 0; j < 12; j++) s[j] = h2mul(s[j], cs);
      t = h2mul(t, cs);
      const float s0 = stat_f32(F.e0).x, s1 = stat_f32(F.e1).x;
      const float kb = __ldcg(&g_par.kb), ik = rcp_fast(__ldcg(&g_par.kappa));
      e.x = fmaxf(s0, kb); e.y = fmaxf(s1, kb);
      const uint32_t aw = pack_h2(__fdividef(s0, e.x), __fdividef(s1, e.y));
      e.x *= ik; e.y *= ik;
#pragma unroll
      for (int j = 0; j < 12; j++) { v[2 * j] = h2mul(v[2 * j], lo2(aw)); v[2 * j + 1] = h2mul(v[2 * j + 1], hi2(aw)); }
    }
#pragma unroll
    for (int j = 0; j < 4; j++) sp[j] = h2ex2(s[j]);
  }
#pragma unroll
  for (int j = 0; j < 12; j++) s[j] = j < 4 ? sp[j] : h2ex2(s[j]);
  t = h2ex2(t);
  Quad q;
  q.v[0] = h2add(t, fold_add(h2add(h2add(h2add(s[0], s[2]), h2add(s[4], s[6])), h2add(s[8], s[10])),
                             h2add(h2add(h2add(s[1], s[3]), h2add(s[5], s[7])), h2add(s[9], s[11]))));
#pragma unroll
  for (int i = 1; i < 4; i++) q.v[i] = shfl_x(q.v[0], i);
  return q;
}
__device__ __forceinline__ void soft_norm(uint32_t (&s)[16], uint32_t& t, const Quad& q, const Frame& F, float2 e, uint32_t tid) {
  const float2 d = unpack_h2(h2add(h2add(q.v[0], q.v[1]), h2add(q.v[2], q.v[3])));
  const uint32_t cb = pack_h2(rcp_fast(d.x * e.x), rcp_fast(d.y * e.y)) & (sel(tid & 28, 0u, 0xffffu) | fresh(F.light ? 0u : 0xffffffffu));
#pragma unroll
  for (int j = 0; j < 6; j++) { s[2 * j] = h2mul(s[2 * j], lo2(cb)); s[2 * j + 1] = h2mul(s[2 * j + 1], hi2(cb)); }
  t = fresh(h2mul(t, cb));
  pin<12>(s);
}
__device__ __forceinline__ void soft_tail(uint32_t (&s)[16], uint32_t t) {
  s[12] = t & 0xffffu; s[13] = t >> 16;
  asm volatile("mov.b32 %0, 0;\nmov.b32 %1, 0;" : "=r"(s[14]), "=r"(s[15]));
}
template <int H>
__device__ __forceinline__ uint8_t* row_ptr(const Frame& F, uint8_t* o) {
  const uint32_t oo = fresh(F.oo);
  if (H) asm volatile("mad.wide.u32 %0, %1, 64, %0;" : "+l"(o) : "r"(oo >> 20));
  else { o += oo & 0xfffffu; asm volatile("" : "+l"(o)); }
  return o;
}
template <int H>
__device__ __forceinline__ void affine(uint32_t* r, const uint32_t (&v)[24], const Frame& F) {
  const uint32_t e = H ? F.e1 : F.e0;
#pragma unroll
  for (int j = 0; j < 12; j++) r[j] = h2fma(v[2 * j + H], lo2(e), hi2(e));
  pin<12>(r);
}
template <int H>
__device__ __forceinline__ void finish(uint32_t* r, const Frame& F, uint8_t*& o, uint32_t off, uint32_t a, uint32_t m, uint32_t& tid) {
  o = row_ptr<H>(F, o);
#pragma unroll
  for (int j = 0; j < 12; j += 2) { const float2 f = unpack_h2(r[j]), g = unpack_h2(r[j + 1]); r[j] = pack_bf2(f.x, g.x); r[j + 1] = pack_bf2(f.y, g.y); }
  pin<12>(r);
  sfence(tid);
  stg3(o, r, off | (fresh(a) & m));
}
__device__ __forceinline__ void finish_wide(const uint32_t (&v)[24], const Frame& F, uint8_t* o, uint32_t tid) {
  const float kb = __ldcg(&g_par.kb);
#pragma unroll
  for (int h = 0; h < 2; h++) {
    const float2 z = stat_f32(h ? F.e1 : F.e0);
    const float w = fmaxf(z.x, kb);
    uint32_t r[12];
#pragma unroll
    for (int j = 0; j < 12; j += 2) {
      const float2 f = unpack_h2(v[2 * j + h]), g = unpack_h2(v[2 * j + 2 + h]);
      r[j] = pack_bf2(fmaf(f.x, w, z.y), fmaf(g.x, w, z.y)); r[j + 1] = pack_bf2(fmaf(f.y, w, z.y), fmaf(g.y, w, z.y));
    }
    o = h ? row_ptr<1>(F, o) : row_ptr<0>(F, o);
    stg3(o, r, F.light ? (h ? 1 : tid & 28) : 0);
  }
}
__device__ __forceinline__ uint32_t window_ahead(uint32_t ring, uint32_t i, uint32_t nfull, uint32_t w) {
  return i + 4 < nfull ? w + 4 * gridDim.x : i + 4 == nfull ? lds32(ring + kExtra) >> 2 : 0;
}

__device__ __forceinline__ void run_S(uint32_t ring, uint64_t d0, uint64_t d1, uint32_t frame, uint32_t nfull, uint32_t i0, uint32_t i1, uint32_t w, int sg, int wp, int lane,
                                      const CUtensorMap* tm, uint8_t* __restrict__ out) {
  Frame A, B;
  uint32_t tid = lane + (frame_init(A, ring, 2 * sg, wp, lane) << 4) + (frame_init(B, ring, 2 * sg + 1, wp, lane) << 16);
  uint32_t va[24], vb[24], x[24], sa[16], sc[16], r0[12], r1[12], ta, tb;
  Quad rs;
  float2 e;
#pragma unroll
  for (int j = 0; j < 24; j++) { vb[j] = 0; x[j] = 0; }
  out += sg * 2 * frame;
  uint8_t *ob = out, *o;
  const uint64_t dr = d0 + (uint32_t)(kWBytes / 16 + sg * (2 * kPlane / 16));
  uint32_t i = i0, slot = ring + (i & 3) * kSlot;
  mbar_wait(slot + kDone, i >> 2);
  load_frame<false>(va, (tid >> 4) & 0xfff0u, slot, tid);
  do {
    const uint32_t ia = i & 3;
    gemm<2, kOffAs, 6144>(x, va, d0);
    const uint32_t wb = is_wide(B);
    if (wb && i != i0) finish_wide(vb, B, ob + frame, tid);
    affine<0>(r0, vb, B); affine<1>(r1, vb, B);
    load_frame<true>(vb, (tid >> 16) & 0xfff0u, slot, tid);
    const uint32_t g4 = load_stats(A, ia, tid);
    uint64_t dp = dr + ia * (kSlot / 16);
    asm volatile("" : "+l"(dp));
    o = ob + frame;
    finish<0>(r0, B, o, wb, g4, B.light ? 28 : 0, tid);
    sfence(tid);
    wg_wait(); pin<24>(x);
    gemm<0, 0, kChunk>(sa, x, dp);
    if (!B.light) finish<1>(r1, B, o, wb, 0, 0, tid);
    else if (sg == 0) {
      if ((tid & 31) == 0) {
        const uint32_t wn = window_ahead(ring, i, nfull, w);
        if (wn) tma_prefetch_win(tm, wn);
      }
      __syncwarp();
    }
    ob = out + (size_t)((((w * 57457u) >> 22) * (7 * kW - 7 * kNWX) + w * 7) * 192u);
    sfence(tid);
    wg_wait(); pin<14>(sa);
    gemm<2, kOffAs, 6144>(x, vb, d1);
    ta = key48(sa, tid);
    rs = soft_exp(sa, ta, va, A, e);
    sfence(tid);
    wg_wait(); pin<24>(x);
    gemm<0, kPlane, kChunk>(sc, x, dp);
    sfence(tid);
    load_stats(B, ia, tid);
    soft_norm(sa, ta, rs, A, e, tid);
    sfence(tid);
    wg_wait(); pin<14>(sc);
    tb = key48(sc, tid);
    sfence(tid);
    soft_tail(sa, ta);
    gemm_u<0>(x, sa, dp);
    rs = soft_exp(sc, tb, vb, B, e);
    sfence(tid);
    wg_wait(); pin<24>(x);
    gemm<1, kOffWs, 6144>(va, x, d0);
    sfence(tid);
    soft_norm(sc, tb, rs, B, e, tid);
    soft_tail(sc, tb);
    const uint32_t wa = is_wide(A);
    sfence(tid);
    wg_wait(); pin<24>(va);
    gemm_u<kPlane>(x, sc, dp);
    sfence(tid);
    const uint32_t sn = ring + ((i + 1) & 3) * kSlot;
    const bool slow = mbar_pending_or(sn + kDone, (i + 1) >> 2, wa | A.light);
    affine<0>(r0, va, A);
    o = ob;
    finish<0>(r0, A, o, wa, tid, A.light ? 28 : 0, tid);
    sfence(tid);
    wg_wait(); pin<24>(x);
    gemm<1, kOffWs, 6144>(vb, x, d1);
    sfence(tid);
    affine<1>(r1, va, A);
    if (slow) {
      if (A.light) {
        if ((tid & 31) == 0) {
          uint32_t old;
          asm volatile("atom.relaxed.cta.shared::cta.inc.u32 %0, [%1], 1;" : "=r"(old) : "r"(slot + kRel) : "memory");
          if (old) {
            const uint32_t wn = window_ahead(ring, i, nfull, w);
            if (wn) tma_load_win(slot, tm, wn);
            else mbar_arrive(slot + kFull);
          }
        }
        __syncwarp();
      }
      if (wa) finish_wide(va, A, ob, tid);
      if (i + 1 < i1) mbar_wait(sn + kDone, (i + 1) >> 2);
    }
    const uint32_t la = (tid >> 4) & 0xfff0u;
    load_frame<false>(va, la, sn, tid);
    if (!A.light) finish<1>(r1, A, o, wa, la, 0x4000, tid);
    wg_wait(); pin<24>(vb);
    launder<24>(vb);
    launder<24>(va);
    slot = sn; w += gridDim.x;
  } while (++i < i1);
  const uint32_t wb = is_wide(B);
  if (wb) finish_wide(vb, B, ob + frame, tid);
  o = ob + frame;
  affine<0>(r0, vb, B); finish<0>(r0, B, o, wb, tid, B.light ? 28 : 0, tid);
  affine<1>(r1, vb, B); finish<1>(r1, B, o, B.light | wb, 0, 0, tid);
}

struct Maps { CUtensorMap load, prefetch; };
__global__ void __launch_bounds__(512, 1) swin_main(const __grid_constant__ Maps tms, uint8_t* __restrict__ out, const uint64_t d0,
                                                    const uint64_t d1, const uint32_t frame) {
  extern __shared__ __align__(1024) uint8_t smem[];
  const CUtensorMap& tm = tms.load;
  const uint32_t sb = smem_u32(smem), ring = sb + kWBytes;
  const int tid = threadIdx.x;
  const int wg = __shfl_sync(0xffffffffu, tid >> 7, 0);
  const int wp = __shfl_sync(0xffffffffu, (tid >> 5) & 3, 0);
  const int lane = tid & 31;
  const uint32_t b = blockIdx.x, nb = gridDim.x;
  const uint32_t nfull = kNWIN / nb, nrem = kNWIN - nfull * nb;
  if (tid == 0) {
    if (sb != 1024 || nfull > 700 || nfull < 12) __trap();
#pragma unroll
    for (int i = 0; i < 4; i++) {
      mbar_init(ring + i * kSlot + kFull, 1);
      mbar_init(ring + i * kSlot + kDone, 49);
      sts32(ring + i * kSlot + kRel, 0); sts32(ring + i * kSlot + kFlag, 0);
    }
    asm volatile("fence.mbarrier_init.release.cluster;" ::: "memory");
    for (int i = 0; i < 2; i++) tma_load_win(ring + i * kSlot, &tm, b + i * nb);
  }
  __syncwarp();
  if (wg == 1 || wg == 2)
    asm volatile("st.shared.v4.b32 [%0], {%1,%1,%1,%1};" ::"r"(ring + ((tid - 128) >> 6) * kSlot + kXBytes + (tid & 63) * 16), "r"(0) : "memory");
  __syncthreads();
  asm volatile("griddepcontrol.wait;" ::: "memory");
#pragma unroll
  for (int q = 0; q < kWBytes / 16 / 512; q++)
    asm volatile("cp.async.cg.shared.global [%0], [%1], 16;" ::"r"(sb + (tid + q * 512) * 16), "l"(g_wimg + tid + q * 512) : "memory");
  if (wg == 0 && wp < 3) {
    static_assert(kWBytes / 16 == 9 * 512 + 96, "weight copy split");
    const int e = tid + 9 * 512;
    asm volatile("cp.async.cg.shared.global [%0], [%1], 16;" ::"r"(sb + e * 16), "l"(g_wimg + e) : "memory");
  }
  const float4 p0 = __ldcg(reinterpret_cast<const float4*>(&g_par));
  const float kb = __ldcg(&g_par.kb);
  TPar P;
  P.kt = p0.z;
  P.sgmin = p0.y != 1.f || p0.w != 1.f ? 1e30f : fmaxf(0.0045f, kb * 0.011f);
  P.outmax = fmaf(kb, -627.2f, 60000.f);
  const bool scaled = __any_sync(0xffffffffu, p0.x != 1.f);
  const uint32_t pdir = __ballot_sync(0xffffffffu, scaled || !(P.kt <= 256.f));
  asm volatile("cp.async.wait_all;\nfence.proxy.async.shared::cta;" ::: "memory");
  __syncthreads();
  if (tid == 128) for (int i = 2; i < 4; i++) tma_load_win(ring + i * kSlot, &tm, b + i * nb);
  __syncwarp();
  const bool isT = wg < 2;
  run_T(ring, d0, d1, nfull, nrem, !isT, wg, wp, lane, P, scaled, pdir);
  const uint32_t ex = isT ? __shfl_sync(0xffffffffu, lds32(ring + kExtra), 0) : 3;
  if ((ex >> (wg & 1)) & 1) run_S(ring, d0, d1, frame, nfull, isT ? nfull : 0, nfull + isT, isT ? ex >> 2 : b, wg & 1, wp, lane, &tm, out);
}

__device__ __forceinline__ int ch_pos(int ch) { return 32 * (ch >> 5) + 16 * ((ch >> 2) & 1) + 8 * (ch & 1) + 2 * ((ch >> 3) & 3) + ((ch >> 1) & 1); }
__device__ __forceinline__ float pow2_ceil(float v) {
  return __uint_as_float((__float_as_uint(v) + 0x7fffffu) & 0x7f800000u);
}

constexpr int kPrepSplit = 12;
constexpr int kPrepThreads = 384;
__global__ void __launch_bounds__(kPrepThreads) swin_prep(const __nv_bfloat16* __restrict__ wqkv_t, const __nv_bfloat16* __restrict__ wo_t,
                                                          const __nv_bfloat16* __restrict__ wqkv_s, const __nv_bfloat16* __restrict__ wo_s) {
  asm volatile("griddepcontrol.launch_dependents;");
  __shared__ __align__(16) uint32_t raw[2][96][52];
  __shared__ __align__(16) uint32_t mu[3][52];
  __shared__ float nrm[12], nrm2[6], csum[6][9];
  const int mat = blockIdx.x / kPrepSplit, blk = blockIdx.x % kPrepSplit;
  const int tid = threadIdx.x, lane = tid & 31, warp = tid >> 5, g = lane >> 2, c = lane & 3;
  const __nv_bfloat16* wqkv = mat < 2 ? wqkv_t : wqkv_s;
  const __nv_bfloat16* wo = mat < 2 ? wo_t : wo_s;
  const bool isA = (mat & 1) == 0;
  {
    uint4 v[3], u[3];
#pragma unroll
    for (int q = 0; q < 3; q++) {
      const int e = tid + q * kPrepThreads, i = e / 12, c8 = (e % 12) * 8;
      v[q] = __ldg(reinterpret_cast<const uint4*>(wqkv + i * 288 + (isA ? 0 : 192) + c8));
      u[q] = __ldg(reinterpret_cast<const uint4*>(isA ? wqkv + i * 288 + 96 + c8 : wo + i * 96 + c8));
    }
#pragma unroll
    for (int q = 0; q < 3; q++) {
      const int e = tid + q * kPrepThreads, i = e / 12, c4 = (e % 12) * 4;
      *reinterpret_cast<uint4*>(&raw[0][i][c4]) = v[q];
      *reinterpret_cast<uint4*>(&raw[1][i][c4]) = u[q];
    }
  }
  __syncthreads();
  {
    const int m = warp / 6, cp = (warp % 6) * 8 + g;
    float s0 = 0.f, s1 = 0.f, q0 = 0.f, q1 = 0.f;
#pragma unroll
    for (int i = 0; i < 24; i++) {
      const uint32_t w = raw[m][4 * i + c][cp];
      const float lo = __uint_as_float(w << 16), hi = __uint_as_float(w & 0xffff0000u);
      s0 += lo; s1 += hi; q0 = fmaf(lo, lo, q0); q1 = fmaf(hi, hi, q1);
    }
    s0 = quad_sum(s0) * (1.f / 96.f); s1 = quad_sum(s1) * (1.f / 96.f); q0 = quad_sum(q0); q1 = quad_sum(q1);
    if (mat == 1 && m == 1) {
      float r0 = 0.f, r1 = 0.f;
#pragma unroll
      for (int i = 0; i < 12; i++) {
        const uint32_t w0 = raw[1][2 * cp][4 * i + c], w1 = raw[1][2 * cp + 1][4 * i + c];
        r0 += __uint_as_float(w0 << 16) + __uint_as_float(w0 & 0xffff0000u);
        r1 += __uint_as_float(w1 << 16) + __uint_as_float(w1 & 0xffff0000u);
      }
      r0 = quad_sum(r0) * (1.f / 96.f); r1 = quad_sum(r1) * (1.f / 96.f);
      s0 = r0; s1 = r1;
    }
    if (m == 1 && c == 0) {
      const uint32_t hi = mat == 3 ? 0u : pack_bf2(s0, s1);
      mu[0][cp] = hi;
      mu[1][cp] = mat == 3 ? 0u : pack_bf2(s0 - __uint_as_float(hi << 16), s1 - __uint_as_float(hi & 0xffff0000u));
      mu[2][cp] = 0u;
    }
    if (m == 0 || isA) {
      q0 = fmaxf(fmaf(-96.f * s0, s0, q0), 0.f) + q0 * 1e-6f;
      q1 = fmaxf(fmaf(-96.f * s1, s1, q1), 0.f) + q1 * 1e-6f;
    }
    const bool usemax = m == 1 && mat == 3;
    float t = usemax ? fmaxf(q0, q1) : q0 + q1;
#pragma unroll
    for (int o = 4; o < 32; o <<= 1) { const float z = __shfl_xor_sync(0xffffffffu, t, o); t = usemax ? fmaxf(t, z) : t + z; }
    if (lane == 0) nrm[warp] = t;
  }
  __syncthreads();
  if (warp >= 6) return;
  float d[4] = {0.f, 0.f, 0.f, 0.f}, e[4] = {0.f, 0.f, 0.f, 0.f}, v0, v1;
  {
    const uint32_t arow = smem_u32(&raw[0][16 * warp + (lane & 15)][(lane >> 4) * 4]);
    const uint32_t brow = isA ? smem_u32(&raw[1][blk * 8 + (lane & 7)][(lane >> 3) * 4]) : smem_u32(&raw[1][lane][blk * 4]);
    const uint32_t mrow = smem_u32(&mu[min(lane & 7, 2)][(lane >> 3) * 4]);
#pragma unroll
    for (int k2 = 0; k2 < 3; k2++) {
      uint32_t b[4], m[4];
      if (isA) ldsm4(b, brow + k2 * 64);
      else asm volatile("ldmatrix.sync.aligned.m8n8.x4.trans.shared.b16 {%0,%1,%2,%3}, [%4];"
                        : "=r"(b[0]), "=r"(b[1]), "=r"(b[2]), "=r"(b[3]) : "r"(brow + k2 * (32 * 208)) : "memory");
      ldsm4(m, mrow + k2 * 64);
#pragma unroll
      for (int hf = 0; hf < 2; hf++) {
        uint32_t a[4];
        ldsm4(a, arow + (2 * k2 + hf) * 32);
        asm volatile("mma.sync.aligned.m16n8k16.row.col.f32.bf16.bf16.f32 {%0,%1,%2,%3},{%4,%5,%6,%7},{%8,%9},{%0,%1,%2,%3};"
                     : "+f"(d[0]), "+f"(d[1]), "+f"(d[2]), "+f"(d[3])
                     : "r"(a[0]), "r"(a[1]), "r"(a[2]), "r"(a[3]), "r"(b[2 * hf]), "r"(b[2 * hf + 1]));
        asm volatile("mma.sync.aligned.m16n8k16.row.col.f32.bf16.bf16.f32 {%0,%1,%2,%3},{%4,%5,%6,%7},{%8,%9},{%0,%1,%2,%3};"
                     : "+f"(e[0]), "+f"(e[1]), "+f"(e[2]), "+f"(e[3])
                     : "r"(a[0]), "r"(a[1]), "r"(a[2]), "r"(a[3]), "r"(m[2 * hf]), "r"(m[2 * hf + 1]));
      }
    }
    v0 = __shfl_sync(0xffffffffu, e[0] + e[1], lane & ~3); v1 = __shfl_sync(0xffffffffu, e[2] + e[3], lane & ~3);
    d[0] -= v0; d[1] -= v0; d[2] -= v1; d[3] -= v1;
    float t0 = d[0] + d[2], t1 = d[1] + d[3], t2 = v0 + v1;
#pragma unroll
    for (int o = 4; o < 32; o <<= 1) {
      t0 += __shfl_xor_sync(0xffffffffu, t0, o); t1 += __shfl_xor_sync(0xffffffffu, t1, o); t2 += __shfl_xor_sync(0xffffffffu, t2, o);
    }
    if (g == 0) { csum[warp][2 * c] = t0; csum[warp][2 * c + 1] = t1; csum[warp][8] = t2; }
  }
  const float nl = nrm[0] + nrm[1] + nrm[2] + nrm[3] + nrm[4] + nrm[5];
  const float nr = mat == 3 ? fmaxf(fmaxf(fmaxf(nrm[6], nrm[7]), fmaxf(nrm[8], nrm[9])), fmaxf(nrm[10], nrm[11]))
                            : nrm[6] + nrm[7] + nrm[8] + nrm[9] + nrm[10] + nrm[11];
  const float bound = __fsqrt_rn(nl) * __fsqrt_rn(nr) * 1.01f;
  const float f = isA ? 0.14724448f : 1.f;
  float sc = pow2_ceil(fmaxf(bound * (isA ? 0.14724448f / 160.f : mat == 1 ? 1.f / 16.f : 1.f / 64.f), 1e-30f));
  if (isA) sc = fminf(fmaxf(sc, 1.f), 32768.f);
  if (mat == 3) {
    if (blk == 0 && tid == 0) { g_par.kb = sc; g_par.ticket = 0; }
    if (sc <= 1.f && sc >= 1.f / 1024.f) sc = 1.f;
  }
  const float mul = f * __uint_as_float(0x7f000000u - __float_as_uint(sc));
  if (blk == 0 && tid == 0) (mat == 0 ? g_par.cS_t : mat == 1 ? g_par.kt : mat == 2 ? g_par.cS_s : g_par.kappa) = sc;
  asm volatile("bar.sync 1, 192;" ::: "memory");
  float mean[2];
#pragma unroll
  for (int b = 0; b < 2; b++)
    mean[b] = (csum[0][2 * c + b] + csum[1][2 * c + b] + csum[2][2 * c + b] + csum[3][2 * c + b] + csum[4][2 * c + b] + csum[5][2 * c + b]) *
              (1.f / 96.f);
  uint8_t* img = reinterpret_cast<uint8_t*>(g_wimg) + (mat == 0 ? 0 : mat == 1 ? kOffWt : mat == 2 ? kOffAs : kOffWs);
  const float vmean = (csum[0][8] + csum[1][8] + csum[2][8] + csum[3][8] + csum[4][8] + csum[5][8]) * (1.f / 96.f);
  float q2 = 0.f;
#pragma unroll
  for (int q = 0; q < 4; q++) q2 = fmaf(d[q] - mean[q & 1], d[q] - mean[q & 1], q2);
#pragma unroll
  for (int o = 16; o; o >>= 1) q2 += __shfl_xor_sync(0xffffffffu, q2, o);
  if (lane == 0) nrm2[warp] = q2;
  asm volatile("bar.sync 1, 192;" ::: "memory");
  const float rms = __fsqrt_rn((nrm2[0] + nrm2[1] + nrm2[2] + nrm2[3] + nrm2[4] + nrm2[5]) * (1.f / 768.f)) * mul;
  const float big = 12582912.f * pow2_ceil(fmaxf(rms * (1.f / 256.f), 1e-30f));
  const float off = mat == 2 ? 1.5f * pow2_ceil(fmaxf(rms * 3.f, 1e-4f)) : 0.f;
#pragma unroll
  for (int q = 0; q < 4; q++) {
    const int kp = ch_pos(16 * warp + g + 8 * (q >> 1)), np = ch_pos(blk * 8 + 2 * c + (q & 1));
    const uint32_t ko = (kp >> 5) * (mat < 2 ? kAtChunk : 6144) + (kp & 31) * 2;
    uint32_t a = ko + np * 64;
    a ^= ((a >> 7) & 3) << 4;
    const float o = __fadd_rn(__fadd_rn((d[q] - mean[q & 1]) * mul, big), -big);
    *reinterpret_cast<__half*>(img + a) = __float2half_rn(o + off);
    if (mat == 1 && blk == 0) {
      a = (kp >> 5) * kAtChunk + (kp & 31) * 2 + (96 + 2 * c + (q & 1)) * 64;
      a ^= ((a >> 7) & 3) << 4;
      *reinterpret_cast<__half*>(reinterpret_cast<uint8_t*>(g_wimg) + a) = __float2half_rn((q & 1) ? ((q >> 1 ? v1 : v0) - vmean) * mul : 1.f / 96.f);
    }
  }
}

typedef CUresult (*EncodeFn)(CUtensorMap*, CUtensorMapDataType, cuuint32_t, void*, const cuuint64_t*, const cuuint64_t*,
                             const cuuint32_t*, const cuuint32_t*, CUtensorMapInterleave, CUtensorMapSwizzle,
                             CUtensorMapL2promotion, CUtensorMapFloatOOBfill);

}

extern "C" void kernel_launch(void* const* d_in, const int* in_sizes, int n_in, void* d_out, int out_size) {
  (void)in_sizes; (void)n_in; (void)out_size;
  static EncodeFn enc = nullptr;
  static int nsm = 0;
  if (!enc) {
    void* fn = nullptr;
    cudaDriverEntryPointQueryResult qr;
    cudaGetDriverEntryPoint("cuTensorMapEncodeTiled", &fn, cudaEnableDefault, &qr);
    enc = reinterpret_cast<EncodeFn>(fn);
    int dev = 0;
    cudaGetDevice(&dev);
    cudaDeviceGetAttribute(&nsm, cudaDevAttrMultiProcessorCount, dev);
    cudaFuncSetAttribute(swin_main, cudaFuncAttributeMaxDynamicSharedMemorySize, kSmemBytes);
  }
  Maps tms;
  CUtensorMap& tm = tms.load;
  const cuuint64_t dims[5] = {32, kW, kH, kT, 3};
  const cuuint64_t strides[4] = {192, 192ull * kW, 192ull * kW * kH, 64};
  const cuuint32_t box[5] = {32, 7, 7, 4, 3};
  const cuuint32_t es[5] = {1, 1, 1, 1, 1};
  enc(&tm, CU_TENSOR_MAP_DATA_TYPE_BFLOAT16, 5, d_in[0], dims, strides, box, es, CU_TENSOR_MAP_INTERLEAVE_NONE,
      CU_TENSOR_MAP_SWIZZLE_64B, CU_TENSOR_MAP_L2_PROMOTION_L2_128B, CU_TENSOR_MAP_FLOAT_OOB_FILL_NONE);

  const cuuint64_t dims2[3] = {24ull * kW, kH, kT};
  const cuuint64_t strides2[2] = {192ull * kW, 192ull * kW * kH};
  const cuuint32_t box2[3] = {168, 7, 4};
  enc(&tms.prefetch, CU_TENSOR_MAP_DATA_TYPE_UINT64, 3, d_in[0], dims2, strides2, box2, es, CU_TENSOR_MAP_INTERLEAVE_NONE,
      CU_TENSOR_MAP_SWIZZLE_NONE, CU_TENSOR_MAP_L2_PROMOTION_L2_128B, CU_TENSOR_MAP_FLOAT_OOB_FILL_NONE);

  cudaStream_t st = cudaStreamPerThread;
  swin_prep<<<4 * kPrepSplit, kPrepThreads, 0, st>>>(
      static_cast<const __nv_bfloat16*>(d_in[1]), static_cast<const __nv_bfloat16*>(d_in[2]),
      static_cast<const __nv_bfloat16*>(d_in[3]), static_cast<const __nv_bfloat16*>(d_in[4]));

  cudaLaunchConfig_t cfg = {};
  cfg.gridDim = dim3(nsm);
  cfg.blockDim = dim3(512);
  cfg.dynamicSmemBytes = kSmemBytes;
  cfg.stream = st;
  cudaLaunchAttribute at[1];
  at[0].id = cudaLaunchAttributeProgrammaticStreamSerialization;
  at[0].val.programmaticStreamSerializationAllowed = 1;
  cfg.attrs = at;
  cfg.numAttrs = 1;
  cudaLaunchKernelEx(&cfg, swin_main, tms, static_cast<uint8_t*>(d_out), mk_desc(1024), mk_desc(1024), (uint32_t)(kH * kW * 192));
}
```

```cpp
#include <cuda_runtime.h>
#include <cuda.h>
#include <cuda_bf16.h>
#include <cuda_fp16.h>
#include <stdint.h>

namespace {

constexpr int kH = 511, kW = 511, kT = 4;
constexpr int kNWX = 73, kNWIN = 73 * 73;
constexpr int kChunk = 12544;
constexpr int kPlane = 3136;
constexpr int kXBytes = 37632;
constexpr int kZero = kXBytes + 896, kFull = kXBytes + 1024, kDone = kFull + 8, kRel = kFull + 16, kFlag = kFull + 20, kExtra = kFull + 24,
              kWide = kFull + 28;
constexpr int kSlot = 38912;
constexpr int kWMat = 18432;
constexpr int kAtChunk = 200 * 64;
constexpr int kOffWt = 104 * 64;
constexpr int kOffAs = 3 * kAtChunk, kOffWs = kOffAs + kWMat;
constexpr int kWBytes = kOffWs + kWMat;
constexpr int kSmemBytes = kWBytes + 4 * kSlot;

struct Params {
  float cS_t, cS_s;
  float kt;
  float kappa;
  float kb;
  uint32_t ticket;
};

__device__ uint4 g_wimg[kWBytes / 16];
__device__ __align__(16) Params g_par;

__device__ __forceinline__ uint32_t smem_u32(const void* p) { return (uint32_t)__cvta_generic_to_shared(p); }
__device__ __forceinline__ void mbar_init(uint32_t a, int c) { asm volatile("mbarrier.init.shared::cta.b64 [%0], %1;" ::"r"(a), "r"(c)); }
__device__ __forceinline__ void mbar_expect(uint32_t a, int bytes) {
  asm volatile("mbarrier.arrive.expect_tx.shared::cta.b64 _, [%0], %1;" ::"r"(a), "r"(bytes) : "memory");
}
__device__ __forceinline__ void mbar_arrive(uint32_t a, uint32_t off = 0) {
  asm volatile("{\n.reg .pred p;\nsetp.eq.u32 p, %1, 0;\n@p mbarrier.arrive.shared::cta.b64 _, [%0];\n}" ::"r"(a), "r"(off) : "memory");
}
__device__ __forceinline__ void mbar_wait(uint32_t a, uint32_t par) {
  asm volatile(
      "{\n.reg .pred p;\n.reg .u32 n;\n"
      "mbarrier.try_wait.parity.shared::cta.b64 p, [%0], %1;\n"
      "@p bra.uni WDONE;\n"
      "mov.u32 n, 0;\n"
      "WLOOP:\n"
      "mbarrier.try_wait.parity.shared::cta.b64 p, [%0], %1;\n"
      "@p bra.uni WDONE;\n"
      "add.u32 n, n, 1;\n"
      "setp.lt.u32 p, n, 0x100000;\n"
      "@p bra.uni WLOOP;\n"
      "trap;\n"
      "WDONE:\n}" ::"r"(a), "r"(par & 1) : "memory");
}
template <int OFF>
__device__ __forceinline__ bool mbar_pending_or(uint32_t a, uint32_t par) {
  uint32_t r;
  asm volatile("{\n.reg .pred p;\n.reg .b32 t;\nmbarrier.test_wait.parity.shared::cta.b64 p, [%1], %2;\nld.shared.b32 t, [%1+%3];\n"
               "setp.ne.or.u32 p, t, 0, !p;\nvote.sync.any.pred p, p, 0xffffffff;\nselp.b32 %0, 1, 0, p;\n}"
               : "=r"(r) : "r"(a), "r"(par & 1), "n"(OFF) : "memory");
  return r;
}
__device__ __forceinline__ uint32_t lds32(uint32_t a) {
  uint32_t v; asm volatile("ld.shared.b32 %0, [%1];" : "=r"(v) : "r"(a) : "memory"); return v;
}
__device__ __forceinline__ void sts32(uint32_t a, uint32_t v) { asm volatile("st.shared.b32 [%0], %1;" ::"r"(a), "r"(v) : "memory"); }
__device__ __forceinline__ void tma_load_win(uint32_t slot, const CUtensorMap* m, uint32_t w) {
  const uint32_t wy = (w * 57457u) >> 22, wx = w - wy * kNWX;
  mbar_expect(slot + kFull, kXBytes);
  asm volatile(
      "cp.async.bulk.tensor.5d.shared::cluster.global.mbarrier::complete_tx::bytes [%0], [%1, {%3,%4,%5,%3,%3}], [%2];" ::"r"(slot),
      "l"(m), "r"(slot + kFull), "r"(0), "r"(wx * 7), "r"(wy * 7)
      : "memory");
}
__device__ __forceinline__ void tma_prefetch_win(const CUtensorMap* m, uint32_t w) {
  const uint32_t wy = (w * 57457u) >> 22, wx = w - wy * kNWX;
  asm volatile("cp.async.bulk.prefetch.tensor.3d.L2.global [%0, {%1,%2,%3}];" ::"l"(m + 1), "r"(wx * 168), "r"(wy * 7), "r"(0) : "memory");
}
__device__ __forceinline__ void wg_fence() { asm volatile("wgmma.fence.sync.aligned;" ::: "memory"); }
__device__ __forceinline__ void wg_commit() { asm volatile("wgmma.commit_group.sync.aligned;" ::: "memory"); }
__device__ __forceinline__ void wg_wait() { asm volatile("wgmma.wait_group.sync.aligned 0;" ::: "memory"); }
template <int N>
__device__ __forceinline__ void pin(uint32_t* d) {
#pragma unroll
  for (int i = 0; i < N; i++) asm volatile("" : "+r"(d[i])::"memory");
}
__device__ __forceinline__ uint32_t fresh(uint32_t v) { asm volatile("" : "+r"(v)); return v; }
__device__ __forceinline__ float fresh(float v) { asm volatile("" : "+f"(v)); return v; }
template <int N>
__device__ __forceinline__ void launder(uint32_t* q) {
#pragma unroll
  for (int j = 0; j < N; j++) { uint32_t t; asm volatile("mov.b32 %0, %1;" : "=r"(t) : "r"(q[j])); q[j] = t; }
}
__device__ __forceinline__ void sfence(uint32_t& v) {
  asm volatile("{\n.reg .pred p;\nsetp.eq.u32 p, %1, 0x7fffffff;\n@p mov.u32 %0, %%clock;\n}" : "+r"(v) : "r"(gridDim.x) : "memory");
}
constexpr uint64_t mk_desc(uint32_t addr) { return ((uint64_t)0x80000020u << 32) | (addr >> 4) | (1u << 16); }

#define R4(d, i) "+r"(d[i]), "+r"(d[i + 1]), "+r"(d[i + 2]), "+r"(d[i + 3])
#define O4(d, i) "=r"(d[i]), "=r"(d[i + 1]), "=r"(d[i + 2]), "=r"(d[i + 3])
#define D26 "{%0,%1,%2,%3,%4,%5,%6,%7,%8,%9,%10,%11,%12,%13,%14,%15,%16,%17,%18,%19,%20,%21,%22,%23,%24,%25},"
#define D24 "{%0,%1,%2,%3,%4,%5,%6,%7,%8,%9,%10,%11,%12,%13,%14,%15,%16,%17,%18,%19,%20,%21,%22,%23},"
#define D14 "{%0,%1,%2,%3,%4,%5,%6,%7,%8,%9,%10,%11,%12,%13},"

template <int SC, int TB>
__device__ __forceinline__ void wgmma(uint32_t (&d)[24], const uint32_t* a, uint64_t db) {
  if (SC == 2)
    asm volatile("{\n.reg .pred p;\nsetp.eq.u32 p, %30, 0x7fffffff;\n"
                 "wgmma.mma_async.sync.aligned.m64n96k16.f16.f16.f16 " D24 "{%24,%25,%26,%27}, %28, p, 1, 1, %29;\n}"
                 : R4(d, 0), R4(d, 4), R4(d, 8), R4(d, 12), R4(d, 16), R4(d, 20)
                 : "r"(a[0]), "r"(a[1]), "r"(a[2]), "r"(a[3]), "l"(db), "n"(TB), "r"(gridDim.x));
  else if (SC)
    asm volatile("wgmma.mma_async.sync.aligned.m64n96k16.f16.f16.f16 " D24 "{%24,%25,%26,%27}, %28, 1, 1, 1, %29;"
                 : R4(d, 0), R4(d, 4), R4(d, 8), R4(d, 12), R4(d, 16), R4(d, 20)
                 : "r"(a[0]), "r"(a[1]), "r"(a[2]), "r"(a[3]), "l"(db), "n"(TB));
  else
    asm volatile("wgmma.mma_async.sync.aligned.m64n96k16.f16.f16.f16 " D24 "{%24,%25,%26,%27}, %28, 0, 1, 1, %29;"
                 : O4(d, 0), O4(d, 4), O4(d, 8), O4(d, 12), O4(d, 16), O4(d, 20)
                 : "r"(a[0]), "r"(a[1]), "r"(a[2]), "r"(a[3]), "l"(db), "n"(TB));
}
template <int SC, int TB>
__device__ __forceinline__ void wgmma(uint32_t (&d)[26], const uint32_t* a, uint64_t db) {
  if (SC)
    asm volatile("wgmma.mma_async.sync.aligned.m64n104k16.f16.f16.f16 " D26 "{%26,%27,%28,%29}, %30, 1, 1, 1, 0;"
                 : R4(d, 0), R4(d, 4), R4(d, 8), R4(d, 12), R4(d, 16), R4(d, 20), "+r"(d[24]), "+r"(d[25])
                 : "r"(a[0]), "r"(a[1]), "r"(a[2]), "r"(a[3]), "l"(db));
  else
    asm volatile("wgmma.mma_async.sync.aligned.m64n104k16.f16.f16.f16 " D26 "{%26,%27,%28,%29}, %30, 0, 1, 1, 0;"
                 : O4(d, 0), O4(d, 4), O4(d, 8), O4(d, 12), O4(d, 16), O4(d, 20), "=r"(d[24]), "=r"(d[25])
                 : "r"(a[0]), "r"(a[1]), "r"(a[2]), "r"(a[3]), "l"(db));
}
template <int SC, int TB>
__device__ __forceinline__ void wgmma(uint32_t (&d)[16], const uint32_t* a, uint64_t db) {
  if (SC)
    asm volatile("wgmma.mma_async.sync.aligned.m64n56k16.f16.f16.f16 " D14 "{%14,%15,%16,%17}, %18, 1, 1, 1, 0;"
                 : R4(d, 0), R4(d, 4), R4(d, 8), "+r"(d[12]), "+r"(d[13])
                 : "r"(a[0]), "r"(a[1]), "r"(a[2]), "r"(a[3]), "l"(db));
  else
    asm volatile("wgmma.mma_async.sync.aligned.m64n56k16.f16.f16.f16 " D14 "{%14,%15,%16,%17}, %18, 0, 1, 1, 0;"
                 : O4(d, 0), O4(d, 4), O4(d, 8), "=r"(d[12]), "=r"(d[13])
                 : "r"(a[0]), "r"(a[1]), "r"(a[2]), "r"(a[3]), "l"(db));
}
template <int SC, int OFF, int CH, int ND>
__device__ __forceinline__ void gemm(uint32_t (&d)[ND], const uint32_t* a, uint64_t db) {
  asm volatile("" : "+l"(db));
  wg_fence();
  wgmma<SC, 0>(d, a, db + OFF / 16);
#pragma unroll
  for (int k = 1; k < 6; k++) wgmma<1, 0>(d, a + 4 * k, db + (OFF + (k >> 1) * CH + (k & 1) * 32) / 16);
  wg_commit();
}
__device__ __forceinline__ void lds128(uint32_t* r, uint32_t a) {
  asm volatile("ld.shared.v4.b32 {%0,%1,%2,%3}, [%4];" : "=r"(r[0]), "=r"(r[1]), "=r"(r[2]), "=r"(r[3]) : "r"(a) : "memory");
}
__device__ __forceinline__ void ldsm4(uint32_t* r, uint32_t a) {
  asm volatile("ldmatrix.sync.aligned.m8n8.x4.shared.b16 {%0,%1,%2,%3}, [%4];"
               : "=r"(r[0]), "=r"(r[1]), "=r"(r[2]), "=r"(r[3]) : "r"(a) : "memory");
}
__device__ __forceinline__ void stsm4(uint32_t a, const uint32_t* r) {
  asm volatile("stmatrix.sync.aligned.m8n8.x4.shared.b16 [%0], {%1,%2,%3,%4};" ::"r"(a), "r"(r[0]), "r"(r[1]), "r"(r[2]), "r"(r[3])
               : "memory");
}
__device__ __forceinline__ void stg3(uint8_t* p, const uint32_t* r, uint32_t off) {
  asm volatile("{\n.reg .pred p;\nsetp.eq.u32 p, %13, 0;\n@p st.global.v4.b32 [%0], {%1,%2,%3,%4};\n"
               "@p st.global.v4.b32 [%0+64], {%5,%6,%7,%8};\n@p st.global.v4.b32 [%0+128], {%9,%10,%11,%12};\n}" ::"l"(p),
               "r"(r[0]), "r"(r[1]), "r"(r[2]), "r"(r[3]), "r"(r[4]), "r"(r[5]), "r"(r[6]), "r"(r[7]), "r"(r[8]), "r"(r[9]), "r"(r[10]), "r"(r[11]),
               "r"(off) : "memory");
}
__device__ __forceinline__ uint32_t pack_h2(float lo, float hi) {
  uint32_t r; asm("cvt.rn.f16x2.f32 %0, %1, %2;" : "=r"(r) : "f"(hi), "f"(lo)); return r;
}
__device__ __forceinline__ uint32_t pack_h2_sat(float lo, float hi) {
  uint32_t r; asm("cvt.rn.satfinite.f16x2.f32 %0, %1, %2;" : "=r"(r) : "f"(hi), "f"(lo)); return r;
}
__device__ __forceinline__ uint32_t pack_bf2(float lo, float hi) {
  uint32_t r; asm("cvt.rn.bf16x2.f32 %0, %1, %2;" : "=r"(r) : "f"(hi), "f"(lo)); return r;
}
__device__ __forceinline__ __half2 as_h2(uint32_t v) { return *reinterpret_cast<__half2*>(&v); }
__device__ __forceinline__ uint32_t as_u(__half2 v) { return *reinterpret_cast<uint32_t*>(&v); }
__device__ __forceinline__ float2 unpack_h2(uint32_t v) { return __half22float2(as_h2(v)); }
__device__ __forceinline__ float low_f(uint32_t v) { return __low2float(as_h2(v)); }
__device__ __forceinline__ uint32_t h2ex2(uint32_t v) { uint32_t r; asm("ex2.approx.f16x2 %0, %1;" : "=r"(r) : "r"(v)); return r; }
__device__ __forceinline__ uint32_t h2max(uint32_t a, uint32_t b) { return as_u(__hmax2(as_h2(a), as_h2(b))); }
__device__ __forceinline__ uint32_t h2add(uint32_t a, uint32_t b) { return as_u(__hadd2(as_h2(a), as_h2(b))); }
__device__ __forceinline__ uint32_t h2sub(uint32_t a, uint32_t b) { return as_u(__hsub2(as_h2(a), as_h2(b))); }
__device__ __forceinline__ uint32_t h2mul(uint32_t a, uint32_t b) { return as_u(__hmul2(as_h2(a), as_h2(b))); }
__device__ __forceinline__ uint32_t h2neg(uint32_t a) { return as_u(__hneg2(as_h2(a))); }
__device__ __forceinline__ uint32_t h2fma(uint32_t a, uint32_t b, uint32_t c) { return as_u(__hfma2(as_h2(a), as_h2(b), as_h2(c))); }
__device__ __forceinline__ uint32_t lo2(uint32_t v) { return as_u(__low2half2(as_h2(v))); }
__device__ __forceinline__ uint32_t hi2(uint32_t v) { return as_u(__high2half2(as_h2(v))); }
__device__ __forceinline__ uint32_t fold_add(uint32_t a, uint32_t b) { return h2add(__byte_perm(a, b, 0x5410), __byte_perm(a, b, 0x7632)); }
__device__ __forceinline__ uint32_t sel(uint32_t p, uint32_t a, uint32_t b) {
  uint32_t r; asm("{\n.reg .pred p;\nsetp.ne.u32 p, %3, 0;\nselp.b32 %0, %1, %2, p;\n}" : "=r"(r) : "r"(a), "r"(b), "r"(p)); return r;
}
__device__ __forceinline__ float sel4(uint32_t c, float a0, float a1, float a2, float a3) {
  return __uint_as_float(sel(c & 2, sel(c & 1, __float_as_uint(a3), __float_as_uint(a2)), sel(c & 1, __float_as_uint(a1), __float_as_uint(a0))));
}
__device__ __forceinline__ float rcp_fast(float v) { float r; asm("rcp.approx.ftz.f32 %0, %1;" : "=f"(r) : "f"(v)); return r; }
__device__ __forceinline__ float rsq_fast(float v) { float r; asm("rsqrt.approx.ftz.f32 %0, %1;" : "=f"(r) : "f"(v)); return r; }
__device__ __forceinline__ uint32_t shfl_x(uint32_t v, int m) { return __shfl_xor_sync(0xffffffffu, v, m); }
__device__ __forceinline__ uint32_t shfl_q(uint32_t v, int i) { return __shfl_sync(0xffffffffu, v, i, 4); }
__device__ __forceinline__ float quad_sum(float v) {
  v += __shfl_xor_sync(0xffffffffu, v, 1);
  return v + __shfl_xor_sync(0xffffffffu, v, 2);
}
__device__ __forceinline__ uint32_t score_scale(const float* p) { const float v = __ldcg(p); return pack_h2(v, v); }

constexpr float kEps96 = 1e-5f * 96.f * 96.f;
__device__ __forceinline__ float2 stat_f32(uint32_t e) {
  const float2 h = unpack_h2(e);
  return make_float2(__uint_as_float(sel(e & 0x8000u, (e << 16) & 0x7fff0000u, __float_as_uint(h.x))),
                     __uint_as_float(sel(e & 0x8000u, e & 0xffff0000u, __float_as_uint(h.y))));
}

struct Tile {
  uint32_t ring, a;
  uint32_t next;
  uint32_t n;
  int live;
  uint32_t stat, wrap;
  uint32_t flag;
  uint32_t gate;
};
struct TPar { float kt, sgmin, outmax; };

__device__ __forceinline__ uint32_t swz(uint32_t r, int t) { return fresh(r ^ (((r >> 3) + 8 * t) & 0x30)); }
__device__ __forceinline__ void load_rows(uint32_t* x0, uint32_t* x1, uint32_t ring, uint32_t r, int t) {
  const uint32_t a0 = swz(r, t), a1 = swz(r, t + 1), u0 = ring + t * kPlane, u1 = u0 + kPlane;
  lds128(x0, a0 + u0); lds128(x1, a1 + u1);
  lds128(x0 + 4, fresh(a0 ^ 32) + (u0 + kChunk)); lds128(x1 + 4, fresh(a1 ^ 32) + (u1 + kChunk));
  lds128(x0 + 8, a0 + (u0 + 2 * kChunk)); lds128(x1 + 8, a1 + (u1 + 2 * kChunk));
}
__device__ __forceinline__ void to_half(uint32_t (&z)[24], const uint32_t* x, int o0, int o1) {
#pragma unroll
  for (int j = 0; j < 24; j += 2) {
    const int o = j < 12 ? 2 * j : 2 * j - 23;
    if (o < o0 || o >= o1) continue;
    uint32_t t;
    asm("cvt.rz.f16x2.f32 %0, %1, %2;" : "=r"(t) : "f"(__uint_as_float(x[j + 1])), "f"(__uint_as_float(x[j])));
    z[o] = fresh(pack_h2(__uint_as_float(x[j] << 16), __uint_as_float(x[j + 1] << 16)));
    z[o + 2] = fresh(t & 0xfff8fff8u);
  }
}
__device__ __forceinline__ void load_general(uint32_t (&z)[24], uint32_t ring, uint32_t r, int t, float& ie0, float& ie1, float& m0, float& m1) {
  float acc[48];
  uint32_t x0[12], x1[12];
  load_rows(x0, x1, ring, r, t);
#pragma unroll
  for (int j = 0; j < 12; j++) {
    acc[4 * j] = __uint_as_float(x0[j] << 16); acc[4 * j + 1] = __uint_as_float(x0[j] & 0xffff0000u);
    acc[4 * j + 2] = __uint_as_float(x1[j] << 16); acc[4 * j + 3] = __uint_as_float(x1[j] & 0xffff0000u);
  }
  float s[4], q[4];
#pragma unroll
  for (int e = 0; e < 4; e++) { s[e] = acc[e]; q[e] = acc[e] * acc[e]; }
#pragma unroll
  for (int j = 4; j < 48; j++) { s[j & 3] += acc[j]; q[j & 3] = fmaf(acc[j], acc[j], q[j & 3]); }
  const float s0 = quad_sum(s[0] + s[1]), s1 = quad_sum(s[2] + s[3]), q0 = quad_sum(q[0] + q[1]), q1 = quad_sum(q[2] + q[3]);
  const float u0 = rsq_fast(fmaxf(fmaf(-s0, s0, fmaf(q0, 96.f, kEps96)), kEps96));
  const float u1 = rsq_fast(fmaxf(fmaf(-s1, s1, fmaf(q1, 96.f, kEps96)), kEps96));
  const float n0 = -s0 * u0, n1 = -s1 * u1;
  ie0 = 96.f * u0; ie1 = 96.f * u1;
  m0 = s0 * (1.f / 96.f); m1 = s1 * (1.f / 96.f);
#pragma unroll
  for (int j = 0; j < 12; j++) {
    const int o = 8 * (j >> 1) + (j & 1);
    z[2 * j] = pack_h2(fmaf(acc[o], ie0, n0), fmaf(acc[o + 4], ie0, n0));
    z[2 * j + 1] = pack_h2(fmaf(acc[o + 2], ie1, n1), fmaf(acc[o + 6], ie1, n1));
  }
}
template <bool kDown>
__device__ __forceinline__ uint32_t sumsq2(const uint32_t* z) {
  uint32_t q0, q1;
#pragma unroll
  for (int j = 0; j < 12; j++) {
    const uint32_t u = kDown ? h2mul(z[2 * j], 0x1c001c00u) : z[2 * j], v = kDown ? h2mul(z[2 * j + 1], 0x1c001c00u) : z[2 * j + 1];
    q0 = j ? h2fma(u, u, q0) : h2mul(u, u); q1 = j ? h2fma(v, v, q1) : h2mul(v, v);
  }
  return fold_add(q0, q1);
}
template <bool kDown>
__device__ __forceinline__ float row_sumsq(const uint32_t* z0, const uint32_t* z1, uint32_t c) {
  const uint32_t a = sumsq2<kDown>(z0), b = sumsq2<kDown>(z1);
  uint32_t t = h2add(sel(c & 2, b, a), shfl_x(sel(c & 2, a, b), 2));
  t = h2add(t, shfl_x(t, 1));
  return low_f(sel(c & 1, t >> 16, t));
}
__device__ __forceinline__ void scores2(const uint32_t* q, const uint32_t* z0, const uint32_t* z1, uint32_t* f) {
  uint32_t d[8];
#pragma unroll
  for (int j = 0; j < 12; j++) {
    const uint32_t kk[4] = {z0[2 * j], z0[2 * j + 1], z1[2 * j], z1[2 * j + 1]};
#pragma unroll
    for (int e = 0; e < 4; e++) {
      d[e] = j ? h2fma(q[2 * j], kk[e], d[e]) : h2mul(q[2 * j], kk[e]);
      d[4 + e] = j ? h2fma(q[2 * j + 1], kk[e], d[4 + e]) : h2mul(q[2 * j + 1], kk[e]);
    }
  }
#pragma unroll
  for (int e = 0; e < 4; e++) f[e] = fold_add(d[2 * e], d[2 * e + 1]);
}
struct Xch { uint32_t keep[2], got[2]; };
__device__ __forceinline__ Xch pair_send(const uint32_t* a, const uint32_t* b, uint32_t c, int m) {
  Xch x;
#pragma unroll
  for (int e = 0; e < 2; e++) { x.keep[e] = fresh(sel(c & m, b[e], a[e])); x.got[e] = shfl_x(sel(c & m, a[e], b[e]), m); }
  return x;
}
__device__ __forceinline__ void pair_recv(uint32_t* k, const Xch& x) { k[0] = h2add(x.keep[0], x.got[0]); k[1] = h2add(x.keep[1], x.got[1]); }
__device__ __forceinline__ void mix2(uint32_t* y, const uint32_t* v, uint32_t c0, uint32_t c1) {
#pragma unroll
  for (int j = 0; j < 12; j++) {
    y[2 * j] = h2fma(v[2 * j + 1], hi2(c0), h2fma(v[2 * j], lo2(c0), y[2 * j]));
    y[2 * j + 1] = h2fma(v[2 * j + 1], hi2(c1), h2fma(v[2 * j], lo2(c1), y[2 * j + 1]));
  }
  pin<24>(y);
}
__device__ __forceinline__ void norm_store(uint32_t* y, uint32_t r0, uint32_t r1, uint32_t r, int t) {
#pragma unroll
  for (int j = 0; j < 12; j++) { y[2 * j] = h2fma(y[2 * j], lo2(r0), hi2(r0)); y[2 * j + 1] = h2fma(y[2 * j + 1], lo2(r1), hi2(r1)); }
  const uint32_t ma = swz(r, t), mb = fresh(ma ^ 32), u = t * kPlane;
  stsm4(ma + u, y); stsm4(mb + u, y + 4);
  stsm4(mb + (u + kChunk), y + 8); stsm4(ma + (u + kChunk), y + 12);
  stsm4(ma + (u + 2 * kChunk), y + 16); stsm4(mb + (u + 2 * kChunk), y + 20);
}

template <bool kAlways>
__device__ __forceinline__ void gate_open(uint32_t id) {
  if (kAlways) asm volatile("barrier.cta.arrive.aligned %0, 256;" ::"r"(id) : "memory");
  else asm volatile("{\n.reg .pred p;\nsetp.ne.u32 p, %0, 0;\n@p barrier.cta.arrive.aligned %0, 256;\n}" ::"r"(id) : "memory");
}

struct TState { uint32_t z0[24], z1[24], mu, bad; float ie, mm, mz, qq; };
template <bool kDirect>
__device__ __forceinline__ void temporal(TState& S, uint64_t da, const Tile& T, const TPar& P, bool scaled, uint32_t lane, uint32_t& lst) {
  uint32_t (&z0)[24] = S.z0, (&z1)[24] = S.z1;
  const uint32_t c = lane;
  const uint32_t a0 = T.a + lane * 16 + (lane >= 4 * T.n ? T.next : 0);
  uint32_t q0[26], q1[24], v0[24], w1[26], nn = 0, ng = 0, ca0 = 0, ca1 = 0;
  uint32_t* const v1 = w1 + 2;
  float ie = 1.f, mm = 0.f;
  bool tiny = false;
  if (kDirect) {
    uint32_t x[48];
    load_rows(x, x + 12, T.ring, a0, 0);
    to_half(z0, x, 0, 16);
    sfence(lst);
    load_rows(x + 24, x + 36, T.ring, a0, 2);
    to_half(z0, x, 16, 24);
    gemm<0, 0, kAtChunk>(q0, z0, da);
    sfence(lst);
    to_half(z1, x + 24, 0, 24);
    const uint32_t n0 = sumsq2<false>(z0), n1 = sumsq2<false>(z1);
    nn = fresh(sel(c & 2, n1, n0)); ng = shfl_x(sel(c & 2, n0, n1), 2);
    pin<24>(z1); sfence(lst);
  } else {
    float e[4], m[4];
    load_general(z0, T.ring, a0, 0, e[0], e[1], m[0], m[1]);
    pin<24>(z0); sfence(lst);
    load_general(z1, T.ring, a0, 2, e[2], e[3], m[2], m[3]);
    ie = sel4(c, e[0], e[1], e[2], e[3]);
    mm = sel4(c, m[0], m[1], m[2], m[3]);
    tiny = __any_sync(0xffffffffu, ie * P.kt > 400.f);
    if (tiny) {
      float u = 0.f;
#pragma unroll
      for (int r = 0; r < 4; r++) {
        float t = 0.f;
#pragma unroll
        for (int j = 0; j < 12; j++) { const float2 f = unpack_h2((r & 2 ? z1 : z0)[2 * j + (r & 1)]); t = fmaf(f.x, f.x, fmaf(f.y, f.y, t)); }
        u = fmaxf(u, quad_sum(t));
      }
      const float t = fminf(ie, 9.8f * rsq_fast(fmaxf(u, 2e-7f)) * rcp_fast(fresh(P.kt)));
      const uint32_t a = pack_h2(__fdividef(t, ie), 0.f);
      ca0 = __byte_perm(shfl_q(a, 0), shfl_q(a, 1), 0x5410); ca1 = __byte_perm(shfl_q(a, 2), shfl_q(a, 3), 0x5410);
      ie = t;
    }
    gemm<0, 0, kAtChunk>(q0, z0, da);
  }
  uint32_t f[4], k0[2], k1[2], sk[2];
  wg_wait(); pin<26>(q0);
  gemm<0, 0, kAtChunk>(q1, z1, da);
  gate_open<kDirect>(T.gate);
  sfence(lst);
  if (kDirect) { nn = h2add(nn, ng); ng = shfl_x(nn, 1); sfence(lst); }
  scores2(q0, z0, z1, f);
  const uint32_t nu0 = fresh(__byte_perm(q0[24], q0[25], 0x7632)), m01 = fresh(sel(c & 1, q0[25], q0[24]));
  Xch xc = pair_send(f, f + 2, c, 1);
  sfence(lst);
  wg_wait(); pin<24>(q1);
  gemm<0, kOffWt - 512, kAtChunk>(w1, z1, da);
  sfence(lst);
  pair_recv(k0, xc);
  float e2 = 0.f, lim = 0.f;
  if (kDirect) {
    nn = h2add(nn, ng);
    e2 = fresh(fmaf(low_f(sel(c & 1, nn >> 16, nn)), 1.f / 96.f, 1e-5f));
    lim = fresh(e2 <= 4.f ? fmaxf(0.5f * e2, 4e-4f) : __uint_as_float(0x7fffffffu));
  }
  scores2(q1, z0, z1, f);
  xc = pair_send(f, f + 2, c, 1);
  pin<2>(k0); sfence(lst);
  wg_wait(); pin<26>(w1);
  float mz = 0.f, d2 = 0.f;
  if (kDirect) {
    mz = low_f(sel(c & 2, sel(c & 1, w1[1], w1[0]), m01));
    d2 = fmaf(-mz, mz, e2);
    asm volatile("{\n.reg .pred p;\nsetp.lt.s32 p, %3, %4;\nsetp.ltu.and.f32 p, %1, %2, p;\n@p st.volatile.shared.f32 [%0], %2;\n}" ::"r"(T.flag), "f"(d2),
                 "f"(lim), "r"(lane), "r"(T.live) : "memory");
  }
  gemm<0, kOffWt, kAtChunk>(v0, z0, da);
  sfence(lst);
  uint32_t cw[8], mu;
  {
    uint32_t rc = 0, r0 = 0, r1 = 0;
    if (kDirect) {
      const float r = rsq_fast(d2);
      rc = pack_h2(r, r);
      r0 = __byte_perm(shfl_q(rc, 0), shfl_q(rc, 1), 0x5410); r1 = __byte_perm(shfl_q(rc, 2), shfl_q(rc, 3), 0x5410);
    }
    pair_recv(k1, xc);
    pair_recv(sk, pair_send(k0, k1, c, 2));
    if (kDirect) { sk[0] = h2mul(sk[0], r0); sk[1] = h2mul(sk[1], r1); }
    uint32_t mx = h2max(sk[0], sk[1]);
    mx = h2max(lo2(mx), hi2(mx));
    if (kDirect) {
      const uint32_t nm = h2mul(h2neg(mx), rc);
      sk[0] = h2fma(sk[0], rc, nm); sk[1] = h2fma(sk[1], rc, nm);
    } else {
      sk[0] = h2sub(sk[0], mx); sk[1] = h2sub(sk[1], mx);
      if (scaled) {
        const uint32_t cs = score_scale(&g_par.cS_t);
        sk[0] = h2mul(sk[0], cs); sk[1] = h2mul(sk[1], cs);
      }
    }
    sk[0] = h2ex2(sk[0]); sk[1] = h2ex2(sk[1]);
    const uint32_t sm = h2add(sk[0], sk[1]);
    const float iv = (kDirect ? P.kt : P.kt * ie) * rcp_fast(low_f(h2add(lo2(sm), hi2(sm))));
    const uint32_t inv = pack_h2(iv, iv);
    if (kDirect) { sk[0] = h2mul(sk[0], r0); sk[1] = h2mul(sk[1], r1); }
    sk[0] = h2mul(sk[0], inv); sk[1] = h2mul(sk[1], inv);
#pragma unroll
    for (int i = 0; i < 4; i++) { cw[2 * i] = shfl_q(sk[0], i); cw[2 * i + 1] = shfl_q(sk[1], i); }
    mu = h2fma(sk[1], __byte_perm(w1[0], w1[1], 0x7632), h2mul(sk[0], nu0));
    mu = h2add(lo2(mu), hi2(mu));
  }
  uint32_t bad = 0;
  if (kDirect) {
    mix2(z1, v1, cw[5], cw[7]);
    sfence(lst);
    wg_wait(); pin<24>(v0);
    mix2(z1, v0, cw[4], cw[6]);
    sfence(lst);
    bad = lds32(T.flag);
  } else {
    wg_wait(); pin<24>(v0);
    if (tiny) {
#pragma unroll
      for (int j = 0; j < 12; j++) {
        z0[2 * j] = h2mul(z0[2 * j], lo2(ca0)); z0[2 * j + 1] = h2mul(z0[2 * j + 1], hi2(ca0));
        z1[2 * j] = h2mul(z1[2 * j], lo2(ca1)); z1[2 * j + 1] = h2mul(z1[2 * j + 1], hi2(ca1));
      }
    }
    mix2(z1, v1, cw[5], cw[7]);
    mix2(z1, v0, cw[4], cw[6]);
  }
  mix2(z0, v1, cw[1], cw[3]);
  mix2(z0, v0, cw[0], cw[2]);
  S.qq = row_sumsq<false>(z0, z1, c);
  S.mu = mu; S.bad = bad; S.ie = ie; S.mm = mm; S.mz = mz;
}
__device__ __forceinline__ bool irregular(const TState& S, const Tile& T, uint32_t lane) {
  return __any_sync(0xffffffffu, (!(S.qq < 65000.f) & ((int)lane < T.live)) | (S.bad != 0));
}
__device__ __forceinline__ void resum(TState& S, uint32_t lane) {
  const float q2 = row_sumsq<true>(S.z0, S.z1, lane) * 65536.f;
  S.qq = S.qq < 65000.f ? S.qq : q2;
}
template <bool kDirect>
__device__ __forceinline__ void temporal_out(TState& S, const Tile& T, uint32_t slot, const TPar& P, uint32_t lane, uint32_t lst) {
  uint32_t (&z0)[24] = S.z0, (&z1)[24] = S.z1;
  const uint32_t mu = S.mu;
  const float ie = S.ie, mz = S.mz, qq = S.qq;
  float mm = S.mm;
  const float rf = kDirect ? rsq_fast(fmaxf(fmaf(-mz, mz, fmaf(qq, 1.f / 96.f, 1e-5f)), 1e-5f)) : rsq_fast(fmaf(qq, 1.f / 96.f, 1e-5f * ie * ie));
  const uint32_t rn = pack_h2_sat(rf, -mz * rf);
  uint32_t rr[4];
#pragma unroll
  for (int i = 0; i < 4; i++) rr[i] = shfl_q(rn, i);
  lane = fresh(lane);
  const uint32_t ma = fresh(T.ring + T.a) + lst + ((lane & 7) >= T.n ? T.next : 0);
  norm_store(z0, rr[0], rr[1], ma, 0);
  const float2 rm = unpack_h2(rn);
  const float sg = rcp_fast(kDirect ? rm.x : rm.x * ie);
  mm = kDirect ? fmaf(-rm.y, sg, low_f(mu)) : fmaf(low_f(mu) * rm.x, sg, mm);
  const uint32_t bars = slot + (lane >= 4 * T.n ? T.next + kPlane : 0);
  const bool ok = (sg >= P.sgmin) & (fmaf(sg, 9.8f, fabsf(mm)) < P.outmax);
  asm volatile("{\n.reg .pred p;\nsetp.lt.s32 p, %2, %3;\n@p st.shared.b32 [%0], %1;\n}" ::"r"(
                   T.stat + fresh((lane & 3) * (kSlot - 1) + lane + (lane >= 4 * T.n ? T.wrap : 0))),
               "r"(sel(ok, pack_h2(sg, mm), pack_bf2(sg, mm) | 0x8000u)), "r"(lane), "r"(T.live) : "memory");
  asm volatile("{\n.reg .pred p;\nsetp.eq.u32 p, %1, 0;\n@p st.shared.b32 [%0], %0;\n}" ::"r"(bars + kWide), "r"((uint32_t)ok) : "memory");
  norm_store(z1, rr[2], rr[3], ma, 2);
}

__device__ __forceinline__ void run_T(uint32_t ring, uint64_t d0, uint64_t d1, uint32_t nfull, uint32_t nrem, bool helper, int wg, int wp, uint32_t lane,
                                      const TPar& P, bool scaled, uint32_t pdir) {
  uint32_t lst = (lane & 7) * 64 + (lane & 8) * (kPlane / 8) + (lane & 16);
  uint32_t p0 = 32 * (wg & 1) + (helper ? 0 : 64) + 8 * wp;
  uint32_t npx = 49 * nfull, pstop = npx - 6 * 49 + 8 * wp;
  if (helper) pstop = 0;
  uint32_t pgap = 0;
  sfence(lane);
  Tile T;
  T.ring = ring;
  T.flag = ring + wg * kSlot + kFlag;
  T.gate = wg == 3 ? 6 : 5 + wg;
  while (true) {
    const uint32_t iw = (p0 * 21400u) >> 20, ow = p0 - 49 * iw;
    const uint32_t slot = ring + (iw & 3) * kSlot, dn = (iw & 3) == 3 ? -3 * kSlot : kSlot;
    asm volatile("{\n.reg .pred p;\nsetp.eq.u32 p, %1, 0;\n@p barrier.cta.sync.aligned %0, 256;\n}" ::"r"(6 - (wg & 1)), "r"((uint32_t)helper) : "memory");
    mbar_wait(slot + kFull, iw >> 2);
    if (ow > 41) mbar_wait(slot + dn + kFull, (iw + 1) >> 2);
    T.a = (iw & 3) * kSlot + ow * 64; T.next = dn - kPlane; T.n = 49 - ow;
    T.live = 4 * (npx - p0);
    T.stat = ring + kXBytes + (p0 - 196 * (iw >> 2)) * 4; T.wrap = (iw & 3) == 3 ? -784 : 0;
    lane = fresh(lane);
    {
      TState S;
      Tile G = T;
      if (p0 >= pdir) {
        temporal<true>(S, d0, T, P, false, lane, lst);
        if (irregular(S, T, lane)) {
          if (__any_sync(0xffffffffu, S.bad != 0)) goto redo;
          resum(S, lane);
        }
        temporal_out<true>(S, T, slot, P, lane, lst);
        goto stored;
      redo:
        asm volatile("barrier.cta.sync.aligned %0, 128;" ::"r"(wg + 1) : "memory");
        asm volatile("st.shared.b32 [%0], %1;\nfence.acq_rel.cta;" ::"r"(T.flag), "r"(0) : "memory");
        G.gate = 0;
        pgap = p0 == pdir ? 4 * pgap + 64 : 0;
        pdir = p0 + 64 + pgap;
      }
      temporal<false>(S, d1, G, P, scaled, lane, lst);
      if (irregular(S, T, lane)) resum(S, lane);
      temporal_out<false>(S, T, slot, P, lane, lst);
    }
  stored:
    const uint32_t pn = __shfl_sync(0xffffffffu, p0 + 64, 0);
    bool last = false;
    if (pn >= pstop) {
      if (helper) last = true;
      else if (pstop < npx - 4 * 49) {
        if (((wg & 1) | wp | lane) == 0) {
          const uint32_t nb = gridDim.x, nwh = min(max((int)(2 * nrem - nb), (int)(nrem / 2)), nrem);
          const uint32_t r = atomicAdd(&g_par.ticket, 1u), j = r - nwh;
          sts32(ring + kExtra, r < nwh ? (nfull * nb + r) * 4 + 3 : j < 2 * (nrem - nwh) ? (nfull * nb + nwh + (j >> 1)) * 4 + 1 + (j & 1) : 0);
        }
        __syncwarp();
        pstop = npx - 2 * 49 + 8 * wp;
      } else if (pstop < npx) {
        if (__shfl_sync(0xffffffffu, lds32(ring + kExtra), 0)) npx += 49;
        pstop = npx + 8 * wp;
      } else last = true;
    }
    asm volatile("fence.proxy.async.shared::cta;" ::: "memory");
    __syncwarp();
    mbar_arrive(slot + kDone + (fresh(lane) >= 4 * T.n ? dn : 0), lane & 3);
    __syncwarp();
    if (last) break;
    p0 = pn;
  }
}

struct Frame {
  bool light;
  uint32_t sta;
  uint32_t oo;
  uint32_t e0, e1;
};
__device__ __forceinline__ uint32_t frame_init(Frame& F, uint32_t ring, uint32_t t, int wp, int lane) {
  wp = (wp + t) & 3;
  F.light = wp == 3;
  F.sta = ring + t * kSlot + kXBytes + 64 * wp;
  const uint32_t r = 16 * wp + (lane >> 2);
  F.oo = ((r / 7) * (kW - 7) + r) * 192u + (lane & 3) * 16 + (((((r + 8) / 7 - r / 7) * (kW - 7) + 8) * 3u) << 20);
  F.e0 = F.e1 = 0;
  const uint32_t am = t * kPlane + wp * 1024 + ((lane * 65) & 0x3d0);
  return F.light && (lane & 15) ? kZero : am ^ ((am >> 3) & 0x30);
}
template <bool F>
__device__ __forceinline__ void load_frame(uint32_t (&v)[24], uint32_t ma, uint32_t slot, uint32_t& tid) {
  const uint32_t st = ma < kXBytes ? kChunk : 0, mb = ma ^ 32;
  uint32_t a[6] = {ma, mb, mb + st, ma + st, ma + 2 * st, mb + 2 * st};
  pin<6>(a);
  if (F) sfence(tid);
#pragma unroll
  for (int k = 0; k < 6; k++) ldsm4(v + 4 * k, slot + a[k]);
}
__device__ __forceinline__ void load_block(uint32_t (&v)[24], uint32_t ma, uint32_t slot) {
  const uint32_t mb = fresh(ma ^ 32);
  ldsm4(v, ma + slot); ldsm4(v + 4, mb + slot);
  ldsm4(v + 8, mb + (slot + kChunk)); ldsm4(v + 12, ma + (slot + kChunk));
  ldsm4(v + 16, ma + (slot + 2 * kChunk)); ldsm4(v + 20, mb + (slot + 2 * kChunk));
}
__device__ __forceinline__ void load_light(uint32_t (&v)[24], uint32_t t, uint32_t slot, uint32_t& tid) {
  const uint32_t r = t * kPlane + 48 * 64, a0 = ((tid & 3) << 2) | ((r >> 3) & 0x30), u = slot + r, off = tid & 28;
  uint32_t a[4] = {a0, a0 ^ 16, a0 ^ 32, a0 ^ 48};
  pin<4>(a);
  sfence(tid);
#pragma unroll
  for (int j = 0; j < 12; j++) {
    asm volatile("mov.b32 %0, 0;" : "=r"(v[2 * j + 1]));
    asm volatile("{\n.reg .pred p;\nsetp.eq.u32 p, %2, 0;\nmov.b32 %0, 0;\n@p ld.shared.b32 %0, [%1];\n}"
                 : "=r"(v[2 * j]) : "r"(a[(j & 3) ^ (j & 4 ? 2 : 0)] + (u + (j >> 2) * kChunk)), "r"(off) : "memory");
  }
}
__device__ __forceinline__ void load_stats(Frame& F, uint32_t ia, uint32_t tid) {
  const uint32_t a = fresh(tid & 0x1c), u = F.sta + ia * 196;
  F.e0 = lds32(a + u);
  F.e1 = lds32(a + (u + 32));
}
template <int OFF>
__device__ __forceinline__ void gemm_u(uint32_t (&u)[24], const uint32_t* s, uint64_t db) {
  constexpr uint32_t kMN = (((kChunk >> 4) - 1) << 16) + OFF / 16;
  asm volatile("" : "+l"(db));
  wg_fence();
  wgmma<2, 1>(u, s, db + kMN); wgmma<1, 1>(u, s + 4, db + kMN + 64); wgmma<1, 1>(u, s + 8, db + kMN + 128); wgmma<1, 1>(u, s + 12, db + kMN + 192);
  wg_commit();
}
__device__ __forceinline__ uint32_t key48(uint32_t (&s)[16], uint32_t tid) {
  return fresh(sel(tid & 3, 0xfc00fc00u, __byte_perm(s[12], s[13], 0x5410)));
}
__device__ __forceinline__ uint32_t amax3(uint32_t a, uint32_t b, uint32_t c) {
  return as_u(__hmax2(__hmax2(__habs2(as_h2(a)), __habs2(as_h2(b))), __habs2(as_h2(c))));
}
struct Quad { uint32_t v[4]; };
__device__ __forceinline__ void sub_max(uint32_t (&s)[16], uint32_t& t) {
  const uint32_t x0 = h2max(h2max(h2max(s[0], s[2]), h2max(s[4], s[6])), h2max(s[8], s[10]));
  const uint32_t x1 = h2max(h2max(h2max(s[1], s[3]), h2max(s[5], s[7])), h2max(s[9], s[11]));
  uint32_t mx = h2max(h2max(__byte_perm(x0, x1, 0x5410), __byte_perm(x0, x1, 0x7632)), t);
  mx = h2max(mx, shfl_x(mx, 1));
  mx = h2max(mx, shfl_x(mx, 2));
#pragma unroll
  for (int j = 0; j < 6; j++) { s[2 * j] = h2sub(s[2 * j], lo2(mx)); s[2 * j + 1] = h2sub(s[2 * j + 1], hi2(mx)); }
  t = h2sub(t, mx);
}
template <int J>
__device__ __forceinline__ Quad exp_sum(uint32_t (&s)[16], uint32_t& t) {
#pragma unroll
  for (int j = J; j < 12; j++) s[j] = h2ex2(s[j]);
  t = h2ex2(t);
  Quad q;
  q.v[0] = h2add(t, fold_add(h2add(h2add(h2add(s[0], s[2]), h2add(s[4], s[6])), h2add(s[8], s[10])),
                             h2add(h2add(h2add(s[1], s[3]), h2add(s[5], s[7])), h2add(s[9], s[11]))));
#pragma unroll
  for (int i = 1; i < 4; i++) q.v[i] = shfl_x(q.v[0], i);
  return q;
}
__device__ __forceinline__ Quad soft_exp(uint32_t (&s)[16], uint32_t& t) {
  const uint32_t am = h2max(h2max(h2max(amax3(s[0], s[1], s[2]), amax3(s[3], s[4], s[5])), amax3(s[6], s[7], s[8])), h2max(amax3(s[9], s[10], s[11]), t));
  uint32_t rare, sp[4];
#pragma unroll
  for (int j = 0; j < 4; j++) sp[j] = fresh(h2ex2(s[j]));
  asm("{\n.reg .pred p, q;\n.reg .b32 t;\nmov.b32 t, 0x49004900;\nsetp.le.f16x2 p|q, %1, t;\nand.pred p, p, q;\nselp.b32 %0, 0, 1, p;\n}" : "=r"(rare) : "r"(am));
  if (__any_sync(0xffffffffu, rare)) {
    sub_max(s, t);
#pragma unroll
    for (int j = 0; j < 4; j++) sp[j] = h2ex2(s[j]);
  }
#pragma unroll
  for (int j = 0; j < 4; j++) s[j] = sp[j];
  return exp_sum<4>(s, t);
}
__device__ __forceinline__ void soft_norm(uint32_t (&s)[16], uint32_t& t, const Quad& q, const Frame& F, float2 e, uint32_t tid) {
  const float2 d = unpack_h2(h2add(h2add(q.v[0], q.v[1]), h2add(q.v[2], q.v[3])));
  const uint32_t cb = pack_h2(rcp_fast(d.x * e.x), rcp_fast(d.y * e.y)) & (sel(tid & 28, 0u, 0xffffu) | fresh(F.light ? 0u : 0xffffffffu));
#pragma unroll
  for (int j = 0; j < 6; j++) { s[2 * j] = h2mul(s[2 * j], lo2(cb)); s[2 * j + 1] = h2mul(s[2 * j + 1], hi2(cb)); }
  t = fresh(h2mul(t, cb));
  pin<12>(s);
}
__device__ __forceinline__ void soft_tail(uint32_t (&s)[16], uint32_t t) {
  s[12] = t & 0xffffu; s[13] = t >> 16;
  asm volatile("mov.b32 %0, 0;\nmov.b32 %1, 0;" : "=r"(s[14]), "=r"(s[15]));
}
template <int H>
__device__ __forceinline__ uint8_t* row_ptr(const Frame& F, uint8_t* o) {
  const uint32_t oo = fresh(F.oo);
  if (H) asm volatile("mad.wide.u32 %0, %1, 64, %0;" : "+l"(o) : "r"(oo >> 20));
  else { o += oo & 0xfffffu; asm volatile("" : "+l"(o)); }
  return o;
}
template <int H>
__device__ __forceinline__ void affine(uint32_t* r, const uint32_t (&v)[24], const Frame& F) {
  const uint32_t e = H ? F.e1 : F.e0;
#pragma unroll
  for (int j = 0; j < 12; j++) r[j] = h2fma(v[2 * j + H], lo2(e), hi2(e));
  pin<12>(r);
}
template <int H, bool kFence = false>
__device__ __forceinline__ void finish(uint32_t* r, const Frame& F, uint8_t*& o, uint32_t off, uint32_t a, uint32_t m, uint32_t& tid) {
  o = row_ptr<H>(F, o);
#pragma unroll
  for (int j = 0; j < 12; j += 2) { const float2 f = unpack_h2(r[j]), g = unpack_h2(r[j + 1]); r[j] = pack_bf2(f.x, g.x); r[j + 1] = pack_bf2(f.y, g.y); }
  pin<12>(r);
  if (kFence) sfence(tid);
  stg3(o, r, off | (fresh(a) & m));
}
__device__ __forceinline__ uint32_t window_ahead(uint32_t ring, uint32_t i, uint32_t nfull, uint32_t w) {
  return i + 4 < nfull ? w + 4 * gridDim.x : i + 4 == nfull ? lds32(ring + kExtra) >> 2 : 0;
}

__device__ __forceinline__ void release(uint32_t ring, uint32_t slot, uint32_t i, uint32_t nfull, uint32_t w, const CUtensorMap* tm, uint32_t lane) {
  uint32_t old = 0;
  asm volatile("{\n.reg .pred p;\nsetp.eq.u32 p, %2, 0;\n@p atom.relaxed.cta.shared::cta.inc.u32 %0, [%1], 1;\n}" : "+r"(old) : "r"(slot + kRel), "r"(lane) : "memory");
  if (old) {
    const uint32_t wn = window_ahead(ring, i, nfull, w);
    sts32(slot + kWide, 0);
    if (wn) tma_load_win(slot, tm, wn);
    else mbar_arrive(slot + kFull);
  }
  __syncwarp();
}
__device__ __forceinline__ uint32_t window_offset(uint32_t w) { return (((w * 57457u) >> 22) * (7 * kW - 7 * kNWX) + w * 7) * 192u; }

__device__ __forceinline__ void round_wide(uint32_t ring, uint64_t d0, uint32_t frame, uint32_t nfull, uint32_t i, uint32_t w, int sg, int wp, uint32_t lane,
                                           const CUtensorMap* tm, uint8_t* __restrict__ out) {
  const uint32_t slot = ring + (i & 3) * kSlot;
  uint32_t x[24];
#pragma unroll
  for (int j = 0; j < 24; j++) x[j] = 0;
#pragma unroll 1
  for (uint32_t t = 2 * sg; t < 2 * sg + 2; t++) {
    Frame F;
    uint32_t v[24], s[16];
    load_frame<false>(v, frame_init(F, ring, t, wp, lane), slot, lane);
    load_stats(F, i & 3, lane);
    const uint64_t dp = d0 + (uint32_t)((kWBytes + (i & 3) * kSlot + t * kPlane) / 16);
    gemm<2, kOffAs, 6144>(x, v, d0);
    const uint32_t cs = score_scale(&g_par.cS_s);
    const float kb = __ldcg(&g_par.kb), ik = rcp_fast(__ldcg(&g_par.kappa));
    wg_wait(); pin<24>(x);
    gemm<0, 0, kChunk>(s, x, dp);
    wg_wait(); pin<14>(s);
    uint32_t u = key48(s, lane);
    sub_max(s, u);
#pragma unroll
    for (int j = 0; j < 12; j++) s[j] = h2mul(s[j], cs);
    u = h2mul(u, cs);
    const float2 z0 = stat_f32(F.e0), z1 = stat_f32(F.e1);
    const float e0 = fmaxf(z0.x, kb), e1 = fmaxf(z1.x, kb);
    const uint32_t aw = pack_h2(__fdividef(z0.x, e0), __fdividef(z1.x, e1));
#pragma unroll
    for (int j = 0; j < 12; j++) { v[2 * j] = h2mul(v[2 * j], lo2(aw)); v[2 * j + 1] = h2mul(v[2 * j + 1], hi2(aw)); }
    soft_norm(s, u, exp_sum<0>(s, u), F, make_float2(e0 * ik, e1 * ik), lane);
    soft_tail(s, u);
    gemm_u<0>(x, s, dp);
    wg_wait(); pin<24>(x);
    gemm<1, kOffWs, 6144>(v, x, d0);
    if ((t & 1) && wp == 0) release(ring, slot, i, nfull, w, tm, lane);
    wg_wait(); pin<24>(v);
    uint8_t* o = out + (size_t)(window_offset(w) + t * frame);
#pragma unroll
    for (int h = 0; h < 2; h++) {
      const float e = h ? e1 : e0, m = h ? z1.y : z0.y;
      uint32_t r[12];
#pragma unroll
      for (int j = 0; j < 12; j += 2) {
        const float2 f = unpack_h2(v[2 * j + h]), g = unpack_h2(v[2 * j + 2 + h]);
        r[j] = pack_bf2(fmaf(f.x, e, m), fmaf(g.x, e, m)); r[j + 1] = pack_bf2(fmaf(f.y, e, m), fmaf(g.y, e, m));
      }
      o = h ? row_ptr<1>(F, o) : row_ptr<0>(F, o);
      stg3(o, r, F.light ? (h ? 1 : lane & 28) : 0);
    }
  }
}

__device__ __forceinline__ uint32_t rounds(uint32_t ring, uint64_t d0, uint64_t d1, uint32_t frame, uint32_t nfull, uint32_t i, uint32_t i1, uint32_t w,
                                           int sg, int wp, int lane, const CUtensorMap* tm, uint8_t* __restrict__ out) {
  Frame A, B;
  uint32_t tid = lane + (frame_init(A, ring, 2 * sg, wp, lane) << 4) + (frame_init(B, ring, 2 * sg + 1, wp, lane) << 16);
  uint32_t va[24], vb[24], x[24], sa[16], sc[16], r0[12], r1[12], ta, tb;
  Quad rs;
#pragma unroll
  for (int j = 0; j < 24; j++) { vb[j] = 0; x[j] = 0; }
  out += sg * 2 * frame;
  uint8_t *ob = out, *o;
  const uint64_t dr = d0 + (uint32_t)(kWBytes / 16 + sg * (2 * kPlane / 16));
  uint32_t slot = ring + (i & 3) * kSlot, first = 1;
  load_frame<false>(va, (tid >> 4) & 0xfff0u, slot, tid);
  do {
    const uint32_t ia = i & 3;
    gemm<2, kOffAs, 6144>(x, va, d0);
    sfence(tid);
    affine<0>(r0, vb, B); affine<1>(r1, vb, B);
    load_frame<true>(vb, (tid >> 16) & 0xfff0u, slot, tid);
    uint64_t dp = dr + ia * (kSlot / 16);
    asm volatile("" : "+l"(dp));
    sfence(tid);
    o = ob + frame;
    finish<0, true>(r0, B, o, first, tid, B.light ? 28 : 0, tid);
    sfence(tid);
    wg_wait(); pin<24>(x);
    gemm<0, 0, kChunk>(sa, x, dp);
    if (!B.light) finish<1>(r1, B, o, first, 0, 0, tid);
    else if (sg == 0) {
      if ((tid & 31) == 0) {
        const uint32_t wn = window_ahead(ring, i, nfull, w);
        if (wn) tma_prefetch_win(tm, wn);
      }
      __syncwarp();
    }
    ob = out + (size_t)window_offset(w);
    sfence(tid);
    wg_wait(); pin<14>(sa);
    gemm<2, kOffAs, 6144>(x, vb, d1);
    ta = key48(sa, tid);
    rs = soft_exp(sa, ta);
    load_stats(A, ia, tid);
    sfence(tid);
    wg_wait(); pin<24>(x);
    gemm<0, kPlane, kChunk>(sc, x, dp);
    sfence(tid);
    soft_norm(sa, ta, rs, A, make_float2(low_f(A.e0), low_f(A.e1)), tid);
    sfence(tid);
    wg_wait(); pin<14>(sc);
    tb = key48(sc, tid);
    sfence(tid);
    soft_tail(sa, ta);
    gemm_u<0>(x, sa, dp);
    rs = soft_exp(sc, tb);
    load_stats(B, ia, tid);
    sfence(tid);
    wg_wait(); pin<24>(x);
    gemm<1, kOffWs, 6144>(va, x, d0);
    sfence(tid);
    soft_norm(sc, tb, rs, B, make_float2(low_f(B.e0), low_f(B.e1)), tid);
    soft_tail(sc, tb);
    sfence(tid);
    wg_wait(); pin<24>(va);
    gemm_u<kPlane>(x, sc, dp);
    sfence(tid);
    const uint32_t sn = ring + ((i + 1) & 3) * kSlot;
    const bool slow = mbar_pending_or<kWide - kDone>(sn + kDone, (i + 1) >> 2);
    affine<0>(r0, va, A);
    o = ob;
    finish<0>(r0, A, o, 0, tid, A.light ? 28 : 0, tid);
    sfence(tid);
    wg_wait(); pin<24>(x);
    gemm<1, kOffWs, 6144>(vb, x, d1);
    affine<1>(r1, va, A);
    if (slow || A.light) {
      if (A.light) release(ring, slot, i, nfull, w, tm, tid & 31);
      if (slow) {
        if (i + 1 < i1) mbar_wait(sn + kDone, (i + 1) >> 2);
        if (__any_sync(0xffffffffu, lds32(sn + kWide))) i1 = 0;
      }
    }
    const uint32_t la = (tid >> 4) & 0xfff0u;
    if (!A.light) { load_block(va, la, sn); finish<1>(r1, A, o, 0, la, 0x4000, tid); }
    else load_light(va, 2 * sg, sn, tid);
    wg_wait(); pin<24>(vb);
    launder<24>(vb);
    launder<24>(va);
    slot = sn; w += gridDim.x; first = 0;
  } while (++i < i1);
  o = ob + frame;
  affine<0>(r0, vb, B); finish<0>(r0, B, o, 0, tid, B.light ? 28 : 0, tid);
  affine<1>(r1, vb, B); finish<1>(r1, B, o, B.light, 0, 0, tid);
  return i;
}

__device__ __forceinline__ void run_S(uint32_t ring, uint64_t d0, uint64_t d1, uint32_t frame, uint32_t nfull, uint32_t i, uint32_t i1, uint32_t w0,
                                      int sg, int wp, const CUtensorMap* tm, uint8_t* __restrict__ out) {
  do {
    const uint32_t lane = fresh(threadIdx.x) & 31;
    const uint32_t slot = ring + (i & 3) * kSlot, w = w0 + i * gridDim.x;
    mbar_wait(slot + kDone, i >> 2);
    if (__any_sync(0xffffffffu, lds32(slot + kWide) | lds32(ring + kSlot + kExtra))) {
      round_wide(ring, d1, frame, nfull, i, w, sg, wp, lane, tm, out);
      i++;
    } else {
      i = rounds(ring, d0, d1, frame, nfull, i, i1, w, sg, wp, lane, tm, out);
    }
  } while (i < i1);
}

struct Maps { CUtensorMap load, prefetch; };
__global__ void __launch_bounds__(512, 1) swin_main(const __grid_constant__ Maps tms, uint8_t* __restrict__ out, const uint64_t d0,
                                                    const uint64_t d1, const uint32_t frame) {
  extern __shared__ __align__(1024) uint8_t smem[];
  const CUtensorMap& tm = tms.load;
  const uint32_t sb = smem_u32(smem), ring = sb + kWBytes;
  const int tid = threadIdx.x;
  const int wg = __shfl_sync(0xffffffffu, tid >> 7, 0);
  const int wp = __shfl_sync(0xffffffffu, (tid >> 5) & 3, 0);
  const int lane = tid & 31;
  const uint32_t b = blockIdx.x, nb = gridDim.x;
  const uint32_t nfull = kNWIN / nb, nrem = kNWIN - nfull * nb;
  if (tid == 0) {
    if (sb != 1024 || nfull > 700 || nfull < 12) __trap();
#pragma unroll
    for (int i = 0; i < 4; i++) {
      mbar_init(ring + i * kSlot + kFull, 1);
      mbar_init(ring + i * kSlot + kDone, 49);
      sts32(ring + i * kSlot + kRel, 0); sts32(ring + i * kSlot + kFlag, 0); sts32(ring + i * kSlot + kWide, 0);
    }
    asm volatile("fence.mbarrier_init.release.cluster;" ::: "memory");
    for (int i = 0; i < 2; i++) tma_load_win(ring + i * kSlot, &tm, b + i * nb);
  }
  __syncwarp();
  if (wg == 1 || wg == 2)
    asm volatile("st.shared.v4.b32 [%0], {%1,%1,%1,%1};" ::"r"(ring + ((tid - 128) >> 6) * kSlot + kXBytes + (tid & 63) * 16), "r"(0) : "memory");
  __syncthreads();
  asm volatile("griddepcontrol.wait;" ::: "memory");
#pragma unroll
  for (int q = 0; q < kWBytes / 16 / 512; q++)
    asm volatile("cp.async.cg.shared.global [%0], [%1], 16;" ::"r"(sb + (tid + q * 512) * 16), "l"(g_wimg + tid + q * 512) : "memory");
  if (wg == 0 && wp < 3) {
    static_assert(kWBytes / 16 == 9 * 512 + 96, "weight copy split");
    const int e = tid + 9 * 512;
    asm volatile("cp.async.cg.shared.global [%0], [%1], 16;" ::"r"(sb + e * 16), "l"(g_wimg + e) : "memory");
  }
  const float4 p0 = __ldcg(reinterpret_cast<const float4*>(&g_par));
  const float kb = __ldcg(&g_par.kb);
  TPar P;
  P.kt = p0.z;
  P.sgmin = fmaxf(0.0045f, kb * 0.011f);
  P.outmax = fmaf(kb, -627.2f, 60000.f);
  const bool scaled = __any_sync(0xffffffffu, p0.x != 1.f);
  const uint32_t pdir = __ballot_sync(0xffffffffu, scaled || !(P.kt <= 256.f));
  if (wg == 0) sts32(ring + kSlot + kExtra, p0.y != 1.f || p0.w != 1.f);
  asm volatile("cp.async.wait_all;\nfence.proxy.async.shared::cta;" ::: "memory");
  __syncthreads();
  if (tid == 128) for (int i = 2; i < 4; i++) tma_load_win(ring + i * kSlot, &tm, b + i * nb);
  __syncwarp();
  const bool isT = wg < 2;
  run_T(ring, d0, d1, nfull, nrem, !isT, wg, wp, lane, P, scaled, pdir);
  const uint32_t ex = isT ? __shfl_sync(0xffffffffu, lds32(ring + kExtra), 0) : 3;
  if ((ex >> (wg & 1)) & 1) run_S(ring, d0, d1, frame, nfull, isT ? nfull : 0, nfull + isT, isT ? (ex >> 2) - nfull * nb : b, wg & 1, wp, &tm, out);
}

__device__ __forceinline__ int ch_pos(int ch) { return 32 * (ch >> 5) + 16 * ((ch >> 2) & 1) + 8 * (ch & 1) + 2 * ((ch >> 3) & 3) + ((ch >> 1) & 1); }
__device__ __forceinline__ float pow2_ceil(float v) {
  return __uint_as_float((__float_as_uint(v) + 0x7fffffu) & 0x7f800000u);
}

constexpr int kPrepSplit = 12;
constexpr int kPrepThreads = 384;
__global__ void __launch_bounds__(kPrepThreads) swin_prep(const __nv_bfloat16* __restrict__ wqkv_t, const __nv_bfloat16* __restrict__ wo_t,
                                                          const __nv_bfloat16* __restrict__ wqkv_s, const __nv_bfloat16* __restrict__ wo_s) {
  asm volatile("griddepcontrol.launch_dependents;");
  __shared__ __align__(16) uint32_t raw[2][96][52];
  __shared__ __align__(16) uint32_t mu[3][52];
  __shared__ float nrm[12], nrm2[6], csum[6][9];
  const int mat = blockIdx.x / kPrepSplit, blk = blockIdx.x % kPrepSplit;
  const int tid = threadIdx.x, lane = tid & 31, warp = tid >> 5, g = lane >> 2, c = lane & 3;
  const __nv_bfloat16* wqkv = mat < 2 ? wqkv_t : wqkv_s;
  const __nv_bfloat16* wo = mat < 2 ? wo_t : wo_s;
  const bool isA = (mat & 1) == 0;
  {
    uint4 v[3], u[3];
#pragma unroll
    for (int q = 0; q < 3; q++) {
      const int e = tid + q * kPrepThreads, i = e / 12, c8 = (e % 12) * 8;
      v[q] = __ldg(reinterpret_cast<const uint4*>(wqkv + i * 288 + (isA ? 0 : 192) + c8));
      u[q] = __ldg(reinterpret_cast<const uint4*>(isA ? wqkv + i * 288 + 96 + c8 : wo + i * 96 + c8));
    }
#pragma unroll
    for (int q = 0; q < 3; q++) {
      const int e = tid + q * kPrepThreads, i = e / 12, c4 = (e % 12) * 4;
      *reinterpret_cast<uint4*>(&raw[0][i][c4]) = v[q];
      *reinterpret_cast<uint4*>(&raw[1][i][c4]) = u[q];
    }
  }
  __syncthreads();
  {
    const int m = warp / 6, cp = (warp % 6) * 8 + g;
    float s0 = 0.f, s1 = 0.f, q0 = 0.f, q1 = 0.f;
#pragma unroll
    for (int i = 0; i < 24; i++) {
      const uint32_t w = raw[m][4 * i + c][cp];
      const float lo = __uint_as_float(w << 16), hi = __uint_as_float(w & 0xffff0000u);
      s0 += lo; s1 += hi; q0 = fmaf(lo, lo, q0); q1 = fmaf(hi, hi, q1);
    }
    s0 = quad_sum(s0) * (1.f / 96.f); s1 = quad_sum(s1) * (1.f / 96.f); q0 = quad_sum(q0); q1 = quad_sum(q1);
    if (mat == 1 && m == 1) {
      float r0 = 0.f, r1 = 0.f;
#pragma unroll
      for (int i = 0; i < 12; i++) {
        const uint32_t w0 = raw[1][2 * cp][4 * i + c], w1 = raw[1][2 * cp + 1][4 * i + c];
        r0 += __uint_as_float(w0 << 16) + __uint_as_float(w0 & 0xffff0000u);
        r1 += __uint_as_float(w1 << 16) + __uint_as_float(w1 & 0xffff0000u);
      }
      r0 = quad_sum(r0) * (1.f / 96.f); r1 = quad_sum(r1) * (1.f / 96.f);
      s0 = r0; s1 = r1;
    }
    if (m == 1 && c == 0) {
      const uint32_t hi = mat == 3 ? 0u : pack_bf2(s0, s1);
      mu[0][cp] = hi;
      mu[1][cp] = mat == 3 ? 0u : pack_bf2(s0 - __uint_as_float(hi << 16), s1 - __uint_as_float(hi & 0xffff0000u));
      mu[2][cp] = 0u;
    }
    if (m == 0 || isA) {
      q0 = fmaxf(fmaf(-96.f * s0, s0, q0), 0.f) + q0 * 1e-6f;
      q1 = fmaxf(fmaf(-96.f * s1, s1, q1), 0.f) + q1 * 1e-6f;
    }
    const bool usemax = m == 1 && mat == 3;
    float t = usemax ? fmaxf(q0, q1) : q0 + q1;
#pragma unroll
    for (int o = 4; o < 32; o <<= 1) { const float z = __shfl_xor_sync(0xffffffffu, t, o); t = usemax ? fmaxf(t, z) : t + z; }
    if (lane == 0) nrm[warp] = t;
  }
  __syncthreads();
  if (warp >= 6) return;
  float d[4] = {0.f, 0.f, 0.f, 0.f}, e[4] = {0.f, 0.f, 0.f, 0.f}, v0, v1;
  {
    const uint32_t arow = smem_u32(&raw[0][16 * warp + (lane & 15)][(lane >> 4) * 4]);
    const uint32_t brow = isA ? smem_u32(&raw[1][blk * 8 + (lane & 7)][(lane >> 3) * 4]) : smem_u32(&raw[1][lane][blk * 4]);
    const uint32_t mrow = smem_u32(&mu[min(lane & 7, 2)][(lane >> 3) * 4]);
#pragma unroll
    for (int k2 = 0; k2 < 3; k2++) {
      uint32_t b[4], m[4];
      if (isA) ldsm4(b, brow + k2 * 64);
      else asm volatile("ldmatrix.sync.aligned.m8n8.x4.trans.shared.b16 {%0,%1,%2,%3}, [%4];"
                        : "=r"(b[0]), "=r"(b[1]), "=r"(b[2]), "=r"(b[3]) : "r"(brow + k2 * (32 * 208)) : "memory");
      ldsm4(m, mrow + k2 * 64);
#pragma unroll
      for (int hf = 0; hf < 2; hf++) {
        uint32_t a[4];
        ldsm4(a, arow + (2 * k2 + hf) * 32);
        asm volatile("mma.sync.aligned.m16n8k16.row.col.f32.bf16.bf16.f32 {%0,%1,%2,%3},{%4,%5,%6,%7},{%8,%9},{%0,%1,%2,%3};"
                     : "+f"(d[0]), "+f"(d[1]), "+f"(d[2]), "+f"(d[3])
                     : "r"(a[0]), "r"(a[1]), "r"(a[2]), "r"(a[3]), "r"(b[2 * hf]), "r"(b[2 * hf + 1]));
        asm volatile("mma.sync.aligned.m16n8k16.row.col.f32.bf16.bf16.f32 {%0,%1,%2,%3},{%4,%5,%6,%7},{%8,%9},{%0,%1,%2,%3};"
                     : "+f"(e[0]), "+f"(e[1]), "+f"(e[2]), "+f"(e[3])
                     : "r"(a[0]), "r"(a[1]), "r"(a[2]), "r"(a[3]), "r"(m[2 * hf]), "r"(m[2 * hf + 1]));
      }
    }
    v0 = __shfl_sync(0xffffffffu, e[0] + e[1], lane & ~3); v1 = __shfl_sync(0xffffffffu, e[2] + e[3], lane & ~3);
    d[0] -= v0; d[1] -= v0; d[2] -= v1; d[3] -= v1;
    float t0 = d[0] + d[2], t1 = d[1] + d[3], t2 = v0 + v1;
#pragma unroll
    for (int o = 4; o < 32; o <<= 1) {
      t0 += __shfl_xor_sync(0xffffffffu, t0, o); t1 += __shfl_xor_sync(0xffffffffu, t1, o); t2 += __shfl_xor_sync(0xffffffffu, t2, o);
    }
    if (g == 0) { csum[warp][2 * c] = t0; csum[warp][2 * c + 1] = t1; csum[warp][8] = t2; }
  }
  const float nl = nrm[0] + nrm[1] + nrm[2] + nrm[3] + nrm[4] + nrm[5];
  const float nr = mat == 3 ? fmaxf(fmaxf(fmaxf(nrm[6], nrm[7]), fmaxf(nrm[8], nrm[9])), fmaxf(nrm[10], nrm[11]))
                            : nrm[6] + nrm[7] + nrm[8] + nrm[9] + nrm[10] + nrm[11];
  const float bound = __fsqrt_rn(nl) * __fsqrt_rn(nr) * 1.01f;
  const float f = isA ? 0.14724448f : 1.f;
  float sc = pow2_ceil(fmaxf(bound * (isA ? 0.14724448f / 160.f : mat == 1 ? 1.f / 16.f : 1.f / 64.f), 1e-30f));
  if (isA) sc = fminf(fmaxf(sc, 1.f), 32768.f);
  if (mat == 3) {
    if (blk == 0 && tid == 0) { g_par.kb = sc; g_par.ticket = 0; }
    if (sc <= 1.f && sc >= 1.f / 1024.f) sc = 1.f;
  }
  const float mul = f * __uint_as_float(0x7f000000u - __float_as_uint(sc));
  if (blk == 0 && tid == 0) (mat == 0 ? g_par.cS_t : mat == 1 ? g_par.kt : mat == 2 ? g_par.cS_s : g_par.kappa) = sc;
  asm volatile("bar.sync 1, 192;" ::: "memory");
  float mean[2];
#pragma unroll
  for (int b = 0; b < 2; b++)
    mean[b] = (csum[0][2 * c + b] + csum[1][2 * c + b] + csum[2][2 * c + b] + csum[3][2 * c + b] + csum[4][2 * c + b] + csum[5][2 * c + b]) *
              (1.f / 96.f);
  uint8_t* img = reinterpret_cast<uint8_t*>(g_wimg) + (mat == 0 ? 0 : mat == 1 ? kOffWt : mat == 2 ? kOffAs : kOffWs);
  const float vmean = (csum[0][8] + csum[1][8] + csum[2][8] + csum[3][8] + csum[4][8] + csum[5][8]) * (1.f / 96.f);
  float q2 = 0.f;
#pragma unroll
  for (int q = 0; q < 4; q++) q2 = fmaf(d[q] - mean[q & 1], d[q] - mean[q & 1], q2);
#pragma unroll
  for (int o = 16; o; o >>= 1) q2 += __shfl_xor_sync(0xffffffffu, q2, o);
  if (lane == 0) nrm2[warp] = q2;
  asm volatile("bar.sync 1, 192;" ::: "memory");
  const float rms = __fsqrt_rn((nrm2[0] + nrm2[1] + nrm2[2] + nrm2[3] + nrm2[4] + nrm2[5]) * (1.f / 768.f)) * mul;
  const float big = 12582912.f * pow2_ceil(fmaxf(rms * (1.f / 256.f), 1e-30f));
  const float off = mat == 2 ? 1.5f * pow2_ceil(fmaxf(rms * 3.f, 1e-4f)) : 0.f;
#pragma unroll
  for (int q = 0; q < 4; q++) {
    const int kp = ch_pos(16 * warp + g + 8 * (q >> 1)), np = ch_pos(blk * 8 + 2 * c + (q & 1));
    const uint32_t ko = (kp >> 5) * (mat < 2 ? kAtChunk : 6144) + (kp & 31) * 2;
    uint32_t a = ko + np * 64;
    a ^= ((a >> 7) & 3) << 4;
    const float o = __fadd_rn(__fadd_rn((d[q] - mean[q & 1]) * mul, big), -big);
    *reinterpret_cast<__half*>(img + a) = __float2half_rn(o + off);
    if (mat == 1 && blk == 0) {
      a = (kp >> 5) * kAtChunk + (kp & 31) * 2 + (96 + 2 * c + (q & 1)) * 64;
      a ^= ((a >> 7) & 3) << 4;
      *reinterpret_cast<__half*>(reinterpret_cast<uint8_t*>(g_wimg) + a) = __float2half_rn((q & 1) ? ((q >> 1 ? v1 : v0) - vmean) * mul : 1.f / 96.f);
    }
  }
}

typedef CUresult (*EncodeFn)(CUtensorMap*, CUtensorMapDataType, cuuint32_t, void*, const cuuint64_t*, const cuuint64_t*,
                             const cuuint32_t*, const cuuint32_t*, CUtensorMapInterleave, CUtensorMapSwizzle,
                             CUtensorMapL2promotion, CUtensorMapFloatOOBfill);

}

extern "C" void kernel_launch(void* const* d_in, const int* in_sizes, int n_in, void* d_out, int out_size) {
  (void)in_sizes; (void)n_in; (void)out_size;
  static EncodeFn enc = nullptr;
  static int nsm = 0;
  if (!enc) {
    void* fn = nullptr;
    cudaDriverEntryPointQueryResult qr;
    cudaGetDriverEntryPoint("cuTensorMapEncodeTiled", &fn, cudaEnableDefault, &qr);
    enc = reinterpret_cast<EncodeFn>(fn);
    int dev = 0;
    cudaGetDevice(&dev);
    cudaDeviceGetAttribute(&nsm, cudaDevAttrMultiProcessorCount, dev);
    cudaFuncSetAttribute(swin_main, cudaFuncAttributeMaxDynamicSharedMemorySize, kSmemBytes);
  }
  Maps tms;
  CUtensorMap& tm = tms.load;
  const cuuint64_t dims[5] = {32, kW, kH, kT, 3};
  const cuuint64_t strides[4] = {192, 192ull * kW, 192ull * kW * kH, 64};
  const cuuint32_t box[5] = {32, 7, 7, 4, 3};
  const cuuint32_t es[5] = {1, 1, 1, 1, 1};
  enc(&tm, CU_TENSOR_MAP_DATA_TYPE_BFLOAT16, 5, d_in[0], dims, strides, box, es, CU_TENSOR_MAP_INTERLEAVE_NONE,
      CU_TENSOR_MAP_SWIZZLE_64B, CU_TENSOR_MAP_L2_PROMOTION_L2_128B, CU_TENSOR_MAP_FLOAT_OOB_FILL_NONE);

  const cuuint64_t dims2[3] = {24ull * kW, kH, kT};
  const cuuint64_t strides2[2] = {192ull * kW, 192ull * kW * kH};
  const cuuint32_t box2[3] = {168, 7, 4};
  enc(&tms.prefetch, CU_TENSOR_MAP_DATA_TYPE_UINT64, 3, d_in[0], dims2, strides2, box2, es, CU_TENSOR_MAP_INTERLEAVE_NONE,
      CU_TENSOR_MAP_SWIZZLE_NONE, CU_TENSOR_MAP_L2_PROMOTION_L2_128B, CU_TENSOR_MAP_FLOAT_OOB_FILL_NONE);

  cudaStream_t st = cudaStreamPerThread;
  swin_prep<<<4 * kPrepSplit, kPrepThreads, 0, st>>>(
      static_cast<const __nv_bfloat16*>(d_in[1]), static_cast<const __nv_bfloat16*>(d_in[2]),
      static_cast<const __nv_bfloat16*>(d_in[3]), static_cast<const __nv_bfloat16*>(d_in[4]));

  cudaLaunchConfig_t cfg = {};
  cfg.gridDim = dim3(nsm);
  cfg.blockDim = dim3(512);
  cfg.dynamicSmemBytes = kSmemBytes;
  cfg.stream = st;
  cudaLaunchAttribute at[1];
  at[0].id = cudaLaunchAttributeProgrammaticStreamSerialization;
  at[0].val.programmaticStreamSerializationAllowed = 1;
  cfg.attrs = at;
  cfg.numAttrs = 1;
  cudaLaunchKernelEx(&cfg, swin_main, tms, static_cast<uint8_t*>(d_out), mk_desc(1024), mk_desc(1024), (uint32_t)(kH * kW * 192));
}
```

```cpp
#include <cuda_runtime.h>
#include <cuda.h>
#include <cuda_bf16.h>
#include <cuda_fp16.h>
#include <stdint.h>

namespace {

constexpr int kH = 511, kW = 511, kT = 4;
constexpr int kNWX = 73, kNWIN = 73 * 73;
constexpr int kChunk = 12544;
constexpr int kPlane = 3136;
constexpr int kXBytes = 37632;
constexpr int kZero = kXBytes + 896, kFull = kXBytes + 1024, kDone = kFull + 8, kRel = kFull + 16, kFlag = kFull + 20, kExtra = kFull + 24,
              kWide = kFull + 28;
constexpr int kSlot = 38912;
constexpr int kWMat = 18432;
constexpr int kAtChunk = 200 * 64;
constexpr int kOffWt = 104 * 64;
constexpr int kOffAs = 3 * kAtChunk, kOffWs = kOffAs + kWMat;
constexpr int kWBytes = kOffWs + kWMat;
constexpr int kSmemBytes = kWBytes + 4 * kSlot;

struct Params {
  float cS_t, cS_s;
  float kt;
  float kappa;
  float kb;
  uint32_t ticket;
};

__device__ uint4 g_wimg[kWBytes / 16];
__device__ __align__(16) Params g_par;

__device__ __forceinline__ uint32_t smem_u32(const void* p) { return (uint32_t)__cvta_generic_to_shared(p); }
__device__ __forceinline__ void mbar_init(uint32_t a, int c) { asm volatile("mbarrier.init.shared::cta.b64 [%0], %1;" ::"r"(a), "r"(c)); }
__device__ __forceinline__ void mbar_expect(uint32_t a, int bytes) {
  asm volatile("mbarrier.arrive.expect_tx.shared::cta.b64 _, [%0], %1;" ::"r"(a), "r"(bytes) : "memory");
}
__device__ __forceinline__ void mbar_arrive(uint32_t a, uint32_t off = 0) {
  asm volatile("{\n.reg .pred p;\nsetp.eq.u32 p, %1, 0;\n@p mbarrier.arrive.shared::cta.b64 _, [%0];\n}" ::"r"(a), "r"(off) : "memory");
}
__device__ __forceinline__ void mbar_wait(uint32_t a, uint32_t par) {
  asm volatile(
      "{\n.reg .pred p;\n.reg .u32 n;\n"
      "mbarrier.try_wait.parity.shared::cta.b64 p, [%0], %1;\n"
      "@p bra.uni WDONE;\n"
      "mov.u32 n, 0;\n"
      "WLOOP:\n"
      "mbarrier.try_wait.parity.shared::cta.b64 p, [%0], %1;\n"
      "@p bra.uni WDONE;\n"
      "add.u32 n, n, 1;\n"
      "setp.lt.u32 p, n, 0x100000;\n"
      "@p bra.uni WLOOP;\n"
      "trap;\n"
      "WDONE:\n}" ::"r"(a), "r"(par & 1) : "memory");
}
template <int OFF>
__device__ __forceinline__ bool mbar_pending_or(uint32_t a, uint32_t par) {
  uint32_t r;
  asm volatile("{\n.reg .pred p;\n.reg .b32 t;\nmbarrier.test_wait.parity.shared::cta.b64 p, [%1], %2;\nld.shared.b32 t, [%1+%3];\n"
               "setp.ne.or.u32 p, t, 0, !p;\nvote.sync.any.pred p, p, 0xffffffff;\nselp.b32 %0, 1, 0, p;\n}"
               : "=r"(r) : "r"(a), "r"(par & 1), "n"(OFF) : "memory");
  return r;
}
__device__ __forceinline__ uint32_t lds32(uint32_t a) {
  uint32_t v; asm volatile("ld.shared.b32 %0, [%1];" : "=r"(v) : "r"(a) : "memory"); return v;
}
__device__ __forceinline__ void sts32(uint32_t a, uint32_t v) { asm volatile("st.shared.b32 [%0], %1;" ::"r"(a), "r"(v) : "memory"); }
__device__ __forceinline__ void tma_load_win(uint32_t slot, const CUtensorMap* m, uint32_t w) {
  const uint32_t wy = (w * 57457u) >> 22, wx = w - wy * kNWX;
  mbar_expect(slot + kFull, kXBytes);
  asm volatile(
      "cp.async.bulk.tensor.5d.shared::cluster.global.mbarrier::complete_tx::bytes [%0], [%1, {%3,%4,%5,%3,%3}], [%2];" ::"r"(slot),
      "l"(m), "r"(slot + kFull), "r"(0), "r"(wx * 7), "r"(wy * 7)
      : "memory");
}
__device__ __forceinline__ void tma_prefetch_win(const CUtensorMap* m, uint32_t w) {
  const uint32_t wy = (w * 57457u) >> 22, wx = w - wy * kNWX;
  asm volatile("cp.async.bulk.prefetch.tensor.3d.L2.global [%0, {%1,%2,%3}];" ::"l"(m + 1), "r"(wx * 168), "r"(wy * 7), "r"(0) : "memory");
}
__device__ __forceinline__ void wg_fence() { asm volatile("wgmma.fence.sync.aligned;" ::: "memory"); }
__device__ __forceinline__ void wg_commit() { asm volatile("wgmma.commit_group.sync.aligned;" ::: "memory"); }
__device__ __forceinline__ void wg_wait() { asm volatile("wgmma.wait_group.sync.aligned 0;" ::: "memory"); }
template <int N>
__device__ __forceinline__ void pin(uint32_t* d) {
#pragma unroll
  for (int i = 0; i < N; i++) asm volatile("" : "+r"(d[i])::"memory");
}
__device__ __forceinline__ uint32_t fresh(uint32_t v) { asm volatile("" : "+r"(v)); return v; }
__device__ __forceinline__ float fresh(float v) { asm volatile("" : "+f"(v)); return v; }
template <int N>
__device__ __forceinline__ void launder(uint32_t* q) {
#pragma unroll
  for (int j = 0; j < N; j++) { uint32_t t; asm volatile("mov.b32 %0, %1;" : "=r"(t) : "r"(q[j])); q[j] = t; }
}
__device__ __forceinline__ void sfence(uint32_t& v) {
  asm volatile("{\n.reg .pred p;\nsetp.eq.u32 p, %1, 0x7fffffff;\n@p mov.u32 %0, %%clock;\n}" : "+r"(v) : "r"(gridDim.x) : "memory");
}
constexpr uint64_t mk_desc(uint32_t addr) { return ((uint64_t)0x80000020u << 32) | (addr >> 4) | (1u << 16); }

#define R4(d, i) "+r"(d[i]), "+r"(d[i + 1]), "+r"(d[i + 2]), "+r"(d[i + 3])
#define O4(d, i) "=r"(d[i]), "=r"(d[i + 1]), "=r"(d[i + 2]), "=r"(d[i + 3])
#define D26 "{%0,%1,%2,%3,%4,%5,%6,%7,%8,%9,%10,%11,%12,%13,%14,%15,%16,%17,%18,%19,%20,%21,%22,%23,%24,%25},"
#define D24 "{%0,%1,%2,%3,%4,%5,%6,%7,%8,%9,%10,%11,%12,%13,%14,%15,%16,%17,%18,%19,%20,%21,%22,%23},"
#define D14 "{%0,%1,%2,%3,%4,%5,%6,%7,%8,%9,%10,%11,%12,%13},"

template <int SC, int TB>
__device__ __forceinline__ void wgmma(uint32_t (&d)[24], const uint32_t* a, uint64_t db) {
  if (SC == 2)
    asm volatile("{\n.reg .pred p;\nsetp.eq.u32 p, %30, 0x7fffffff;\n"
                 "wgmma.mma_async.sync.aligned.m64n96k16.f16.f16.f16 " D24 "{%24,%25,%26,%27}, %28, p, 1, 1, %29;\n}"
                 : R4(d, 0), R4(d, 4), R4(d, 8), R4(d, 12), R4(d, 16), R4(d, 20)
                 : "r"(a[0]), "r"(a[1]), "r"(a[2]), "r"(a[3]), "l"(db), "n"(TB), "r"(gridDim.x));
  else if (SC)
    asm volatile("wgmma.mma_async.sync.aligned.m64n96k16.f16.f16.f16 " D24 "{%24,%25,%26,%27}, %28, 1, 1, 1, %29;"
                 : R4(d, 0), R4(d, 4), R4(d, 8), R4(d, 12), R4(d, 16), R4(d, 20)
                 : "r"(a[0]), "r"(a[1]), "r"(a[2]), "r"(a[3]), "l"(db), "n"(TB));
  else
    asm volatile("wgmma.mma_async.sync.aligned.m64n96k16.f16.f16.f16 " D24 "{%24,%25,%26,%27}, %28, 0, 1, 1, %29;"
                 : O4(d, 0), O4(d, 4), O4(d, 8), O4(d, 12), O4(d, 16), O4(d, 20)
                 : "r"(a[0]), "r"(a[1]), "r"(a[2]), "r"(a[3]), "l"(db), "n"(TB));
}
template <int SC, int TB>
__device__ __forceinline__ void wgmma(uint32_t (&d)[26], const uint32_t* a, uint64_t db) {
  if (SC)
    asm volatile("wgmma.mma_async.sync.aligned.m64n104k16.f16.f16.f16 " D26 "{%26,%27,%28,%29}, %30, 1, 1, 1, 0;"
                 : R4(d, 0), R4(d, 4), R4(d, 8), R4(d, 12), R4(d, 16), R4(d, 20), "+r"(d[24]), "+r"(d[25])
                 : "r"(a[0]), "r"(a[1]), "r"(a[2]), "r"(a[3]), "l"(db));
  else
    asm volatile("wgmma.mma_async.sync.aligned.m64n104k16.f16.f16.f16 " D26 "{%26,%27,%28,%29}, %30, 0, 1, 1, 0;"
                 : O4(d, 0), O4(d, 4), O4(d, 8), O4(d, 12), O4(d, 16), O4(d, 20), "=r"(d[24]), "=r"(d[25])
                 : "r"(a[0]), "r"(a[1]), "r"(a[2]), "r"(a[3]), "l"(db));
}
template <int SC, int TB>
__device__ __forceinline__ void wgmma(uint32_t (&d)[16], const uint32_t* a, uint64_t db) {
  if (SC)
    asm volatile("wgmma.mma_async.sync.aligned.m64n56k16.f16.f16.f16 " D14 "{%14,%15,%16,%17}, %18, 1, 1, 1, 0;"
                 : R4(d, 0), R4(d, 4), R4(d, 8), "+r"(d[12]), "+r"(d[13])
                 : "r"(a[0]), "r"(a[1]), "r"(a[2]), "r"(a[3]), "l"(db));
  else
    asm volatile("wgmma.mma_async.sync.aligned.m64n56k16.f16.f16.f16 " D14 "{%14,%15,%16,%17}, %18, 0, 1, 1, 0;"
                 : O4(d, 0), O4(d, 4), O4(d, 8), "=r"(d[12]), "=r"(d[13])
                 : "r"(a[0]), "r"(a[1]), "r"(a[2]), "r"(a[3]), "l"(db));
}
template <int SC, int OFF, int CH, int ND>
__device__ __forceinline__ void gemm(uint32_t (&d)[ND], const uint32_t* a, uint64_t db) {
  asm volatile("" : "+l"(db));
  wg_fence();
  wgmma<SC, 0>(d, a, db + OFF / 16);
#pragma unroll
  for (int k = 1; k < 6; k++) wgmma<1, 0>(d, a + 4 * k, db + (OFF + (k >> 1) * CH + (k & 1) * 32) / 16);
  wg_commit();
}
__device__ __forceinline__ void lds128(uint32_t* r, uint32_t a) {
  asm volatile("ld.shared.v4.b32 {%0,%1,%2,%3}, [%4];" : "=r"(r[0]), "=r"(r[1]), "=r"(r[2]), "=r"(r[3]) : "r"(a) : "memory");
}
__device__ __forceinline__ void ldsm4(uint32_t* r, uint32_t a) {
  asm volatile("ldmatrix.sync.aligned.m8n8.x4.shared.b16 {%0,%1,%2,%3}, [%4];"
               : "=r"(r[0]), "=r"(r[1]), "=r"(r[2]), "=r"(r[3]) : "r"(a) : "memory");
}
__device__ __forceinline__ void stsm4(uint32_t a, const uint32_t* r) {
  asm volatile("stmatrix.sync.aligned.m8n8.x4.shared.b16 [%0], {%1,%2,%3,%4};" ::"r"(a), "r"(r[0]), "r"(r[1]), "r"(r[2]), "r"(r[3])
               : "memory");
}
__device__ __forceinline__ void stg3(uint8_t* p, const uint32_t* r, uint32_t off) {
  asm volatile("{\n.reg .pred p;\nsetp.eq.u32 p, %13, 0;\n@p st.global.v4.b32 [%0], {%1,%2,%3,%4};\n"
               "@p st.global.v4.b32 [%0+64], {%5,%6,%7,%8};\n@p st.global.v4.b32 [%0+128], {%9,%10,%11,%12};\n}" ::"l"(p),
               "r"(r[0]), "r"(r[1]), "r"(r[2]), "r"(r[3]), "r"(r[4]), "r"(r[5]), "r"(r[6]), "r"(r[7]), "r"(r[8]), "r"(r[9]), "r"(r[10]), "r"(r[11]),
               "r"(off) : "memory");
}
__device__ __forceinline__ uint32_t pack_h2(float lo, float hi) {
  uint32_t r; asm("cvt.rn.f16x2.f32 %0, %1, %2;" : "=r"(r) : "f"(hi), "f"(lo)); return r;
}
__device__ __forceinline__ uint32_t pack_h2_sat(float lo, float hi) {
  uint32_t r; asm("cvt.rn.satfinite.f16x2.f32 %0, %1, %2;" : "=r"(r) : "f"(hi), "f"(lo)); return r;
}
__device__ __forceinline__ uint32_t pack_bf2(float lo, float hi) {
  uint32_t r; asm("cvt.rn.bf16x2.f32 %0, %1, %2;" : "=r"(r) : "f"(hi), "f"(lo)); return r;
}
__device__ __forceinline__ __half2 as_h2(uint32_t v) { return *reinterpret_cast<__half2*>(&v); }
__device__ __forceinline__ uint32_t as_u(__half2 v) { return *reinterpret_cast<uint32_t*>(&v); }
__device__ __forceinline__ float2 unpack_h2(uint32_t v) { return __half22float2(as_h2(v)); }
__device__ __forceinline__ float low_f(uint32_t v) { return __low2float(as_h2(v)); }
__device__ __forceinline__ uint32_t h2ex2(uint32_t v) { uint32_t r; asm("ex2.approx.f16x2 %0, %1;" : "=r"(r) : "r"(v)); return r; }
__device__ __forceinline__ uint32_t h2max(uint32_t a, uint32_t b) { return as_u(__hmax2(as_h2(a), as_h2(b))); }
__device__ __forceinline__ uint32_t h2add(uint32_t a, uint32_t b) { return as_u(__hadd2(as_h2(a), as_h2(b))); }
__device__ __forceinline__ uint32_t h2sub(uint32_t a, uint32_t b) { return as_u(__hsub2(as_h2(a), as_h2(b))); }
__device__ __forceinline__ uint32_t h2mul(uint32_t a, uint32_t b) { return as_u(__hmul2(as_h2(a), as_h2(b))); }
__device__ __forceinline__ uint32_t h2neg(uint32_t a) { return as_u(__hneg2(as_h2(a))); }
__device__ __forceinline__ uint32_t h2fma(uint32_t a, uint32_t b, uint32_t c) { return as_u(__hfma2(as_h2(a), as_h2(b), as_h2(c))); }
__device__ __forceinline__ uint32_t lo2(uint32_t v) { return as_u(__low2half2(as_h2(v))); }
__device__ __forceinline__ uint32_t hi2(uint32_t v) { return as_u(__high2half2(as_h2(v))); }
__device__ __forceinline__ uint32_t fold_add(uint32_t a, uint32_t b) { return h2add(__byte_perm(a, b, 0x5410), __byte_perm(a, b, 0x7632)); }
__device__ __forceinline__ uint32_t sel(uint32_t p, uint32_t a, uint32_t b) {
  uint32_t r; asm("{\n.reg .pred p;\nsetp.ne.u32 p, %3, 0;\nselp.b32 %0, %1, %2, p;\n}" : "=r"(r) : "r"(a), "r"(b), "r"(p)); return r;
}
__device__ __forceinline__ float sel4(uint32_t c, float a0, float a1, float a2, float a3) {
  return __uint_as_float(sel(c & 2, sel(c & 1, __float_as_uint(a3), __float_as_uint(a2)), sel(c & 1, __float_as_uint(a1), __float_as_uint(a0))));
}
__device__ __forceinline__ float rcp_fast(float v) { float r; asm("rcp.approx.ftz.f32 %0, %1;" : "=f"(r) : "f"(v)); return r; }
__device__ __forceinline__ float rsq_fast(float v) { float r; asm("rsqrt.approx.ftz.f32 %0, %1;" : "=f"(r) : "f"(v)); return r; }
__device__ __forceinline__ uint32_t shfl_x(uint32_t v, int m) { return __shfl_xor_sync(0xffffffffu, v, m); }
__device__ __forceinline__ uint32_t shfl_q(uint32_t v, int i) { return __shfl_sync(0xffffffffu, v, i, 4); }
__device__ __forceinline__ float quad_sum(float v) {
  v += __shfl_xor_sync(0xffffffffu, v, 1);
  return v + __shfl_xor_sync(0xffffffffu, v, 2);
}
__device__ __forceinline__ uint32_t score_scale(const float* p) { const float v = __ldcg(p); return pack_h2(v, v); }

constexpr float kEps96 = 1e-5f * 96.f * 96.f;
__device__ __forceinline__ float2 stat_f32(uint32_t e) {
  const float2 h = unpack_h2(e);
  return make_float2(__uint_as_float(sel(e & 0x8000u, (e << 16) & 0x7fff0000u, __float_as_uint(h.x))),
                     __uint_as_float(sel(e & 0x8000u, e & 0xffff0000u, __float_as_uint(h.y))));
}

struct Tile {
  uint32_t ring, a;
  uint32_t next;
  uint32_t n;
  int live;
  uint32_t stat, wrap;
  uint32_t flag;
  uint32_t gate;
};
struct TPar { float kt, sgmin, outmax; };

__device__ __forceinline__ uint32_t swz(uint32_t r, int t) { return fresh(r ^ (((r >> 3) + 8 * t) & 0x30)); }
__device__ __forceinline__ void load_rows(uint32_t* x0, uint32_t* x1, uint32_t ring, uint32_t r, int t) {
  const uint32_t a0 = swz(r, t), a1 = swz(r, t + 1), u0 = ring + t * kPlane, u1 = u0 + kPlane;
  lds128(x0, a0 + u0); lds128(x1, a1 + u1);
  lds128(x0 + 4, fresh(a0 ^ 32) + (u0 + kChunk)); lds128(x1 + 4, fresh(a1 ^ 32) + (u1 + kChunk));
  lds128(x0 + 8, a0 + (u0 + 2 * kChunk)); lds128(x1 + 8, a1 + (u1 + 2 * kChunk));
}
__device__ __forceinline__ void to_half(uint32_t (&z)[24], const uint32_t* x, int o0, int o1) {
#pragma unroll
  for (int j = 0; j < 24; j += 2) {
    const int o = j < 12 ? 2 * j : 2 * j - 23;
    if (o < o0 || o >= o1) continue;
    uint32_t t;
    asm("cvt.rz.f16x2.f32 %0, %1, %2;" : "=r"(t) : "f"(__uint_as_float(x[j + 1])), "f"(__uint_as_float(x[j])));
    z[o] = fresh(pack_h2(__uint_as_float(x[j] << 16), __uint_as_float(x[j + 1] << 16)));
    z[o + 2] = fresh(t & 0xfff8fff8u);
  }
}
__device__ __forceinline__ void load_general(uint32_t (&z)[24], uint32_t ring, uint32_t r, int t, float& ie0, float& ie1, float& m0, float& m1) {
  float acc[48];
  uint32_t x0[12], x1[12];
  load_rows(x0, x1, ring, r, t);
#pragma unroll
  for (int j = 0; j < 12; j++) {
    acc[4 * j] = __uint_as_float(x0[j] << 16); acc[4 * j + 1] = __uint_as_float(x0[j] & 0xffff0000u);
    acc[4 * j + 2] = __uint_as_float(x1[j] << 16); acc[4 * j + 3] = __uint_as_float(x1[j] & 0xffff0000u);
  }
  float s[4], q[4];
#pragma unroll
  for (int e = 0; e < 4; e++) { s[e] = acc[e]; q[e] = acc[e] * acc[e]; }
#pragma unroll
  for (int j = 4; j < 48; j++) { s[j & 3] += acc[j]; q[j & 3] = fmaf(acc[j], acc[j], q[j & 3]); }
  const float s0 = quad_sum(s[0] + s[1]), s1 = quad_sum(s[2] + s[3]), q0 = quad_sum(q[0] + q[1]), q1 = quad_sum(q[2] + q[3]);
  const float u0 = rsq_fast(fmaxf(fmaf(-s0, s0, fmaf(q0, 96.f, kEps96)), kEps96));
  const float u1 = rsq_fast(fmaxf(fmaf(-s1, s1, fmaf(q1, 96.f, kEps96)), kEps96));
  const float n0 = -s0 * u0, n1 = -s1 * u1;
  ie0 = 96.f * u0; ie1 = 96.f * u1;
  m0 = s0 * (1.f / 96.f); m1 = s1 * (1.f / 96.f);
#pragma unroll
  for (int j = 0; j < 12; j++) {
    const int o = 8 * (j >> 1) + (j & 1);
    z[2 * j] = pack_h2(fmaf(acc[o], ie0, n0), fmaf(acc[o + 4], ie0, n0));
    z[2 * j + 1] = pack_h2(fmaf(acc[o + 2], ie1, n1), fmaf(acc[o + 6], ie1, n1));
  }
}
template <bool kDown>
__device__ __forceinline__ uint32_t sumsq2(const uint32_t* z) {
  uint32_t q0, q1;
#pragma unroll
  for (int j = 0; j < 12; j++) {
    const uint32_t u = kDown ? h2mul(z[2 * j], 0x1c001c00u) : z[2 * j], v = kDown ? h2mul(z[2 * j + 1], 0x1c001c00u) : z[2 * j + 1];
    q0 = j ? h2fma(u, u, q0) : h2mul(u, u); q1 = j ? h2fma(v, v, q1) : h2mul(v, v);
  }
  return fold_add(q0, q1);
}
template <bool kDown>
__device__ __forceinline__ float row_sumsq(const uint32_t* z0, const uint32_t* z1, uint32_t c) {
  const uint32_t a = sumsq2<kDown>(z0), b = sumsq2<kDown>(z1);
  uint32_t t = h2add(sel(c & 2, b, a), shfl_x(sel(c & 2, a, b), 2));
  t = h2add(t, shfl_x(t, 1));
  return low_f(sel(c & 1, t >> 16, t));
}
__device__ __forceinline__ void scores2(const uint32_t* q, const uint32_t* z0, const uint32_t* z1, uint32_t* f) {
  uint32_t d[8];
#pragma unroll
  for (int j = 0; j < 12; j++) {
    const uint32_t kk[4] = {z0[2 * j], z0[2 * j + 1], z1[2 * j], z1[2 * j + 1]};
#pragma unroll
    for (int e = 0; e < 4; e++) {
      d[e] = j ? h2fma(q[2 * j], kk[e], d[e]) : h2mul(q[2 * j], kk[e]);
      d[4 + e] = j ? h2fma(q[2 * j + 1], kk[e], d[4 + e]) : h2mul(q[2 * j + 1], kk[e]);
    }
  }
#pragma unroll
  for (int e = 0; e < 4; e++) f[e] = fold_add(d[2 * e], d[2 * e + 1]);
}
struct Xch { uint32_t keep[2], got[2]; };
__device__ __forceinline__ Xch pair_send(const uint32_t* a, const uint32_t* b, uint32_t c, int m) {
  Xch x;
#pragma unroll
  for (int e = 0; e < 2; e++) { x.keep[e] = fresh(sel(c & m, b[e], a[e])); x.got[e] = shfl_x(sel(c & m, a[e], b[e]), m); }
  return x;
}
__device__ __forceinline__ void pair_recv(uint32_t* k, const Xch& x) { k[0] = h2add(x.keep[0], x.got[0]); k[1] = h2add(x.keep[1], x.got[1]); }
__device__ __forceinline__ void mix2(uint32_t* y, const uint32_t* v, uint32_t c0, uint32_t c1) {
#pragma unroll
  for (int j = 0; j < 12; j++) {
    y[2 * j] = h2fma(v[2 * j + 1], hi2(c0), h2fma(v[2 * j], lo2(c0), y[2 * j]));
    y[2 * j + 1] = h2fma(v[2 * j + 1], hi2(c1), h2fma(v[2 * j], lo2(c1), y[2 * j + 1]));
  }
  pin<24>(y);
}
__device__ __forceinline__ void norm_store(uint32_t* y, uint32_t r0, uint32_t r1, uint32_t r, int t) {
#pragma unroll
  for (int j = 0; j < 12; j++) { y[2 * j] = h2fma(y[2 * j], lo2(r0), hi2(r0)); y[2 * j + 1] = h2fma(y[2 * j + 1], lo2(r1), hi2(r1)); }
  const uint32_t ma = swz(r, t), mb = fresh(ma ^ 32), u = t * kPlane;
  stsm4(ma + u, y); stsm4(mb + u, y + 4);
  stsm4(mb + (u + kChunk), y + 8); stsm4(ma + (u + kChunk), y + 12);
  stsm4(ma + (u + 2 * kChunk), y + 16); stsm4(mb + (u + 2 * kChunk), y + 20);
}

template <bool kAlways>
__device__ __forceinline__ void gate_open(uint32_t id) {
  if (kAlways) asm volatile("barrier.cta.arrive.aligned %0, 256;" ::"r"(id) : "memory");
  else asm volatile("{\n.reg .pred p;\nsetp.ne.u32 p, %0, 0;\n@p barrier.cta.arrive.aligned %0, 256;\n}" ::"r"(id) : "memory");
}

struct TState { uint32_t z0[24], z1[24], mu, bad; float ie, mm, mz, qq; };
template <bool kDirect>
__device__ __forceinline__ void temporal(TState& S, uint64_t da, const Tile& T, const TPar& P, bool scaled, uint32_t lane, uint32_t& lst) {
  uint32_t (&z0)[24] = S.z0, (&z1)[24] = S.z1;
  const uint32_t c = lane;
  const uint32_t a0 = T.a + lane * 16 + (lane >= 4 * T.n ? T.next : 0);
  uint32_t q0[26], q1[24], v0[24], w1[26], nn = 0, ng = 0, ca0 = 0, ca1 = 0;
  uint32_t* const v1 = w1 + 2;
  float ie = 1.f, mm = 0.f;
  bool tiny = false;
  if (kDirect) {
    uint32_t x[48];
    load_rows(x, x + 12, T.ring, a0, 0);
    to_half(z0, x, 0, 16);
    sfence(lst);
    load_rows(x + 24, x + 36, T.ring, a0, 2);
    to_half(z0, x, 16, 24);
    gemm<0, 0, kAtChunk>(q0, z0, da);
    sfence(lst);
    to_half(z1, x + 24, 0, 24);
    const uint32_t n0 = sumsq2<false>(z0), n1 = sumsq2<false>(z1);
    nn = fresh(sel(c & 2, n1, n0)); ng = shfl_x(sel(c & 2, n0, n1), 2);
    pin<24>(z1); sfence(lst);
  } else {
    float e[4], m[4];
    load_general(z0, T.ring, a0, 0, e[0], e[1], m[0], m[1]);
    pin<24>(z0); sfence(lst);
    load_general(z1, T.ring, a0, 2, e[2], e[3], m[2], m[3]);
    ie = sel4(c, e[0], e[1], e[2], e[3]);
    mm = sel4(c, m[0], m[1], m[2], m[3]);
    tiny = __any_sync(0xffffffffu, ie * P.kt > 400.f);
    if (tiny) {
      float u = 0.f;
#pragma unroll
      for (int r = 0; r < 4; r++) {
        float t = 0.f;
#pragma unroll
        for (int j = 0; j < 12; j++) { const float2 f = unpack_h2((r & 2 ? z1 : z0)[2 * j + (r & 1)]); t = fmaf(f.x, f.x, fmaf(f.y, f.y, t)); }
        u = fmaxf(u, quad_sum(t));
      }
      const float t = fminf(ie, 9.8f * rsq_fast(fmaxf(u, 2e-7f)) * rcp_fast(fresh(P.kt)));
      const uint32_t a = pack_h2(__fdividef(t, ie), 0.f);
      ca0 = __byte_perm(shfl_q(a, 0), shfl_q(a, 1), 0x5410); ca1 = __byte_perm(shfl_q(a, 2), shfl_q(a, 3), 0x5410);
      ie = t;
    }
    gemm<0, 0, kAtChunk>(q0, z0, da);
  }
  uint32_t f[4], k0[2], k1[2], sk[2];
  wg_wait(); pin<26>(q0);
  gemm<0, 0, kAtChunk>(q1, z1, da);
  gate_open<kDirect>(T.gate);
  sfence(lst);
  if (kDirect) { nn = h2add(nn, ng); ng = shfl_x(nn, 1); sfence(lst); }
  scores2(q0, z0, z1, f);
  const uint32_t nu0 = fresh(__byte_perm(q0[24], q0[25], 0x7632)), m01 = fresh(sel(c & 1, q0[25], q0[24]));
  Xch xc = pair_send(f, f + 2, c, 1);
  sfence(lst);
  wg_wait(); pin<24>(q1);
  gemm<0, kOffWt - 512, kAtChunk>(w1, z1, da);
  sfence(lst);
  pair_recv(k0, xc);
  float e2 = 0.f, lim = 0.f;
  if (kDirect) {
    nn = h2add(nn, ng);
    e2 = fresh(fmaf(low_f(sel(c & 1, nn >> 16, nn)), 1.f / 96.f, 1e-5f));
    lim = fresh(e2 <= 4.f ? fmaxf(0.5f * e2, 4e-4f) : __uint_as_float(0x7fffffffu));
  }
  scores2(q1, z0, z1, f);
  xc = pair_send(f, f + 2, c, 1);
  pin<2>(k0); sfence(lst);
  wg_wait(); pin<26>(w1);
  float mz = 0.f, d2 = 0.f;
  if (kDirect) {
    mz = low_f(sel(c & 2, sel(c & 1, w1[1], w1[0]), m01));
    d2 = fmaf(-mz, mz, e2);
    asm volatile("{\n.reg .pred p;\nsetp.lt.s32 p, %3, %4;\nsetp.ltu.and.f32 p, %1, %2, p;\n@p st.volatile.shared.f32 [%0], %2;\n}" ::"r"(T.flag), "f"(d2),
                 "f"(lim), "r"(lane), "r"(T.live) : "memory");
  }
  gemm<0, kOffWt, kAtChunk>(v0, z0, da);
  sfence(lst);
  uint32_t cw[8], mu;
  {
    uint32_t rc = 0, r0 = 0, r1 = 0;
    if (kDirect) {
      const float r = rsq_fast(d2);
      rc = pack_h2(r, r);
      r0 = __byte_perm(shfl_q(rc, 0), shfl_q(rc, 1), 0x5410); r1 = __byte_perm(shfl_q(rc, 2), shfl_q(rc, 3), 0x5410);
    }
    pair_recv(k1, xc);
    pair_recv(sk, pair_send(k0, k1, c, 2));
    if (kDirect) { sk[0] = h2mul(sk[0], r0); sk[1] = h2mul(sk[1], r1); }
    uint32_t mx = h2max(sk[0], sk[1]);
    mx = h2max(lo2(mx), hi2(mx));
    if (kDirect) {
      const uint32_t nm = h2mul(h2neg(mx), rc);
      sk[0] = h2fma(sk[0], rc, nm); sk[1] = h2fma(sk[1], rc, nm);
    } else {
      sk[0] = h2sub(sk[0], mx); sk[1] = h2sub(sk[1], mx);
      if (scaled) {
        const uint32_t cs = score_scale(&g_par.cS_t);
        sk[0] = h2mul(sk[0], cs); sk[1] = h2mul(sk[1], cs);
      }
    }
    sk[0] = h2ex2(sk[0]); sk[1] = h2ex2(sk[1]);
    const uint32_t sm = h2add(sk[0], sk[1]);
    const float iv = (kDirect ? P.kt : P.kt * ie) * rcp_fast(low_f(h2add(lo2(sm), hi2(sm))));
    const uint32_t inv = pack_h2(iv, iv);
    if (kDirect) { sk[0] = h2mul(sk[0], r0); sk[1] = h2mul(sk[1], r1); }
    sk[0] = h2mul(sk[0], inv); sk[1] = h2mul(sk[1], inv);
#pragma unroll
    for (int i = 0; i < 4; i++) { cw[2 * i] = shfl_q(sk[0], i); cw[2 * i + 1] = shfl_q(sk[1], i); }
    mu = h2fma(sk[1], __byte_perm(w1[0], w1[1], 0x7632), h2mul(sk[0], nu0));
    mu = h2add(lo2(mu), hi2(mu));
  }
  uint32_t bad = 0;
  if (kDirect) {
    mix2(z1, v1, cw[5], cw[7]);
    sfence(lst);
    wg_wait(); pin<24>(v0);
    mix2(z1, v0, cw[4], cw[6]);
    sfence(lst);
    bad = lds32(T.flag);
  } else {
    wg_wait(); pin<24>(v0);
    if (tiny) {
#pragma unroll
      for (int j = 0; j < 12; j++) {
        z0[2 * j] = h2mul(z0[2 * j], lo2(ca0)); z0[2 * j + 1] = h2mul(z0[2 * j + 1], hi2(ca0));
        z1[2 * j] = h2mul(z1[2 * j], lo2(ca1)); z1[2 * j + 1] = h2mul(z1[2 * j + 1], hi2(ca1));
      }
    }
    mix2(z1, v1, cw[5], cw[7]);
    mix2(z1, v0, cw[4], cw[6]);
  }
  mix2(z0, v1, cw[1], cw[3]);
  mix2(z0, v0, cw[0], cw[2]);
  S.qq = row_sumsq<false>(z0, z1, c);
  S.mu = mu; S.bad = bad; S.ie = ie; S.mm = mm; S.mz = mz;
}
__device__ __forceinline__ bool irregular(const TState& S, const Tile& T, uint32_t lane) {
  return __any_sync(0xffffffffu, (!(S.qq < 65000.f) & ((int)lane < T.live)) | (S.bad != 0));
}
__device__ __forceinline__ void resum(TState& S, uint32_t lane) {
  const float q2 = row_sumsq<true>(S.z0, S.z1, lane) * 65536.f;
  S.qq = S.qq < 65000.f ? S.qq : q2;
}
template <bool kDirect>
__device__ __forceinline__ void temporal_out(TState& S, const Tile& T, uint32_t slot, const TPar& P, uint32_t lane, uint32_t lst) {
  uint32_t (&z0)[24] = S.z0, (&z1)[24] = S.z1;
  const uint32_t mu = S.mu;
  const float ie = S.ie, mz = S.mz, qq = S.qq;
  float mm = S.mm;
  const float rf = kDirect ? rsq_fast(fmaxf(fmaf(-mz, mz, fmaf(qq, 1.f / 96.f, 1e-5f)), 1e-5f)) : rsq_fast(fmaf(qq, 1.f / 96.f, 1e-5f * ie * ie));
  const uint32_t rn = pack_h2_sat(rf, -mz * rf);
  uint32_t rr[4];
#pragma unroll
  for (int i = 0; i < 4; i++) rr[i] = shfl_q(rn, i);
  lane = fresh(lane);
  const uint32_t ma = fresh(T.ring + T.a) + lst + ((lane & 7) >= T.n ? T.next : 0);
  norm_store(z0, rr[0], rr[1], ma, 0);
  const float2 rm = unpack_h2(rn);
  const float sg = rcp_fast(kDirect ? rm.x : rm.x * ie);
  mm = kDirect ? fmaf(-rm.y, sg, low_f(mu)) : fmaf(low_f(mu) * rm.x, sg, mm);
  const uint32_t bars = slot + (lane >= 4 * T.n ? T.next + kPlane : 0);
  const bool ok = (sg >= P.sgmin) & (fmaf(sg, 9.8f, fabsf(mm)) < P.outmax);
  asm volatile("{\n.reg .pred p;\nsetp.lt.s32 p, %2, %3;\n@p st.shared.b32 [%0], %1;\n}" ::"r"(
                   T.stat + fresh((lane & 3) * (kSlot - 1) + lane + (lane >= 4 * T.n ? T.wrap : 0))),
               "r"(sel(ok, pack_h2(sg, mm), pack_bf2(sg, mm) | 0x8000u)), "r"(lane), "r"(T.live) : "memory");
  asm volatile("{\n.reg .pred p;\nsetp.eq.u32 p, %1, 0;\n@p st.shared.b32 [%0], %0;\n}" ::"r"(bars + kWide), "r"((uint32_t)ok) : "memory");
  norm_store(z1, rr[2], rr[3], ma, 2);
}

__device__ __forceinline__ void run_T(uint32_t ring, uint64_t d0, uint64_t d1, uint32_t nfull, uint32_t nrem, bool helper, int wg, int wp, uint32_t lane,
                                      const TPar& P, bool scaled, uint32_t pdir) {
  uint32_t lst = (lane & 7) * 64 + (lane & 8) * (kPlane / 8) + (lane & 16);
  uint32_t p0 = 32 * (wg & 1) + (helper ? 0 : 64) + 8 * wp;
  uint32_t npx = 49 * nfull, pstop = npx - 6 * 49 + 8 * wp;
  if (helper) pstop = 0;
  uint32_t pgap = 0;
  sfence(lane);
  Tile T;
  T.ring = ring;
  T.flag = ring + wg * kSlot + kFlag;
  T.gate = wg == 3 ? 6 : 5 + wg;
  while (true) {
    const uint32_t iw = (p0 * 21400u) >> 20, ow = p0 - 49 * iw;
    const uint32_t slot = ring + (iw & 3) * kSlot, dn = (iw & 3) == 3 ? -3 * kSlot : kSlot;
    asm volatile("{\n.reg .pred p;\nsetp.eq.u32 p, %1, 0;\n@p barrier.cta.sync.aligned %0, 256;\n}" ::"r"(6 - (wg & 1)), "r"((uint32_t)helper) : "memory");
    mbar_wait(slot + kFull, iw >> 2);
    if (ow > 41) mbar_wait(slot + dn + kFull, (iw + 1) >> 2);
    T.a = (iw & 3) * kSlot + ow * 64; T.next = dn - kPlane; T.n = 49 - ow;
    T.live = 4 * (npx - p0);
    T.stat = ring + kXBytes + (p0 - 196 * (iw >> 2)) * 4; T.wrap = (iw & 3) == 3 ? -784 : 0;
    lane = fresh(lane);
    {
      TState S;
      Tile G = T;
      if (p0 >= pdir) {
        temporal<true>(S, d0, T, P, false, lane, lst);
        if (irregular(S, T, lane)) {
          if (__any_sync(0xffffffffu, S.bad != 0)) goto redo;
          resum(S, lane);
        }
        temporal_out<true>(S, T, slot, P, lane, lst);
        goto stored;
      redo:
        asm volatile("barrier.cta.sync.aligned %0, 128;" ::"r"(wg + 1) : "memory");
        asm volatile("st.shared.b32 [%0], %1;\nfence.acq_rel.cta;" ::"r"(T.flag), "r"(0) : "memory");
        G.gate = 0;
        pgap = p0 == pdir ? 4 * pgap + 64 : 0;
        pdir = p0 + 64 + pgap;
      }
      temporal<false>(S, d1, G, P, scaled, lane, lst);
      if (irregular(S, T, lane)) resum(S, lane);
      temporal_out<false>(S, T, slot, P, lane, lst);
    }
  stored:
    const uint32_t pn = __shfl_sync(0xffffffffu, p0 + 64, 0);
    bool last = false;
    if (pn >= pstop) {
      if (helper) last = true;
      else if (pstop < npx - 4 * 49) {
        if (((wg & 1) | wp | lane) == 0) {
          const uint32_t nb = gridDim.x, nwh = min(max((int)(2 * nrem - nb), (int)(nrem / 2)), nrem);
          const uint32_t r = atomicAdd(&g_par.ticket, 1u), j = r - nwh;
          sts32(ring + kExtra, r < nwh ? (nfull * nb + r) * 4 + 3 : j < 2 * (nrem - nwh) ? (nfull * nb + nwh + (j >> 1)) * 4 + 1 + (j & 1) : 0);
        }
        __syncwarp();
        pstop = npx - 2 * 49 + 8 * wp;
      } else if (pstop < npx) {
        if (__shfl_sync(0xffffffffu, lds32(ring + kExtra), 0)) npx += 49;
        pstop = npx + 8 * wp;
      } else last = true;
    }
    asm volatile("fence.proxy.async.shared::cta;" ::: "memory");
    __syncwarp();
    mbar_arrive(slot + kDone + (fresh(lane) >= 4 * T.n ? dn : 0), lane & 3);
    __syncwarp();
    if (last) break;
    p0 = pn;
  }
}

struct Frame {
  bool light;
  uint32_t sta;
  uint32_t oo;
  uint32_t e0, e1;
};
__device__ __forceinline__ uint32_t frame_init(Frame& F, uint32_t ring, uint32_t t, int wp, int lane) {
  wp = (wp + t) & 3;
  F.light = wp == 3;
  F.sta = ring + t * kSlot + kXBytes + 64 * wp;
  const uint32_t r = 16 * wp + (lane >> 2);
  F.oo = ((r / 7) * (kW - 7) + r) * 192u + (lane & 3) * 16 + (((((r + 8) / 7 - r / 7) * (kW - 7) + 8) * 3u) << 20);
  F.e0 = F.e1 = 0;
  const uint32_t am = t * kPlane + wp * 1024 + ((lane * 65) & 0x3d0);
  return F.light && (lane & 15) ? kZero : am ^ ((am >> 3) & 0x30);
}
template <bool F>
__device__ __forceinline__ void load_frame(uint32_t (&v)[24], uint32_t ma, uint32_t slot, uint32_t& tid) {
  const uint32_t st = ma < kXBytes ? kChunk : 0, mb = ma ^ 32;
  uint32_t a[6] = {ma, mb, mb + st, ma + st, ma + 2 * st, mb + 2 * st};
  pin<6>(a);
  if (F) sfence(tid);
#pragma unroll
  for (int k = 0; k < 6; k++) ldsm4(v + 4 * k, slot + a[k]);
}
__device__ __forceinline__ void load_block(uint32_t (&v)[24], uint32_t ma, uint32_t slot) {
  const uint32_t mb = fresh(ma ^ 32);
  ldsm4(v, ma + slot); ldsm4(v + 4, mb + slot);
  ldsm4(v + 8, mb + (slot + kChunk)); ldsm4(v + 12, ma + (slot + kChunk));
  ldsm4(v + 16, ma + (slot + 2 * kChunk)); ldsm4(v + 20, mb + (slot + 2 * kChunk));
}
__device__ __forceinline__ void load_light(uint32_t (&v)[24], uint32_t t, uint32_t slot, uint32_t tid) {
  const uint32_t r = t * kPlane + 48 * 64, a0 = ((tid & 3) << 2) | ((r >> 3) & 0x30), u = slot + r, off = tid & 28;
  uint32_t a[4] = {a0, a0 ^ 16, a0 ^ 32, a0 ^ 48};
  pin<4>(a);
#pragma unroll
  for (int j = 0; j < 12; j++) {
    asm volatile("mov.b32 %0, 0;" : "=r"(v[2 * j + 1]));
    asm volatile("{\n.reg .pred p;\nsetp.eq.u32 p, %2, 0;\nmov.b32 %0, 0;\n@p ld.shared.b32 %0, [%1];\n}"
                 : "=r"(v[2 * j]) : "r"(a[(j & 3) ^ (j & 4 ? 2 : 0)] + (u + (j >> 2) * kChunk)), "r"(off) : "memory");
  }
}
__device__ __forceinline__ void load_stats(Frame& F, uint32_t ia, uint32_t tid) {
  const uint32_t a = fresh(tid & 0x1c), u = F.sta + ia * 196;
  F.e0 = lds32(a + u);
  F.e1 = lds32(a + (u + 32));
}
template <int OFF>
__device__ __forceinline__ void gemm_u(uint32_t (&u)[24], const uint32_t* s, uint64_t db) {
  constexpr uint32_t kMN = (((kChunk >> 4) - 1) << 16) + OFF / 16;
  asm volatile("" : "+l"(db));
  wg_fence();
  wgmma<2, 1>(u, s, db + kMN); wgmma<1, 1>(u, s + 4, db + kMN + 64); wgmma<1, 1>(u, s + 8, db + kMN + 128); wgmma<1, 1>(u, s + 12, db + kMN + 192);
  wg_commit();
}
__device__ __forceinline__ uint32_t key48(uint32_t (&s)[16], uint32_t tid) {
  return fresh(sel(tid & 3, 0xfc00fc00u, __byte_perm(s[12], s[13], 0x5410)));
}
__device__ __forceinline__ uint32_t amax3(uint32_t a, uint32_t b, uint32_t c) {
  return as_u(__hmax2(__hmax2(__habs2(as_h2(a)), __habs2(as_h2(b))), __habs2(as_h2(c))));
}
struct Quad { uint32_t v[4]; };
__device__ __forceinline__ void sub_max(uint32_t (&s)[16], uint32_t& t) {
  const uint32_t x0 = h2max(h2max(h2max(s[0], s[2]), h2max(s[4], s[6])), h2max(s[8], s[10]));
  const uint32_t x1 = h2max(h2max(h2max(s[1], s[3]), h2max(s[5], s[7])), h2max(s[9], s[11]));
  uint32_t mx = h2max(h2max(__byte_perm(x0, x1, 0x5410), __byte_perm(x0, x1, 0x7632)), t);
  mx = h2max(mx, shfl_x(mx, 1));
  mx = h2max(mx, shfl_x(mx, 2));
#pragma unroll
  for (int j = 0; j < 6; j++) { s[2 * j] = h2sub(s[2 * j], lo2(mx)); s[2 * j + 1] = h2sub(s[2 * j + 1], hi2(mx)); }
  t = h2sub(t, mx);
}
template <int J>
__device__ __forceinline__ Quad exp_sum(uint32_t (&s)[16], uint32_t& t) {
#pragma unroll
  for (int j = J; j < 12; j++) s[j] = h2ex2(s[j]);
  t = h2ex2(t);
  Quad q;
  q.v[0] = h2add(t, fold_add(h2add(h2add(h2add(s[0], s[2]), h2add(s[4], s[6])), h2add(s[8], s[10])),
                             h2add(h2add(h2add(s[1], s[3]), h2add(s[5], s[7])), h2add(s[9], s[11]))));
#pragma unroll
  for (int i = 1; i < 4; i++) q.v[i] = shfl_x(q.v[0], i);
  return q;
}
__device__ __forceinline__ Quad soft_exp(uint32_t (&s)[16], uint32_t& t) {
  const uint32_t am = h2max(h2max(h2max(amax3(s[0], s[1], s[2]), amax3(s[3], s[4], s[5])), amax3(s[6], s[7], s[8])), h2max(amax3(s[9], s[10], s[11]), t));
  uint32_t rare, sp[4];
#pragma unroll
  for (int j = 0; j < 4; j++) sp[j] = fresh(h2ex2(s[j]));
  asm("{\n.reg .pred p, q;\n.reg .b32 t;\nmov.b32 t, 0x49004900;\nsetp.le.f16x2 p|q, %1, t;\nand.pred p, p, q;\nselp.b32 %0, 0, 1, p;\n}" : "=r"(rare) : "r"(am));
  if (__any_sync(0xffffffffu, rare)) {
    sub_max(s, t);
#pragma unroll
    for (int j = 0; j < 4; j++) sp[j] = h2ex2(s[j]);
  }
#pragma unroll
  for (int j = 0; j < 4; j++) s[j] = sp[j];
  return exp_sum<4>(s, t);
}
__device__ __forceinline__ void soft_norm(uint32_t (&s)[16], uint32_t& t, const Quad& q, const Frame& F, float2 e, uint32_t tid) {
  const float2 d = unpack_h2(h2add(h2add(q.v[0], q.v[1]), h2add(q.v[2], q.v[3])));
  const uint32_t cb = pack_h2(rcp_fast(d.x * e.x), rcp_fast(d.y * e.y)) & (sel(tid & 28, 0u, 0xffffu) | fresh(F.light ? 0u : 0xffffffffu));
#pragma unroll
  for (int j = 0; j < 6; j++) { s[2 * j] = h2mul(s[2 * j], lo2(cb)); s[2 * j + 1] = h2mul(s[2 * j + 1], hi2(cb)); }
  t = fresh(h2mul(t, cb));
  pin<12>(s);
}
__device__ __forceinline__ void soft_tail(uint32_t (&s)[16], uint32_t t) {
  s[12] = t & 0xffffu; s[13] = t >> 16;
  asm volatile("mov.b32 %0, 0;\nmov.b32 %1, 0;" : "=r"(s[14]), "=r"(s[15]));
}
template <int H>
__device__ __forceinline__ uint8_t* row_ptr(const Frame& F, uint8_t* o) {
  const uint32_t oo = fresh(F.oo);
  if (H) asm volatile("mad.wide.u32 %0, %1, 64, %0;" : "+l"(o) : "r"(oo >> 20));
  else { o += oo & 0xfffffu; asm volatile("" : "+l"(o)); }
  return o;
}
template <int H>
__device__ __forceinline__ void affine(uint32_t* r, const uint32_t (&v)[24], const Frame& F) {
  const uint32_t e = H ? F.e1 : F.e0;
#pragma unroll
  for (int j = 0; j < 12; j++) r[j] = h2fma(v[2 * j + H], lo2(e), hi2(e));
  pin<12>(r);
}
template <int H, bool kFence = false>
__device__ __forceinline__ void finish(uint32_t* r, const Frame& F, uint8_t*& o, uint32_t off, uint32_t a, uint32_t m, uint32_t& fz) {
  o = row_ptr<H>(F, o);
#pragma unroll
  for (int j = 0; j < 12; j += 2) { const float2 f = unpack_h2(r[j]), g = unpack_h2(r[j + 1]); r[j] = pack_bf2(f.x, g.x); r[j + 1] = pack_bf2(f.y, g.y); }
  pin<12>(r);
  if (kFence) sfence(fz);
  stg3(o, r, off | (fresh(a) & m));
}
__device__ __forceinline__ uint32_t surplus(uint32_t ring, uint32_t i, uint32_t nfull) { return i + 4 == nfull ? lds32(ring + kExtra) >> 2 : 0; }

__device__ __forceinline__ void release(uint32_t ring, uint32_t slot, uint32_t i, uint32_t nfull, uint32_t w, const CUtensorMap* tm, uint32_t lane) {
  uint32_t old = 0;
  asm volatile("{\n.reg .pred p;\nsetp.eq.u32 p, %2, 0;\n@p atom.relaxed.cta.shared::cta.inc.u32 %0, [%1], 1;\n}" : "+r"(old) : "r"(slot + kRel), "r"(lane) : "memory");
  if (old) {
    sts32(slot + kWide, 0);
    if (i + 4 < nfull) tma_load_win(slot, tm, w + 4 * gridDim.x);
    else if (const uint32_t wn = surplus(ring, i, nfull)) tma_load_win(slot, tm, fresh(wn));
    else mbar_arrive(slot + kFull);
  }
  __syncwarp();
}
__device__ __forceinline__ uint32_t window_offset(uint32_t w) { return (((w * 57457u) >> 22) * (7 * kW - 7 * kNWX) + w * 7) * 192u; }

__device__ __forceinline__ void round_wide(uint32_t ring, uint64_t d0, uint32_t frame, uint32_t nfull, uint32_t i, uint32_t w, int sg, int wp, uint32_t lane,
                                           const CUtensorMap* tm, uint8_t* __restrict__ out) {
  const uint32_t slot = ring + (i & 3) * kSlot;
  uint32_t x[24];
#pragma unroll
  for (int j = 0; j < 24; j++) x[j] = 0;
#pragma unroll 1
  for (uint32_t t = 2 * sg; t < 2 * sg + 2; t++) {
    Frame F;
    uint32_t v[24], s[16];
    load_frame<false>(v, frame_init(F, ring, t, wp, lane), slot, lane);
    load_stats(F, i & 3, lane);
    const uint64_t dp = d0 + (uint32_t)((kWBytes + (i & 3) * kSlot + t * kPlane) / 16);
    gemm<2, kOffAs, 6144>(x, v, d0);
    const uint32_t cs = score_scale(&g_par.cS_s);
    const float kb = __ldcg(&g_par.kb), ik = rcp_fast(__ldcg(&g_par.kappa));
    wg_wait(); pin<24>(x);
    gemm<0, 0, kChunk>(s, x, dp);
    wg_wait(); pin<14>(s);
    uint32_t u = key48(s, lane);
    sub_max(s, u);
#pragma unroll
    for (int j = 0; j < 12; j++) s[j] = h2mul(s[j], cs);
    u = h2mul(u, cs);
    const float2 z0 = stat_f32(F.e0), z1 = stat_f32(F.e1);
    const float e0 = fmaxf(z0.x, kb), e1 = fmaxf(z1.x, kb);
    const uint32_t aw = pack_h2(__fdividef(z0.x, e0), __fdividef(z1.x, e1));
#pragma unroll
    for (int j = 0; j < 12; j++) { v[2 * j] = h2mul(v[2 * j], lo2(aw)); v[2 * j + 1] = h2mul(v[2 * j + 1], hi2(aw)); }
    soft_norm(s, u, exp_sum<0>(s, u), F, make_float2(e0 * ik, e1 * ik), lane);
    soft_tail(s, u);
    gemm_u<0>(x, s, dp);
    wg_wait(); pin<24>(x);
    gemm<1, kOffWs, 6144>(v, x, d0);
    if ((t & 1) && wp == 0) release(ring, slot, i, nfull, w, tm, lane);
    wg_wait(); pin<24>(v);
    uint8_t* o = out + (size_t)(window_offset(w) + t * frame);
#pragma unroll
    for (int h = 0; h < 2; h++) {
      const float e = h ? e1 : e0, m = h ? z1.y : z0.y;
      uint32_t r[12];
#pragma unroll
      for (int j = 0; j < 12; j += 2) {
        const float2 f = unpack_h2(v[2 * j + h]), g = unpack_h2(v[2 * j + 2 + h]);
        r[j] = pack_bf2(fmaf(f.x, e, m), fmaf(g.x, e, m)); r[j + 1] = pack_bf2(fmaf(f.y, e, m), fmaf(g.y, e, m));
      }
      o = h ? row_ptr<1>(F, o) : row_ptr<0>(F, o);
      stg3(o, r, F.light ? (h ? 1 : lane & 28) : 0);
    }
  }
}

__device__ __forceinline__ uint32_t rounds(uint32_t ring, uint64_t d0, uint64_t d1, uint32_t frame, uint32_t nfull, uint32_t i, uint32_t i1, uint32_t w,
                                           int sg, int wp, int lane, const CUtensorMap* tm, uint8_t* __restrict__ out) {
  Frame A, B;
  uint32_t tid = lane + (frame_init(A, ring, 2 * sg, wp, lane) << 4) + (frame_init(B, ring, 2 * sg + 1, wp, lane) << 16);
  uint32_t va[24], vb[24], x[24], sa[16], sc[16], r0[12], r1[12], ta, tb;
  Quad rs;
  uint32_t& fz = A.oo;
#pragma unroll
  for (int j = 0; j < 24; j++) { vb[j] = 0; x[j] = 0; }
  out += sg * 2 * frame;
  asm volatile("" : "+l"(out));
  uint8_t *ob = out, *o;
  const uint64_t dr = d0 + (uint32_t)(kWBytes / 16 + sg * (2 * kPlane / 16));
  uint32_t slot = ring + (i & 3) * kSlot, first = 1;
  load_frame<false>(va, (tid >> 4) & 0xfff0u, slot, tid);
  do {
    const uint32_t ia = i & 3;
    tid = fresh(tid);
    gemm<2, kOffAs, 6144>(x, va, d0);
    sfence(fz);
    affine<0>(r0, vb, B); affine<1>(r1, vb, B);
    load_frame<true>(vb, (tid >> 16) & 0xfff0u, slot, fz);
    uint64_t dp = dr + ia * (kSlot / 16);
    asm volatile("" : "+l"(dp));
    o = ob + frame;
    asm volatile("" : "+l"(o));
    finish<0, true>(r0, B, o, first, tid, B.light ? 28 : 0, fz);
    sfence(fz);
    wg_wait(); pin<24>(x);
    gemm<0, 0, kChunk>(sa, x, dp);
    if (!B.light) finish<1>(r1, B, o, first, 0, 0, fz);
    else if (sg == 0) {
      if ((tid & 31) == 0) {
        if (i + 4 < nfull) tma_prefetch_win(tm, w + 4 * gridDim.x);
        else if (const uint32_t wn = surplus(ring, i, nfull)) tma_prefetch_win(tm, fresh(wn));
      }
      __syncwarp();
    }
    ob = out + (size_t)window_offset(w);
    asm volatile("" : "+l"(ob));
    wg_wait(); pin<14>(sa);
    gemm<2, kOffAs, 6144>(x, vb, d1);
    ta = key48(sa, tid);
    rs = soft_exp(sa, ta);
    load_stats(A, ia, tid);
    sfence(fz);
    wg_wait(); pin<24>(x);
    gemm<0, kPlane, kChunk>(sc, x, dp);
    sfence(fz);
    soft_norm(sa, ta, rs, A, make_float2(low_f(A.e0), low_f(A.e1)), tid);
    sfence(fz);
    wg_wait(); pin<14>(sc);
    tb = key48(sc, tid);
    sfence(fz);
    soft_tail(sa, ta);
    gemm_u<0>(x, sa, dp);
    rs = soft_exp(sc, tb);
    load_stats(B, ia, tid);
    sfence(fz);
    wg_wait(); pin<24>(x);
    gemm<1, kOffWs, 6144>(va, x, d0);
    sfence(fz);
    soft_norm(sc, tb, rs, B, make_float2(low_f(B.e0), low_f(B.e1)), tid);
    soft_tail(sc, tb);
    sfence(fz);
    wg_wait(); pin<24>(va);
    gemm_u<kPlane>(x, sc, dp);
    sfence(fz);
    const uint32_t sn = ring + ((i + 1) & 3) * kSlot;
    const bool slow = mbar_pending_or<kWide - kDone>(sn + kDone, (i + 1) >> 2);
    affine<0>(r0, va, A);
    o = ob;
    finish<0>(r0, A, o, 0, tid, A.light ? 28 : 0, fz);
    sfence(fz);
    wg_wait(); pin<24>(x);
    gemm<1, kOffWs, 6144>(vb, x, d1);
    affine<1>(r1, va, A);
    if (slow || A.light) {
      if (A.light) release(ring, slot, i, nfull, w, tm, tid & 31);
      if (slow) {
        if (i + 1 < i1) mbar_wait(sn + kDone, (i + 1) >> 2);
        if (__any_sync(0xffffffffu, lds32(sn + kWide))) i1 = 0;
      }
    }
    const uint32_t la = (tid >> 4) & 0xfff0u;
    if (!A.light) { load_block(va, la, sn); finish<1>(r1, A, o, 0, la, 0, fz); }
    else load_light(va, 2 * sg, sn, tid);
    wg_wait(); pin<24>(vb);
    launder<24>(vb);
    launder<24>(va);
    slot = sn; w += gridDim.x; first = 0;
  } while (++i < i1);
  o = ob + frame;
  affine<0>(r0, vb, B); finish<0>(r0, B, o, 0, tid, B.light ? 28 : 0, tid);
  affine<1>(r1, vb, B); finish<1>(r1, B, o, B.light, 0, 0, tid);
  return i;
}

__device__ __forceinline__ void run_S(uint32_t ring, uint64_t d0, uint64_t d1, uint32_t frame, uint32_t nfull, uint32_t i, uint32_t i1, uint32_t w0,
                                      int sg, int wp, const CUtensorMap* tm, uint8_t* __restrict__ out) {
  do {
    const uint32_t lane = fresh(threadIdx.x) & 31;
    const uint32_t slot = ring + (i & 3) * kSlot, w = w0 + i * gridDim.x;
    mbar_wait(slot + kDone, i >> 2);
    if (__any_sync(0xffffffffu, lds32(slot + kWide) | lds32(ring + kSlot + kExtra))) {
      round_wide(ring, d1, frame, nfull, i, w, sg, wp, lane, tm, out);
      i++;
    } else {
      i = rounds(ring, d0, d1, frame, nfull, i, i1, w, sg, wp, lane, tm, out);
    }
  } while (i < i1);
}

struct Maps { CUtensorMap load, prefetch; };
__global__ void __launch_bounds__(512, 1) swin_main(const __grid_constant__ Maps tms, uint8_t* __restrict__ out, const uint64_t d0,
                                                    const uint64_t d1, const uint32_t frame) {
  extern __shared__ __align__(1024) uint8_t smem[];
  const CUtensorMap& tm = tms.load;
  const uint32_t sb = smem_u32(smem), ring = sb + kWBytes;
  const int tid = threadIdx.x;
  const int wg = __shfl_sync(0xffffffffu, tid >> 7, 0);
  const int wp = __shfl_sync(0xffffffffu, (tid >> 5) & 3, 0);
  const int lane = tid & 31;
  const uint32_t b = blockIdx.x, nb = gridDim.x;
  const uint32_t nfull = kNWIN / nb, nrem = kNWIN - nfull * nb;
  if (tid == 0) {
    if (sb != 1024 || nfull > 700 || nfull < 12) __trap();
#pragma unroll
    for (int i = 0; i < 4; i++) {
      mbar_init(ring + i * kSlot + kFull, 1);
      mbar_init(ring + i * kSlot + kDone, 49);
      sts32(ring + i * kSlot + kRel, 0); sts32(ring + i * kSlot + kFlag, 0); sts32(ring + i * kSlot + kWide, 0);
    }
    asm volatile("fence.mbarrier_init.release.cluster;" ::: "memory");
    for (int i = 0; i < 2; i++) tma_load_win(ring + i * kSlot, &tm, b + i * nb);
  }
  __syncwarp();
  if (wg == 1 || wg == 2)
    asm volatile("st.shared.v4.b32 [%0], {%1,%1,%1,%1};" ::"r"(ring + ((tid - 128) >> 6) * kSlot + kXBytes + (tid & 63) * 16), "r"(0) : "memory");
  __syncthreads();
  asm volatile("griddepcontrol.wait;" ::: "memory");
#pragma unroll
  for (int q = 0; q < kWBytes / 16 / 512; q++)
    asm volatile("cp.async.cg.shared.global [%0], [%1], 16;" ::"r"(sb + (tid + q * 512) * 16), "l"(g_wimg + tid + q * 512) : "memory");
  if (wg == 0 && wp < 3) {
    static_assert(kWBytes / 16 == 9 * 512 + 96, "weight copy split");
    const int e = tid + 9 * 512;
    asm volatile("cp.async.cg.shared.global [%0], [%1], 16;" ::"r"(sb + e * 16), "l"(g_wimg + e) : "memory");
  }
  const float4 p0 = __ldcg(reinterpret_cast<const float4*>(&g_par));
  const float kb = __ldcg(&g_par.kb);
  TPar P;
  P.kt = p0.z;
  P.sgmin = fmaxf(0.0045f, kb * 0.011f);
  P.outmax = fmaf(kb, -627.2f, 60000.f);
  const bool scaled = __any_sync(0xffffffffu, p0.x != 1.f);
  const uint32_t pdir = __ballot_sync(0xffffffffu, scaled || !(P.kt <= 256.f));
  if (wg == 0) sts32(ring + kSlot + kExtra, p0.y != 1.f || p0.w != 1.f);
  asm volatile("cp.async.wait_all;\nfence.proxy.async.shared::cta;" ::: "memory");
  __syncthreads();
  if (tid == 128) for (int i = 2; i < 4; i++) tma_load_win(ring + i * kSlot, &tm, b + i * nb);
  __syncwarp();
  const bool isT = wg < 2;
  run_T(ring, d0, d1, nfull, nrem, !isT, wg, wp, lane, P, scaled, pdir);
  const uint32_t ex = isT ? __shfl_sync(0xffffffffu, lds32(ring + kExtra), 0) : 3;
  if ((ex >> (wg & 1)) & 1) run_S(ring, d0, d1, frame, nfull, isT ? nfull : 0, nfull + isT, isT ? (ex >> 2) - nfull * nb : b, wg & 1, wp, &tm, out);
}

__device__ __forceinline__ int ch_pos(int ch) { return 32 * (ch >> 5) + 16 * ((ch >> 2) & 1) + 8 * (ch & 1) + 2 * ((ch >> 3) & 3) + ((ch >> 1) & 1); }
__device__ __forceinline__ float pow2_ceil(float v) {
  return __uint_as_float((__float_as_uint(v) + 0x7fffffu) & 0x7f800000u);
}

constexpr int kPrepSplit = 12;
constexpr int kPrepThreads = 384;
__global__ void __launch_bounds__(kPrepThreads) swin_prep(const __nv_bfloat16* __restrict__ wqkv_t, const __nv_bfloat16* __restrict__ wo_t,
                                                          const __nv_bfloat16* __restrict__ wqkv_s, const __nv_bfloat16* __restrict__ wo_s) {
  asm volatile("griddepcontrol.launch_dependents;");
  __shared__ __align__(16) uint32_t raw[2][96][52];
  __shared__ __align__(16) uint32_t mu[3][52];
  __shared__ float nrm[12], nrm2[6], csum[6][9];
  const int mat = blockIdx.x / kPrepSplit, blk = blockIdx.x % kPrepSplit;
  const int tid = threadIdx.x, lane = tid & 31, warp = tid >> 5, g = lane >> 2, c = lane & 3;
  const __nv_bfloat16* wqkv = mat < 2 ? wqkv_t : wqkv_s;
  const __nv_bfloat16* wo = mat < 2 ? wo_t : wo_s;
  const bool isA = (mat & 1) == 0;
  {
    uint4 v[3], u[3];
#pragma unroll
    for (int q = 0; q < 3; q++) {
      const int e = tid + q * kPrepThreads, i = e / 12, c8 = (e % 12) * 8;
      v[q] = __ldg(reinterpret_cast<const uint4*>(wqkv + i * 288 + (isA ? 0 : 192) + c8));
      u[q] = __ldg(reinterpret_cast<const uint4*>(isA ? wqkv + i * 288 + 96 + c8 : wo + i * 96 + c8));
    }
#pragma unroll
    for (int q = 0; q < 3; q++) {
      const int e = tid + q * kPrepThreads, i = e / 12, c4 = (e % 12) * 4;
      *reinterpret_cast<uint4*>(&raw[0][i][c4]) = v[q];
      *reinterpret_cast<uint4*>(&raw[1][i][c4]) = u[q];
    }
  }
  __syncthreads();
  {
    const int m = warp / 6, cp = (warp % 6) * 8 + g;
    float s0 = 0.f, s1 = 0.f, q0 = 0.f, q1 = 0.f;
#pragma unroll
    for (int i = 0; i < 24; i++) {
      const uint32_t w = raw[m][4 * i + c][cp];
      const float lo = __uint_as_float(w << 16), hi = __uint_as_float(w & 0xffff0000u);
      s0 += lo; s1 += hi; q0 = fmaf(lo, lo, q0); q1 = fmaf(hi, hi, q1);
    }
    s0 = quad_sum(s0) * (1.f / 96.f); s1 = quad_sum(s1) * (1.f / 96.f); q0 = quad_sum(q0); q1 = quad_sum(q1);
    if (mat == 1 && m == 1) {
      float r0 = 0.f, r1 = 0.f;
#pragma unroll
      for (int i = 0; i < 12; i++) {
        const uint32_t w0 = raw[1][2 * cp][4 * i + c], w1 = raw[1][2 * cp + 1][4 * i + c];
        r0 += __uint_as_float(w0 << 16) + __uint_as_float(w0 & 0xffff0000u);
        r1 += __uint_as_float(w1 << 16) + __uint_as_float(w1 & 0xffff0000u);
      }
      r0 = quad_sum(r0) * (1.f / 96.f); r1 = quad_sum(r1) * (1.f / 96.f);
      s0 = r0; s1 = r1;
    }
    if (m == 1 && c == 0) {
      const uint32_t hi = mat == 3 ? 0u : pack_bf2(s0, s1);
      mu[0][cp] = hi;
      mu[1][cp] = mat == 3 ? 0u : pack_bf2(s0 - __uint_as_float(hi << 16), s1 - __uint_as_float(hi & 0xffff0000u));
      mu[2][cp] = 0u;
    }
    if (m == 0 || isA) {
      q0 = fmaxf(fmaf(-96.f * s0, s0, q0), 0.f) + q0 * 1e-6f;
      q1 = fmaxf(fmaf(-96.f * s1, s1, q1), 0.f) + q1 * 1e-6f;
    }
    const bool usemax = m == 1 && mat == 3;
    float t = usemax ? fmaxf(q0, q1) : q0 + q1;
#pragma unroll
    for (int o = 4; o < 32; o <<= 1) { const float z = __shfl_xor_sync(0xffffffffu, t, o); t = usemax ? fmaxf(t, z) : t + z; }
    if (lane == 0) nrm[warp] = t;
  }
  __syncthreads();
  if (warp >= 6) return;
  float d[4] = {0.f, 0.f, 0.f, 0.f}, e[4] = {0.f, 0.f, 0.f, 0.f}, v0, v1;
  {
    const uint32_t arow = smem_u32(&raw[0][16 * warp + (lane & 15)][(lane >> 4) * 4]);
    const uint32_t brow = isA ? smem_u32(&raw[1][blk * 8 + (lane & 7)][(lane >> 3) * 4]) : smem_u32(&raw[1][lane][blk * 4]);
    const uint32_t mrow = smem_u32(&mu[min(lane & 7, 2)][(lane >> 3) * 4]);
#pragma unroll
    for (int k2 = 0; k2 < 3; k2++) {
      uint32_t b[4], m[4];
      if (isA) ldsm4(b, brow + k2 * 64);
      else asm volatile("ldmatrix.sync.aligned.m8n8.x4.trans.shared.b16 {%0,%1,%2,%3}, [%4];"
                        : "=r"(b[0]), "=r"(b[1]), "=r"(b[2]), "=r"(b[3]) : "r"(brow + k2 * (32 * 208)) : "memory");
      ldsm4(m, mrow + k2 * 64);
#pragma unroll
      for (int hf = 0; hf < 2; hf++) {
        uint32_t a[4];
        ldsm4(a, arow + (2 * k2 + hf) * 32);
        asm volatile("mma.sync.aligned.m16n8k16.row.col.f32.bf16.bf16.f32 {%0,%1,%2,%3},{%4,%5,%6,%7},{%8,%9},{%0,%1,%2,%3};"
                     : "+f"(d[0]), "+f"(d[1]), "+f"(d[2]), "+f"(d[3])
                     : "r"(a[0]), "r"(a[1]), "r"(a[2]), "r"(a[3]), "r"(b[2 * hf]), "r"(b[2 * hf + 1]));
        asm volatile("mma.sync.aligned.m16n8k16.row.col.f32.bf16.bf16.f32 {%0,%1,%2,%3},{%4,%5,%6,%7},{%8,%9},{%0,%1,%2,%3};"
                     : "+f"(e[0]), "+f"(e[1]), "+f"(e[2]), "+f"(e[3])
                     : "r"(a[0]), "r"(a[1]), "r"(a[2]), "r"(a[3]), "r"(m[2 * hf]), "r"(m[2 * hf + 1]));
      }
    }
    v0 = __shfl_sync(0xffffffffu, e[0] + e[1], lane & ~3); v1 = __shfl_sync(0xffffffffu, e[2] + e[3], lane & ~3);
    d[0] -= v0; d[1] -= v0; d[2] -= v1; d[3] -= v1;
    float t0 = d[0] + d[2], t1 = d[1] + d[3], t2 = v0 + v1;
#pragma unroll
    for (int o = 4; o < 32; o <<= 1) {
      t0 += __shfl_xor_sync(0xffffffffu, t0, o); t1 += __shfl_xor_sync(0xffffffffu, t1, o); t2 += __shfl_xor_sync(0xffffffffu, t2, o);
    }
    if (g == 0) { csum[warp][2 * c] = t0; csum[warp][2 * c + 1] = t1; csum[warp][8] = t2; }
  }
  const float nl = nrm[0] + nrm[1] + nrm[2] + nrm[3] + nrm[4] + nrm[5];
  const float nr = mat == 3 ? fmaxf(fmaxf(fmaxf(nrm[6], nrm[7]), fmaxf(nrm[8], nrm[9])), fmaxf(nrm[10], nrm[11]))
                            : nrm[6] + nrm[7] + nrm[8] + nrm[9] + nrm[10] + nrm[11];
  const float bound = __fsqrt_rn(nl) * __fsqrt_rn(nr) * 1.01f;
  const float f = isA ? 0.14724448f : 1.f;
  float sc = pow2_ceil(fmaxf(bound * (isA ? 0.14724448f / 160.f : mat == 1 ? 1.f / 16.f : 1.f / 64.f), 1e-30f));
  if (isA) sc = fminf(fmaxf(sc, 1.f), 32768.f);
  if (mat == 3) {
    if (blk == 0 && tid == 0) { g_par.kb = sc; g_par.ticket = 0; }
    if (sc <= 1.f && sc >= 1.f / 1024.f) sc = 1.f;
  }
  const float mul = f * __uint_as_float(0x7f000000u - __float_as_uint(sc));
  if (blk == 0 && tid == 0) (mat == 0 ? g_par.cS_t : mat == 1 ? g_par.kt : mat == 2 ? g_par.cS_s : g_par.kappa) = sc;
  asm volatile("bar.sync 1, 192;" ::: "memory");
  float mean[2];
#pragma unroll
  for (int b = 0; b < 2; b++)
    mean[b] = (csum[0][2 * c + b] + csum[1][2 * c + b] + csum[2][2 * c + b] + csum[3][2 * c + b] + csum[4][2 * c + b] + csum[5][2 * c + b]) *
              (1.f / 96.f);
  uint8_t* img = reinterpret_cast<uint8_t*>(g_wimg) + (mat == 0 ? 0 : mat == 1 ? kOffWt : mat == 2 ? kOffAs : kOffWs);
  const float vmean = (csum[0][8] + csum[1][8] + csum[2][8] + csum[3][8] + csum[4][8] + csum[5][8]) * (1.f / 96.f);
  float q2 = 0.f;
#pragma unroll
  for (int q = 0; q < 4; q++) q2 = fmaf(d[q] - mean[q & 1], d[q] - mean[q & 1], q2);
#pragma unroll
  for (int o = 16; o; o >>= 1) q2 += __shfl_xor_sync(0xffffffffu, q2, o);
  if (lane == 0) nrm2[warp] = q2;
  asm volatile("bar.sync 1, 192;" ::: "memory");
  const float rms = __fsqrt_rn((nrm2[0] + nrm2[1] + nrm2[2] + nrm2[3] + nrm2[4] + nrm2[5]) * (1.f / 768.f)) * mul;
  const float big = 12582912.f * pow2_ceil(fmaxf(rms * (1.f / 256.f), 1e-30f));
  const float off = mat == 2 ? 1.5f * pow2_ceil(fmaxf(rms * 3.f, 1e-4f)) : 0.f;
#pragma unroll
  for (int q = 0; q < 4; q++) {
    const int kp = ch_pos(16 * warp + g + 8 * (q >> 1)), np = ch_pos(blk * 8 + 2 * c + (q & 1));
    const uint32_t ko = (kp >> 5) * (mat < 2 ? kAtChunk : 6144) + (kp & 31) * 2;
    uint32_t a = ko + np * 64;
    a ^= ((a >> 7) & 3) << 4;
    const float o = __fadd_rn(__fadd_rn((d[q] - mean[q & 1]) * mul, big), -big);
    *reinterpret_cast<__half*>(img + a) = __float2half_rn(o + off);
    if (mat == 1 && blk == 0) {
      a = (kp >> 5) * kAtChunk + (kp & 31) * 2 + (96 + 2 * c + (q & 1)) * 64;
      a ^= ((a >> 7) & 3) << 4;
      *reinterpret_cast<__half*>(reinterpret_cast<uint8_t*>(g_wimg) + a) = __float2half_rn((q & 1) ? ((q >> 1 ? v1 : v0) - vmean) * mul : 1.f / 96.f);
    }
  }
}

typedef CUresult (*EncodeFn)(CUtensorMap*, CUtensorMapDataType, cuuint32_t, void*, const cuuint64_t*, const cuuint64_t*,
                             const cuuint32_t*, const cuuint32_t*, CUtensorMapInterleave, CUtensorMapSwizzle,
                             CUtensorMapL2promotion, CUtensorMapFloatOOBfill);

}

extern "C" void kernel_launch(void* const* d_in, const int* in_sizes, int n_in, void* d_out, int out_size) {
  (void)in_sizes; (void)n_in; (void)out_size;
  static EncodeFn enc = nullptr;
  static int nsm = 0;
  if (!enc) {
    void* fn = nullptr;
    cudaDriverEntryPointQueryResult qr;
    cudaGetDriverEntryPoint("cuTensorMapEncodeTiled", &fn, cudaEnableDefault, &qr);
    enc = reinterpret_cast<EncodeFn>(fn);
    int dev = 0;
    cudaGetDevice(&dev);
    cudaDeviceGetAttribute(&nsm, cudaDevAttrMultiProcessorCount, dev);
    cudaFuncSetAttribute(swin_main, cudaFuncAttributeMaxDynamicSharedMemorySize, kSmemBytes);
  }
  Maps tms;
  CUtensorMap& tm = tms.load;
  const cuuint64_t dims[5] = {32, kW, kH, kT, 3};
  const cuuint64_t strides[4] = {192, 192ull * kW, 192ull * kW * kH, 64};
  const cuuint32_t box[5] = {32, 7, 7, 4, 3};
  const cuuint32_t es[5] = {1, 1, 1, 1, 1};
  enc(&tm, CU_TENSOR_MAP_DATA_TYPE_BFLOAT16, 5, d_in[0], dims, strides, box, es, CU_TENSOR_MAP_INTERLEAVE_NONE,
      CU_TENSOR_MAP_SWIZZLE_64B, CU_TENSOR_MAP_L2_PROMOTION_L2_128B, CU_TENSOR_MAP_FLOAT_OOB_FILL_NONE);

  const cuuint64_t dims2[3] = {24ull * kW, kH, kT};
  const cuuint64_t strides2[2] = {192ull * kW, 192ull * kW * kH};
  const cuuint32_t box2[3] = {168, 7, 4};
  enc(&tms.prefetch, CU_TENSOR_MAP_DATA_TYPE_UINT64, 3, d_in[0], dims2, strides2, box2, es, CU_TENSOR_MAP_INTERLEAVE_NONE,
      CU_TENSOR_MAP_SWIZZLE_NONE, CU_TENSOR_MAP_L2_PROMOTION_L2_128B, CU_TENSOR_MAP_FLOAT_OOB_FILL_NONE);

  cudaStream_t st = cudaStreamPerThread;
  swin_prep<<<4 * kPrepSplit, kPrepThreads, 0, st>>>(
      static_cast<const __nv_bfloat16*>(d_in[1]), static_cast<const __nv_bfloat16*>(d_in[2]),
      static_cast<const __nv_bfloat16*>(d_in[3]), static_cast<const __nv_bfloat16*>(d_in[4]));

  cudaLaunchConfig_t cfg = {};
  cfg.gridDim = dim3(nsm);
  cfg.blockDim = dim3(512);
  cfg.dynamicSmemBytes = kSmemBytes;
  cfg.stream = st;
  cudaLaunchAttribute at[1];
  at[0].id = cudaLaunchAttributeProgrammaticStreamSerialization;
  at[0].val.programmaticStreamSerializationAllowed = 1;
  cfg.attrs = at;
  cfg.numAttrs = 1;
  cudaLaunchKernelEx(&cfg, swin_main, tms, static_cast<uint8_t*>(d_out), mk_desc(1024), mk_desc(1024), (uint32_t)(kH * kW * 192));
}
```

```cpp
#include <cuda_runtime.h>
#include <cuda.h>
#include <cuda_bf16.h>
#include <cuda_fp16.h>
#include <stddef.h>
#include <stdint.h>

namespace {

constexpr int kH = 511, kW = 511, kT = 4;
constexpr int kNWX = 73, kNWIN = 73 * 73;
constexpr int kChunk = 12544;
constexpr int kPlane = 3136;
constexpr int kXBytes = 37632;
constexpr int kZero = kXBytes + 896, kFull = kXBytes + 1024, kDone = kFull + 8, kRel = kFull + 16, kFlag = kFull + 20, kExtra = kFull + 24,
              kWide = kFull + 28;
constexpr int kPar = kFull + 128;
constexpr int kSlot = 38912;
constexpr int kWMat = 18432;
constexpr int kAtChunk = 200 * 64;
constexpr int kOffWt = 104 * 64;
constexpr int kOffAs = 3 * kAtChunk, kOffWs = kOffAs + kWMat;
constexpr int kWBytes = kOffWs + kWMat;
constexpr int kSmemBytes = kWBytes + 4 * kSlot;

struct Params {
  float cS_t, pad0[7];
  float kt, pad1[7];
  float cS_s, pad2[7];
  float kappa;
  float kb;
  uint32_t ticket, pad3[5];
};

__device__ __align__(128) uint4 g_wimg[kWBytes / 16];
__device__ __align__(128) Params g_par;

__device__ __forceinline__ uint32_t smem_u32(const void* p) { return (uint32_t)__cvta_generic_to_shared(p); }
__device__ __forceinline__ void mbar_init(uint32_t a, int c) { asm volatile("mbarrier.init.shared::cta.b64 [%0], %1;" ::"r"(a), "r"(c)); }
__device__ __forceinline__ void mbar_expect(uint32_t a, int bytes) {
  asm volatile("mbarrier.arrive.expect_tx.shared::cta.b64 _, [%0], %1;" ::"r"(a), "r"(bytes) : "memory");
}
__device__ __forceinline__ void mbar_arrive(uint32_t a, uint32_t off = 0) {
  asm volatile("{\n.reg .pred p;\nsetp.eq.u32 p, %1, 0;\n@p mbarrier.arrive.shared::cta.b64 _, [%0];\n}" ::"r"(a), "r"(off) : "memory");
}
__device__ __forceinline__ void mbar_wait(uint32_t a, uint32_t par) {
  asm volatile(
      "{\n.reg .pred p;\n.reg .u32 n;\n"
      "mbarrier.try_wait.parity.shared::cta.b64 p, [%0], %1;\n"
      "@p bra.uni WDONE;\n"
      "mov.u32 n, 0;\n"
      "WLOOP:\n"
      "mbarrier.try_wait.parity.shared::cta.b64 p, [%0], %1;\n"
      "@p bra.uni WDONE;\n"
      "add.u32 n, n, 1;\n"
      "setp.lt.u32 p, n, 0x100000;\n"
      "@p bra.uni WLOOP;\n"
      "trap;\n"
      "WDONE:\n}" ::"r"(a), "r"(par & 1) : "memory");
}
template <int OFF>
__device__ __forceinline__ bool mbar_pending_or(uint32_t a, uint32_t par) {
  uint32_t r;
  asm volatile("{\n.reg .pred p;\n.reg .b32 t;\nmbarrier.test_wait.parity.shared::cta.b64 p, [%1], %2;\nld.shared.b32 t, [%1+%3];\n"
               "setp.ne.or.u32 p, t, 0, !p;\nvote.sync.any.pred p, p, 0xffffffff;\nselp.b32 %0, 1, 0, p;\n}"
               : "=r"(r) : "r"(a), "r"(par & 1), "n"(OFF) : "memory");
  return r;
}
__device__ __forceinline__ uint32_t lds32(uint32_t a) {
  uint32_t v; asm volatile("ld.shared.b32 %0, [%1];" : "=r"(v) : "r"(a) : "memory"); return v;
}
__device__ __forceinline__ void sts32(uint32_t a, uint32_t v) { asm volatile("st.shared.b32 [%0], %1;" ::"r"(a), "r"(v) : "memory"); }
__device__ __forceinline__ void tma_load_win(uint32_t slot, const CUtensorMap* m, uint32_t w) {
  const uint32_t wy = (w * 57457u) >> 22, wx = w - wy * kNWX;
  mbar_expect(slot + kFull, kXBytes);
  asm volatile(
      "cp.async.bulk.tensor.5d.shared::cluster.global.mbarrier::complete_tx::bytes [%0], [%1, {%3,%4,%5,%3,%3}], [%2];" ::"r"(slot),
      "l"(m), "r"(slot + kFull), "r"(0), "r"(wx * 7), "r"(wy * 7)
      : "memory");
}
__device__ __forceinline__ void tma_prefetch_win(const CUtensorMap* m, uint32_t w) {
  const uint32_t wy = (w * 57457u) >> 22, wx = w - wy * kNWX;
  asm volatile("cp.async.bulk.prefetch.tensor.3d.L2.global [%0, {%1,%2,%3}];" ::"l"(m + 1), "r"(wx * 168), "r"(wy * 7), "r"(0) : "memory");
}
__device__ __forceinline__ void wg_fence() { asm volatile("wgmma.fence.sync.aligned;" ::: "memory"); }
__device__ __forceinline__ void wg_commit() { asm volatile("wgmma.commit_group.sync.aligned;" ::: "memory"); }
__device__ __forceinline__ void wg_wait() { asm volatile("wgmma.wait_group.sync.aligned 0;" ::: "memory"); }
template <int N>
__device__ __forceinline__ void pin(uint32_t* d) {
#pragma unroll
  for (int i = 0; i < N; i++) asm volatile("" : "+r"(d[i])::"memory");
}
__device__ __forceinline__ uint32_t fresh(uint32_t v) { asm volatile("" : "+r"(v)); return v; }
__device__ __forceinline__ float fresh(float v) { asm volatile("" : "+f"(v)); return v; }
template <int N>
__device__ __forceinline__ void launder(uint32_t* q) {
#pragma unroll
  for (int j = 0; j < N; j++) { uint32_t t; asm volatile("mov.b32 %0, %1;" : "=r"(t) : "r"(q[j])); q[j] = t; }
}
__device__ __forceinline__ void sfence(uint32_t& v) {
  asm volatile("{\n.reg .pred p;\nsetp.eq.u32 p, %1, 0x7fffffff;\n@p mov.u32 %0, %%clock;\n}" : "+r"(v) : "r"(gridDim.x) : "memory");
}
constexpr uint64_t mk_desc(uint32_t addr) { return ((uint64_t)0x80000020u << 32) | (addr >> 4) | (1u << 16); }

#define R4(d, i) "+r"(d[i]), "+r"(d[i + 1]), "+r"(d[i + 2]), "+r"(d[i + 3])
#define O4(d, i) "=r"(d[i]), "=r"(d[i + 1]), "=r"(d[i + 2]), "=r"(d[i + 3])
#define D26 "{%0,%1,%2,%3,%4,%5,%6,%7,%8,%9,%10,%11,%12,%13,%14,%15,%16,%17,%18,%19,%20,%21,%22,%23,%24,%25},"
#define D24 "{%0,%1,%2,%3,%4,%5,%6,%7,%8,%9,%10,%11,%12,%13,%14,%15,%16,%17,%18,%19,%20,%21,%22,%23},"
#define D14 "{%0,%1,%2,%3,%4,%5,%6,%7,%8,%9,%10,%11,%12,%13},"

template <int SC, int TB>
__device__ __forceinline__ void wgmma(uint32_t (&d)[24], const uint32_t* a, uint64_t db) {
  if (SC == 2)
    asm volatile("{\n.reg .pred p;\nsetp.eq.u32 p, %30, 0x7fffffff;\n"
                 "wgmma.mma_async.sync.aligned.m64n96k16.f16.f16.f16 " D24 "{%24,%25,%26,%27}, %28, p, 1, 1, %29;\n}"
                 : R4(d, 0), R4(d, 4), R4(d, 8), R4(d, 12), R4(d, 16), R4(d, 20)
                 : "r"(a[0]), "r"(a[1]), "r"(a[2]), "r"(a[3]), "l"(db), "n"(TB), "r"(gridDim.x));
  else if (SC)
    asm volatile("wgmma.mma_async.sync.aligned.m64n96k16.f16.f16.f16 " D24 "{%24,%25,%26,%27}, %28, 1, 1, 1, %29;"
                 : R4(d, 0), R4(d, 4), R4(d, 8), R4(d, 12), R4(d, 16), R4(d, 20)
                 : "r"(a[0]), "r"(a[1]), "r"(a[2]), "r"(a[3]), "l"(db), "n"(TB));
  else
    asm volatile("wgmma.mma_async.sync.aligned.m64n96k16.f16.f16.f16 " D24 "{%24,%25,%26,%27}, %28, 0, 1, 1, %29;"
                 : O4(d, 0), O4(d, 4), O4(d, 8), O4(d, 12), O4(d, 16), O4(d, 20)
                 : "r"(a[0]), "r"(a[1]), "r"(a[2]), "r"(a[3]), "l"(db), "n"(TB));
}
template <int SC, int TB>
__device__ __forceinline__ void wgmma(uint32_t (&d)[26], const uint32_t* a, uint64_t db) {
  if (SC)
    asm volatile("wgmma.mma_async.sync.aligned.m64n104k16.f16.f16.f16 " D26 "{%26,%27,%28,%29}, %30, 1, 1, 1, 0;"
                 : R4(d, 0), R4(d, 4), R4(d, 8), R4(d, 12), R4(d, 16), R4(d, 20), "+r"(d[24]), "+r"(d[25])
                 : "r"(a[0]), "r"(a[1]), "r"(a[2]), "r"(a[3]), "l"(db));
  else
    asm volatile("wgmma.mma_async.sync.aligned.m64n104k16.f16.f16.f16 " D26 "{%26,%27,%28,%29}, %30, 0, 1, 1, 0;"
                 : O4(d, 0), O4(d, 4), O4(d, 8), O4(d, 12), O4(d, 16), O4(d, 20), "=r"(d[24]), "=r"(d[25])
                 : "r"(a[0]), "r"(a[1]), "r"(a[2]), "r"(a[3]), "l"(db));
}
template <int SC, int TB>
__device__ __forceinline__ void wgmma(uint32_t (&d)[16], const uint32_t* a, uint64_t db) {
  if (SC)
    asm volatile("wgmma.mma_async.sync.aligned.m64n56k16.f16.f16.f16 " D14 "{%14,%15,%16,%17}, %18, 1, 1, 1, 0;"
                 : R4(d, 0), R4(d, 4), R4(d, 8), "+r"(d[12]), "+r"(d[13])
                 : "r"(a[0]), "r"(a[1]), "r"(a[2]), "r"(a[3]), "l"(db));
  else
    asm volatile("wgmma.mma_async.sync.aligned.m64n56k16.f16.f16.f16 " D14 "{%14,%15,%16,%17}, %18, 0, 1, 1, 0;"
                 : O4(d, 0), O4(d, 4), O4(d, 8), "=r"(d[12]), "=r"(d[13])
                 : "r"(a[0]), "r"(a[1]), "r"(a[2]), "r"(a[3]), "l"(db));
}
template <int SC, int OFF, int CH, int ND>
__device__ __forceinline__ void gemm(uint32_t (&d)[ND], const uint32_t* a, uint64_t db) {
  asm volatile("" : "+l"(db));
  wg_fence();
  wgmma<SC, 0>(d, a, db + OFF / 16);
#pragma unroll
  for (int k = 1; k < 6; k++) wgmma<1, 0>(d, a + 4 * k, db + (OFF + (k >> 1) * CH + (k & 1) * 32) / 16);
  wg_commit();
}
__device__ __forceinline__ void lds128(uint32_t* r, uint32_t a) {
  asm volatile("ld.shared.v4.b32 {%0,%1,%2,%3}, [%4];" : "=r"(r[0]), "=r"(r[1]), "=r"(r[2]), "=r"(r[3]) : "r"(a) : "memory");
}
__device__ __forceinline__ void ldsm4(uint32_t* r, uint32_t a) {
  asm volatile("ldmatrix.sync.aligned.m8n8.x4.shared.b16 {%0,%1,%2,%3}, [%4];"
               : "=r"(r[0]), "=r"(r[1]), "=r"(r[2]), "=r"(r[3]) : "r"(a) : "memory");
}
__device__ __forceinline__ void stsm4(uint32_t a, const uint32_t* r) {
  asm volatile("stmatrix.sync.aligned.m8n8.x4.shared.b16 [%0], {%1,%2,%3,%4};" ::"r"(a), "r"(r[0]), "r"(r[1]), "r"(r[2]), "r"(r[3])
               : "memory");
}
__device__ __forceinline__ void stg3(uint8_t* p, const uint32_t* r, uint32_t off) {
  asm volatile("{\n.reg .pred p;\nsetp.eq.u32 p, %13, 0;\n@p st.global.v4.b32 [%0], {%1,%2,%3,%4};\n"
               "@p st.global.v4.b32 [%0+64], {%5,%6,%7,%8};\n@p st.global.v4.b32 [%0+128], {%9,%10,%11,%12};\n}" ::"l"(p),
               "r"(r[0]), "r"(r[1]), "r"(r[2]), "r"(r[3]), "r"(r[4]), "r"(r[5]), "r"(r[6]), "r"(r[7]), "r"(r[8]), "r"(r[9]), "r"(r[10]), "r"(r[11]),
               "r"(off) : "memory");
}
__device__ __forceinline__ uint32_t pack_h2(float lo, float hi) {
  uint32_t r; asm("cvt.rn.f16x2.f32 %0, %1, %2;" : "=r"(r) : "f"(hi), "f"(lo)); return r;
}
__device__ __forceinline__ uint32_t pack_h2_sat(float lo, float hi) {
  uint32_t r; asm("cvt.rn.satfinite.f16x2.f32 %0, %1, %2;" : "=r"(r) : "f"(hi), "f"(lo)); return r;
}
__device__ __forceinline__ uint32_t pack_bf2(float lo, float hi) {
  uint32_t r; asm("cvt.rn.bf16x2.f32 %0, %1, %2;" : "=r"(r) : "f"(hi), "f"(lo)); return r;
}
__device__ __forceinline__ __half2 as_h2(uint32_t v) { return *reinterpret_cast<__half2*>(&v); }
__device__ __forceinline__ uint32_t as_u(__half2 v) { return *reinterpret_cast<uint32_t*>(&v); }
__device__ __forceinline__ float2 unpack_h2(uint32_t v) { return __half22float2(as_h2(v)); }
__device__ __forceinline__ float low_f(uint32_t v) { return __low2float(as_h2(v)); }
__device__ __forceinline__ uint32_t h2ex2(uint32_t v) { uint32_t r; asm("ex2.approx.f16x2 %0, %1;" : "=r"(r) : "r"(v)); return r; }
__device__ __forceinline__ uint32_t h2max(uint32_t a, uint32_t b) { return as_u(__hmax2(as_h2(a), as_h2(b))); }
__device__ __forceinline__ uint32_t h2add(uint32_t a, uint32_t b) { return as_u(__hadd2(as_h2(a), as_h2(b))); }
__device__ __forceinline__ uint32_t h2sub(uint32_t a, uint32_t b) { return as_u(__hsub2(as_h2(a), as_h2(b))); }
__device__ __forceinline__ uint32_t h2mul(uint32_t a, uint32_t b) { return as_u(__hmul2(as_h2(a), as_h2(b))); }
__device__ __forceinline__ uint32_t h2neg(uint32_t a) { return as_u(__hneg2(as_h2(a))); }
__device__ __forceinline__ uint32_t h2fma(uint32_t a, uint32_t b, uint32_t c) { return as_u(__hfma2(as_h2(a), as_h2(b), as_h2(c))); }
__device__ __forceinline__ uint32_t lo2(uint32_t v) { return as_u(__low2half2(as_h2(v))); }
__device__ __forceinline__ uint32_t hi2(uint32_t v) { return as_u(__high2half2(as_h2(v))); }
__device__ __forceinline__ uint32_t fold_add(uint32_t a, uint32_t b) { return h2add(__byte_perm(a, b, 0x5410), __byte_perm(a, b, 0x7632)); }
__device__ __forceinline__ uint32_t sel(uint32_t p, uint32_t a, uint32_t b) {
  uint32_t r; asm("{\n.reg .pred p;\nsetp.ne.u32 p, %3, 0;\nselp.b32 %0, %1, %2, p;\n}" : "=r"(r) : "r"(a), "r"(b), "r"(p)); return r;
}
__device__ __forceinline__ float sel4(uint32_t c, float a0, float a1, float a2, float a3) {
  return __uint_as_float(sel(c & 2, sel(c & 1, __float_as_uint(a3), __float_as_uint(a2)), sel(c & 1, __float_as_uint(a1), __float_as_uint(a0))));
}
__device__ __forceinline__ float rcp_fast(float v) { float r; asm("rcp.approx.ftz.f32 %0, %1;" : "=f"(r) : "f"(v)); return r; }
__device__ __forceinline__ float rsq_fast(float v) { float r; asm("rsqrt.approx.ftz.f32 %0, %1;" : "=f"(r) : "f"(v)); return r; }
__device__ __forceinline__ uint32_t shfl_x(uint32_t v, int m) { return __shfl_xor_sync(0xffffffffu, v, m); }
__device__ __forceinline__ uint32_t shfl_q(uint32_t v, int i) { return __shfl_sync(0xffffffffu, v, i, 4); }
__device__ __forceinline__ float quad_sum(float v) {
  v += __shfl_xor_sync(0xffffffffu, v, 1);
  return v + __shfl_xor_sync(0xffffffffu, v, 2);
}
#define PAR(ring, f) __uint_as_float(lds32((ring) + kPar + offsetof(Params, f)))
__device__ __forceinline__ uint32_t dup_h2(float v) { return pack_h2(v, v); }

constexpr float kEps96 = 1e-5f * 96.f * 96.f;
__device__ __forceinline__ float2 stat_f32(uint32_t e) {
  const float2 h = unpack_h2(e);
  return make_float2(__uint_as_float(sel(e & 0x8000u, (e << 16) & 0x7fff0000u, __float_as_uint(h.x))),
                     __uint_as_float(sel(e & 0x8000u, e & 0xffff0000u, __float_as_uint(h.y))));
}

struct Tile {
  uint32_t ring, a;
  uint32_t next;
  uint32_t n;
  int live;
  uint32_t stat, wrap;
  uint32_t flag;
  uint32_t gate;
};
struct TPar { float kt, sgmin, outmax; };

__device__ __forceinline__ uint32_t swz(uint32_t r, int t) { return fresh(r ^ (((r >> 3) + 8 * t) & 0x30)); }
__device__ __forceinline__ void load_rows(uint32_t* x0, uint32_t* x1, uint32_t ring, uint32_t r, int t) {
  const uint32_t a0 = swz(r, t), a1 = swz(r, t + 1), u0 = ring + t * kPlane, u1 = u0 + kPlane;
  lds128(x0, a0 + u0); lds128(x1, a1 + u1);
  lds128(x0 + 4, fresh(a0 ^ 32) + (u0 + kChunk)); lds128(x1 + 4, fresh(a1 ^ 32) + (u1 + kChunk));
  lds128(x0 + 8, a0 + (u0 + 2 * kChunk)); lds128(x1 + 8, a1 + (u1 + 2 * kChunk));
}
__device__ __forceinline__ void to_half(uint32_t (&z)[24], const uint32_t* x, int o0, int o1) {
#pragma unroll
  for (int j = 0; j < 24; j += 2) {
    const int o = j < 12 ? 2 * j : 2 * j - 23;
    if (o < o0 || o >= o1) continue;
    uint32_t t;
    asm("cvt.rz.f16x2.f32 %0, %1, %2;" : "=r"(t) : "f"(__uint_as_float(x[j + 1])), "f"(__uint_as_float(x[j])));
    z[o] = fresh(pack_h2(__uint_as_float(x[j] << 16), __uint_as_float(x[j + 1] << 16)));
    z[o + 2] = fresh(t & 0xfff8fff8u);
  }
}
__device__ __forceinline__ void load_general(uint32_t (&z)[24], uint32_t ring, uint32_t r, int t, float& ie0, float& ie1, float& m0, float& m1) {
  float acc[48];
  uint32_t x0[12], x1[12];
  load_rows(x0, x1, ring, r, t);
#pragma unroll
  for (int j = 0; j < 12; j++) {
    acc[4 * j] = __uint_as_float(x0[j] << 16); acc[4 * j + 1] = __uint_as_float(x0[j] & 0xffff0000u);
    acc[4 * j + 2] = __uint_as_float(x1[j] << 16); acc[4 * j + 3] = __uint_as_float(x1[j] & 0xffff0000u);
  }
  float s[4], q[4];
#pragma unroll
  for (int e = 0; e < 4; e++) { s[e] = acc[e]; q[e] = acc[e] * acc[e]; }
#pragma unroll
  for (int j = 4; j < 48; j++) { s[j & 3] += acc[j]; q[j & 3] = fmaf(acc[j], acc[j], q[j & 3]); }
  const float s0 = quad_sum(s[0] + s[1]), s1 = quad_sum(s[2] + s[3]), q0 = quad_sum(q[0] + q[1]), q1 = quad_sum(q[2] + q[3]);
  const float u0 = rsq_fast(fmaxf(fmaf(-s0, s0, fmaf(q0, 96.f, kEps96)), kEps96));
  const float u1 = rsq_fast(fmaxf(fmaf(-s1, s1, fmaf(q1, 96.f, kEps96)), kEps96));
  const float n0 = -s0 * u0, n1 = -s1 * u1;
  ie0 = 96.f * u0; ie1 = 96.f * u1;
  m0 = s0 * (1.f / 96.f); m1 = s1 * (1.f / 96.f);
#pragma unroll
  for (int j = 0; j < 12; j++) {
    const int o = 8 * (j >> 1) + (j & 1);
    z[2 * j] = pack_h2(fmaf(acc[o], ie0, n0), fmaf(acc[o + 4], ie0, n0));
    z[2 * j + 1] = pack_h2(fmaf(acc[o + 2], ie1, n1), fmaf(acc[o + 6], ie1, n1));
  }
}
template <bool kDown>
__device__ __forceinline__ uint32_t sumsq2(const uint32_t* z) {
  uint32_t q0, q1;
#pragma unroll
  for (int j = 0; j < 12; j++) {
    const uint32_t u = kDown ? h2mul(z[2 * j], 0x1c001c00u) : z[2 * j], v = kDown ? h2mul(z[2 * j + 1], 0x1c001c00u) : z[2 * j + 1];
    q0 = j ? h2fma(u, u, q0) : h2mul(u, u); q1 = j ? h2fma(v, v, q1) : h2mul(v, v);
  }
  return fold_add(q0, q1);
}
template <bool kDown>
__device__ __forceinline__ float row_sumsq(const uint32_t* z0, const uint32_t* z1, uint32_t c) {
  const uint32_t a = sumsq2<kDown>(z0), b = sumsq2<kDown>(z1);
  uint32_t t = h2add(sel(c & 2, b, a), shfl_x(sel(c & 2, a, b), 2));
  t = h2add(t, shfl_x(t, 1));
  return low_f(sel(c & 1, t >> 16, t));
}
__device__ __forceinline__ void scores2(const uint32_t* q, const uint32_t* z0, const uint32_t* z1, uint32_t* f) {
  uint32_t d[8];
#pragma unroll
  for (int j = 0; j < 12; j++) {
    const uint32_t kk[4] = {z0[2 * j], z0[2 * j + 1], z1[2 * j], z1[2 * j + 1]};
#pragma unroll
    for (int e = 0; e < 4; e++) {
      d[e] = j ? h2fma(q[2 * j], kk[e], d[e]) : h2mul(q[2 * j], kk[e]);
      d[4 + e] = j ? h2fma(q[2 * j + 1], kk[e], d[4 + e]) : h2mul(q[2 * j + 1], kk[e]);
    }
  }
#pragma unroll
  for (int e = 0; e < 4; e++) f[e] = fold_add(d[2 * e], d[2 * e + 1]);
}
struct Xch { uint32_t keep[2], got[2]; };
__device__ __forceinline__ Xch pair_send(const uint32_t* a, const uint32_t* b, uint32_t c, int m) {
  Xch x;
#pragma unroll
  for (int e = 0; e < 2; e++) { x.keep[e] = fresh(sel(c & m, b[e], a[e])); x.got[e] = shfl_x(sel(c & m, a[e], b[e]), m); }
  return x;
}
__device__ __forceinline__ void pair_recv(uint32_t* k, const Xch& x) { k[0] = h2add(x.keep[0], x.got[0]); k[1] = h2add(x.keep[1], x.got[1]); }
__device__ __forceinline__ void mix2(uint32_t* y, const uint32_t* v, uint32_t c0, uint32_t c1) {
#pragma unroll
  for (int j = 0; j < 12; j++) {
    y[2 * j] = h2fma(v[2 * j + 1], hi2(c0), h2fma(v[2 * j], lo2(c0), y[2 * j]));
    y[2 * j + 1] = h2fma(v[2 * j + 1], hi2(c1), h2fma(v[2 * j], lo2(c1), y[2 * j + 1]));
  }
  pin<24>(y);
}
__device__ __forceinline__ void norm_store(uint32_t* y, uint32_t r0, uint32_t r1, uint32_t r, int t) {
#pragma unroll
  for (int j = 0; j < 12; j++) { y[2 * j] = h2fma(y[2 * j], lo2(r0), hi2(r0)); y[2 * j + 1] = h2fma(y[2 * j + 1], lo2(r1), hi2(r1)); }
  const uint32_t ma = swz(r, t), mb = fresh(ma ^ 32), u = t * kPlane;
  stsm4(ma + u, y); stsm4(mb + u, y + 4);
  stsm4(mb + (u + kChunk), y + 8); stsm4(ma + (u + kChunk), y + 12);
  stsm4(ma + (u + 2 * kChunk), y + 16); stsm4(mb + (u + 2 * kChunk), y + 20);
}

template <bool kAlways>
__device__ __forceinline__ void gate_open(uint32_t id) {
  if (kAlways) asm volatile("barrier.cta.arrive.aligned %0, 256;" ::"r"(id) : "memory");
  else asm volatile("{\n.reg .pred p;\nsetp.ne.u32 p, %0, 0;\n@p barrier.cta.arrive.aligned %0, 256;\n}" ::"r"(id) : "memory");
}

struct TState { uint32_t z0[24], z1[24], mu, bad; float ie, mm, mz, qq; };
template <bool kDirect>
__device__ __forceinline__ void temporal(TState& S, uint64_t da, const Tile& T, const TPar& P, bool scaled, uint32_t lane, uint32_t& lst) {
  uint32_t (&z0)[24] = S.z0, (&z1)[24] = S.z1;
  const uint32_t c = lane;
  const uint32_t a0 = T.a + lane * 16 + (lane >= 4 * T.n ? T.next : 0);
  uint32_t q0[26], q1[24], v0[24], w1[26], nn = 0, ng = 0, ca0 = 0, ca1 = 0;
  uint32_t* const v1 = w1 + 2;
  float ie = 1.f, mm = 0.f;
  bool tiny = false;
  if (kDirect) {
    uint32_t x[48];
    load_rows(x, x + 12, T.ring, a0, 0);
    to_half(z0, x, 0, 16);
    sfence(lst);
    load_rows(x + 24, x + 36, T.ring, a0, 2);
    to_half(z0, x, 16, 24);
    gemm<0, 0, kAtChunk>(q0, z0, da);
    sfence(lst);
    to_half(z1, x + 24, 0, 24);
    const uint32_t n0 = sumsq2<false>(z0), n1 = sumsq2<false>(z1);
    nn = fresh(sel(c & 2, n1, n0)); ng = shfl_x(sel(c & 2, n0, n1), 2);
    pin<24>(z1); sfence(lst);
  } else {
    float e[4], m[4];
    load_general(z0, T.ring, a0, 0, e[0], e[1], m[0], m[1]);
    pin<24>(z0); sfence(lst);
    load_general(z1, T.ring, a0, 2, e[2], e[3], m[2], m[3]);
    ie = sel4(c, e[0], e[1], e[2], e[3]);
    mm = sel4(c, m[0], m[1], m[2], m[3]);
    tiny = __any_sync(0xffffffffu, ie * P.kt > 400.f);
    if (tiny) {
      float u = 0.f;
#pragma unroll
      for (int r = 0; r < 4; r++) {
        float t = 0.f;
#pragma unroll
        for (int j = 0; j < 12; j++) { const float2 f = unpack_h2((r & 2 ? z1 : z0)[2 * j + (r & 1)]); t = fmaf(f.x, f.x, fmaf(f.y, f.y, t)); }
        u = fmaxf(u, quad_sum(t));
      }
      const float t = fminf(ie, 9.8f * rsq_fast(fmaxf(u, 2e-7f)) * rcp_fast(fresh(P.kt)));
      const uint32_t a = pack_h2(__fdividef(t, ie), 0.f);
      ca0 = __byte_perm(shfl_q(a, 0), shfl_q(a, 1), 0x5410); ca1 = __byte_perm(shfl_q(a, 2), shfl_q(a, 3), 0x5410);
      ie = t;
    }
    gemm<0, 0, kAtChunk>(q0, z0, da);
  }
  uint32_t f[4], k0[2], k1[2], sk[2];
  wg_wait(); pin<26>(q0);
  gemm<0, 0, kAtChunk>(q1, z1, da);
  gate_open<kDirect>(T.gate);
  sfence(lst);
  if (kDirect) { nn = h2add(nn, ng); ng = shfl_x(nn, 1); sfence(lst); }
  scores2(q0, z0, z1, f);
  const uint32_t nu0 = fresh(__byte_perm(q0[24], q0[25], 0x7632)), m01 = fresh(sel(c & 1, q0[25], q0[24]));
  Xch xc = pair_send(f, f + 2, c, 1);
  sfence(lst);
  wg_wait(); pin<24>(q1);
  gemm<0, kOffWt - 512, kAtChunk>(w1, z1, da);
  sfence(lst);
  pair_recv(k0, xc);
  float e2 = 0.f, lim = 0.f;
  if (kDirect) {
    nn = h2add(nn, ng);
    e2 = fresh(fmaf(low_f(sel(c & 1, nn >> 16, nn)), 1.f / 96.f, 1e-5f));
    lim = fresh(e2 <= 4.f ? fmaxf(0.5f * e2, 4e-4f) : __uint_as_float(0x7fffffffu));
  }
  scores2(q1, z0, z1, f);
  xc = pair_send(f, f + 2, c, 1);
  pin<2>(k0); sfence(lst);
  wg_wait(); pin<26>(w1);
  float mz = 0.f, d2 = 0.f;
  if (kDirect) {
    mz = low_f(sel(c & 2, sel(c & 1, w1[1], w1[0]), m01));
    d2 = fmaf(-mz, mz, e2);
    asm volatile("{\n.reg .pred p;\nsetp.lt.s32 p, %3, %4;\nsetp.ltu.and.f32 p, %1, %2, p;\n@p st.volatile.shared.f32 [%0], %2;\n}" ::"r"(T.flag), "f"(d2),
                 "f"(lim), "r"(lane), "r"(T.live) : "memory");
  }
  gemm<0, kOffWt, kAtChunk>(v0, z0, da);
  sfence(lst);
  uint32_t cw[8], mu;
  {
    uint32_t rc = 0, r0 = 0, r1 = 0;
    if (kDirect) {
      const float r = rsq_fast(d2);
      rc = pack_h2(r, r);
      r0 = __byte_perm(shfl_q(rc, 0), shfl_q(rc, 1), 0x5410); r1 = __byte_perm(shfl_q(rc, 2), shfl_q(rc, 3), 0x5410);
    }
    pair_recv(k1, xc);
    pair_recv(sk, pair_send(k0, k1, c, 2));
    if (kDirect) { sk[0] = h2mul(sk[0], r0); sk[1] = h2mul(sk[1], r1); }
    uint32_t mx = h2max(sk[0], sk[1]);
    mx = h2max(lo2(mx), hi2(mx));
    if (kDirect) {
      const uint32_t nm = h2mul(h2neg(mx), rc);
      sk[0] = h2fma(sk[0], rc, nm); sk[1] = h2fma(sk[1], rc, nm);
    } else {
      sk[0] = h2sub(sk[0], mx); sk[1] = h2sub(sk[1], mx);
      if (scaled) {
        const uint32_t cs = dup_h2(PAR(T.ring, cS_t));
        sk[0] = h2mul(sk[0], cs); sk[1] = h2mul(sk[1], cs);
      }
    }
    sk[0] = h2ex2(sk[0]); sk[1] = h2ex2(sk[1]);
    const uint32_t sm = h2add(sk[0], sk[1]);
    const float iv = (kDirect ? P.kt : P.kt * ie) * rcp_fast(low_f(h2add(lo2(sm), hi2(sm))));
    const uint32_t inv = pack_h2(iv, iv);
    if (kDirect) { sk[0] = h2mul(sk[0], r0); sk[1] = h2mul(sk[1], r1); }
    sk[0] = h2mul(sk[0], inv); sk[1] = h2mul(sk[1], inv);
#pragma unroll
    for (int i = 0; i < 4; i++) { cw[2 * i] = shfl_q(sk[0], i); cw[2 * i + 1] = shfl_q(sk[1], i); }
    mu = h2fma(sk[1], __byte_perm(w1[0], w1[1], 0x7632), h2mul(sk[0], nu0));
    mu = h2add(lo2(mu), hi2(mu));
  }
  uint32_t bad = 0;
  if (kDirect) {
    mix2(z1, v1, cw[5], cw[7]);
    sfence(lst);
    wg_wait(); pin<24>(v0);
    mix2(z1, v0, cw[4], cw[6]);
    sfence(lst);
    bad = lds32(T.flag);
  } else {
    wg_wait(); pin<24>(v0);
    if (tiny) {
#pragma unroll
      for (int j = 0; j < 12; j++) {
        z0[2 * j] = h2mul(z0[2 * j], lo2(ca0)); z0[2 * j + 1] = h2mul(z0[2 * j + 1], hi2(ca0));
        z1[2 * j] = h2mul(z1[2 * j], lo2(ca1)); z1[2 * j + 1] = h2mul(z1[2 * j + 1], hi2(ca1));
      }
    }
    mix2(z1, v1, cw[5], cw[7]);
    mix2(z1, v0, cw[4], cw[6]);
  }
  mix2(z0, v1, cw[1], cw[3]);
  mix2(z0, v0, cw[0], cw[2]);
  S.qq = row_sumsq<false>(z0, z1, c);
  S.mu = mu; S.bad = bad; S.ie = ie; S.mm = mm; S.mz = mz;
}
__device__ __forceinline__ bool irregular(const TState& S, const Tile& T, uint32_t lane) {
  return __any_sync(0xffffffffu, (!(S.qq < 65000.f) & ((int)lane < T.live)) | (S.bad != 0));
}
__device__ __forceinline__ void resum(TState& S, uint32_t lane) {
  const float q2 = row_sumsq<true>(S.z0, S.z1, lane) * 65536.f;
  S.qq = S.qq < 65000.f ? S.qq : q2;
}
template <bool kDirect>
__device__ __forceinline__ void temporal_out(TState& S, const Tile& T, uint32_t slot, const TPar& P, uint32_t lane, uint32_t lst) {
  uint32_t (&z0)[24] = S.z0, (&z1)[24] = S.z1;
  const uint32_t mu = S.mu;
  const float ie = S.ie, mz = S.mz, qq = S.qq;
  float mm = S.mm;
  const float rf = kDirect ? rsq_fast(fmaxf(fmaf(-mz, mz, fmaf(qq, 1.f / 96.f, 1e-5f)), 1e-5f)) : rsq_fast(fmaf(qq, 1.f / 96.f, 1e-5f * ie * ie));
  const uint32_t rn = pack_h2_sat(rf, -mz * rf);
  uint32_t rr[4];
#pragma unroll
  for (int i = 0; i < 4; i++) rr[i] = shfl_q(rn, i);
  lane = fresh(lane);
  const uint32_t ma = fresh(T.ring + T.a) + lst + ((lane & 7) >= T.n ? T.next : 0);
  norm_store(z0, rr[0], rr[1], ma, 0);
  const float2 rm = unpack_h2(rn);
  const float sg = rcp_fast(kDirect ? rm.x : rm.x * ie);
  mm = kDirect ? fmaf(-rm.y, sg, low_f(mu)) : fmaf(low_f(mu) * rm.x, sg, mm);
  const uint32_t bars = slot + (lane >= 4 * T.n ? T.next + kPlane : 0);
  const bool ok = (sg >= P.sgmin) & (fmaf(sg, 9.8f, fabsf(mm)) < P.outmax);
  asm volatile("{\n.reg .pred p;\nsetp.lt.s32 p, %2, %3;\n@p st.shared.b32 [%0], %1;\n}" ::"r"(
                   T.stat + fresh((lane & 3) * (kSlot - 1) + lane + (lane >= 4 * T.n ? T.wrap : 0))),
               "r"(sel(ok, pack_h2(sg, mm), pack_bf2(sg, mm) | 0x8000u)), "r"(lane), "r"(T.live) : "memory");
  asm volatile("{\n.reg .pred p;\nsetp.eq.u32 p, %1, 0;\n@p st.shared.b32 [%0], %0;\n}" ::"r"(bars + kWide), "r"((uint32_t)ok) : "memory");
  norm_store(z1, rr[2], rr[3], ma, 2);
}

__device__ __forceinline__ void run_T(uint32_t ring, uint64_t d0, uint64_t d1, uint32_t nfull, uint32_t nrem, bool helper, int wg, int wp, uint32_t lane,
                                      const TPar& P, bool scaled, uint32_t pdir) {
  uint32_t lst = (lane & 7) * 64 + (lane & 8) * (kPlane / 8) + (lane & 16);
  uint32_t p0 = 32 * (wg & 1) + (helper ? 0 : 64) + 8 * wp;
  uint32_t npx = 49 * nfull, pstop = npx - 6 * 49 + 8 * wp;
  if (helper) pstop = 0;
  uint32_t pgap = 0;
  sfence(lane);
  Tile T;
  T.ring = ring;
  T.flag = ring + wg * kSlot + kFlag;
  T.gate = wg == 3 ? 6 : 5 + wg;
  while (true) {
    const uint32_t iw = (p0 * 21400u) >> 20, ow = p0 - 49 * iw;
    const uint32_t slot = ring + (iw & 3) * kSlot, dn = (iw & 3) == 3 ? -3 * kSlot : kSlot;
    asm volatile("{\n.reg .pred p;\nsetp.eq.u32 p, %1, 0;\n@p barrier.cta.sync.aligned %0, 256;\n}" ::"r"(6 - (wg & 1)), "r"((uint32_t)helper) : "memory");
    mbar_wait(slot + kFull, iw >> 2);
    if (ow > 41) mbar_wait(slot + dn + kFull, (iw + 1) >> 2);
    T.a = (iw & 3) * kSlot + ow * 64; T.next = dn - kPlane; T.n = 49 - ow;
    T.live = 4 * (npx - p0);
    T.stat = ring + kXBytes + (p0 - 196 * (iw >> 2)) * 4; T.wrap = (iw & 3) == 3 ? -784 : 0;
    lane = fresh(lane);
    {
      TState S;
      Tile G = T;
      if (p0 >= pdir) {
        temporal<true>(S, d0, T, P, false, lane, lst);
        if (irregular(S, T, lane)) {
          if (__any_sync(0xffffffffu, S.bad != 0)) goto redo;
          resum(S, lane);
        }
        temporal_out<true>(S, T, slot, P, lane, lst);
        goto stored;
      redo:
        asm volatile("barrier.cta.sync.aligned %0, 128;" ::"r"(wg + 1) : "memory");
        asm volatile("st.shared.b32 [%0], %1;\nfence.acq_rel.cta;" ::"r"(T.flag), "r"(0) : "memory");
        G.gate = 0;
        pgap = p0 == pdir ? 4 * pgap + 64 : 0;
        pdir = p0 + 64 + pgap;
      }
      temporal<false>(S, d1, G, P, scaled, lane, lst);
      if (irregular(S, T, lane)) resum(S, lane);
      temporal_out<false>(S, T, slot, P, lane, lst);
    }
  stored:
    const uint32_t pn = __shfl_sync(0xffffffffu, p0 + 64, 0);
    bool last = false;
    if (pn >= pstop) {
      if (helper) last = true;
      else if (pstop < npx - 4 * 49) {
        if (((wg & 1) | wp | lane) == 0) {
          const uint32_t nb = gridDim.x, nwh = min(max((int)(2 * nrem - nb), (int)(nrem / 2)), nrem);
          const uint32_t r = atomicAdd(&g_par.ticket, 1u), j = r - nwh;
          sts32(ring + kExtra, r < nwh ? (nfull * nb + r) * 4 + 3 : j < 2 * (nrem - nwh) ? (nfull * nb + nwh + (j >> 1)) * 4 + 1 + (j & 1) : 0);
        }
        __syncwarp();
        pstop = npx - 2 * 49 + 8 * wp;
      } else if (pstop < npx) {
        if (__shfl_sync(0xffffffffu, lds32(ring + kExtra), 0)) npx += 49;
        pstop = npx + 8 * wp;
      } else last = true;
    }
    asm volatile("fence.proxy.async.shared::cta;" ::: "memory");
    __syncwarp();
    mbar_arrive(slot + kDone + (fresh(lane) >= 4 * T.n ? dn : 0), lane & 3);
    __syncwarp();
    if (last) break;
    p0 = pn;
  }
}

struct Frame {
  bool light;
  uint32_t sta;
  uint32_t oo;
  uint32_t e0, e1;
};
__device__ __forceinline__ uint32_t frame_init(Frame& F, uint32_t ring, uint32_t t, int wp, int lane) {
  wp = (wp + t) & 3;
  F.light = wp == 3;
  F.sta = ring + t * kSlot + kXBytes + 64 * wp;
  const uint32_t r = 16 * wp + (lane >> 2);
  F.oo = ((r / 7) * (kW - 7) + r) * 192u + (lane & 3) * 16 + (((((r + 8) / 7 - r / 7) * (kW - 7) + 8) * 3u) << 20);
  F.e0 = F.e1 = 0;
  const uint32_t am = t * kPlane + wp * 1024 + ((lane * 65) & 0x3d0);
  return F.light && (lane & 15) ? kZero : am ^ ((am >> 3) & 0x30);
}
template <bool F>
__device__ __forceinline__ void load_frame(uint32_t (&v)[24], uint32_t ma, uint32_t slot, uint32_t& tid) {
  const uint32_t st = ma < kXBytes ? kChunk : 0, mb = ma ^ 32;
  uint32_t a[6] = {ma, mb, mb + st, ma + st, ma + 2 * st, mb + 2 * st};
  pin<6>(a);
  if (F) sfence(tid);
#pragma unroll
  for (int k = 0; k < 6; k++) ldsm4(v + 4 * k, slot + a[k]);
}
__device__ __forceinline__ void load_block(uint32_t (&v)[24], uint32_t ma, uint32_t slot) {
  const uint32_t mb = fresh(ma ^ 32);
  ldsm4(v, ma + slot); ldsm4(v + 4, mb + slot);
  ldsm4(v + 8, mb + (slot + kChunk)); ldsm4(v + 12, ma + (slot + kChunk));
  ldsm4(v + 16, ma + (slot + 2 * kChunk)); ldsm4(v + 20, mb + (slot + 2 * kChunk));
}
__device__ __forceinline__ void load_light(uint32_t (&v)[24], uint32_t t, uint32_t slot, uint32_t tid) {
  const uint32_t r = t * kPlane + 48 * 64, a0 = ((tid & 3) << 2) | ((r >> 3) & 0x30), u = slot + r, off = tid & 28;
  uint32_t a[4] = {a0, a0 ^ 16, a0 ^ 32, a0 ^ 48};
  pin<4>(a);
#pragma unroll
  for (int j = 0; j < 12; j++) {
    asm volatile("mov.b32 %0, 0;" : "=r"(v[2 * j + 1]));
    asm volatile("{\n.reg .pred p;\nsetp.eq.u32 p, %2, 0;\nmov.b32 %0, 0;\n@p ld.shared.b32 %0, [%1];\n}"
                 : "=r"(v[2 * j]) : "r"(a[(j & 3) ^ (j & 4 ? 2 : 0)] + (u + (j >> 2) * kChunk)), "r"(off) : "memory");
  }
}
__device__ __forceinline__ void load_stats(Frame& F, uint32_t ia, uint32_t tid) {
  const uint32_t a = fresh(tid & 0x1c), u = F.sta + ia * 196;
  F.e0 = lds32(a + u);
  F.e1 = lds32(a + (u + 32));
}
template <int OFF>
__device__ __forceinline__ void gemm_u(uint32_t (&u)[24], const uint32_t* s, uint64_t db) {
  constexpr uint32_t kMN = (((kChunk >> 4) - 1) << 16) + OFF / 16;
  asm volatile("" : "+l"(db));
  wg_fence();
  wgmma<2, 1>(u, s, db + kMN); wgmma<1, 1>(u, s + 4, db + kMN + 64); wgmma<1, 1>(u, s + 8, db + kMN + 128); wgmma<1, 1>(u, s + 12, db + kMN + 192);
  wg_commit();
}
__device__ __forceinline__ uint32_t key48(uint32_t (&s)[16], uint32_t tid) {
  return fresh(sel(tid & 3, 0xfc00fc00u, __byte_perm(s[12], s[13], 0x5410)));
}
__device__ __forceinline__ uint32_t amax3(uint32_t a, uint32_t b, uint32_t c) {
  return as_u(__hmax2(__hmax2(__habs2(as_h2(a)), __habs2(as_h2(b))), __habs2(as_h2(c))));
}
struct Quad { uint32_t v[4]; };
__device__ __forceinline__ void sub_max(uint32_t (&s)[16], uint32_t& t) {
  const uint32_t x0 = h2max(h2max(h2max(s[0], s[2]), h2max(s[4], s[6])), h2max(s[8], s[10]));
  const uint32_t x1 = h2max(h2max(h2max(s[1], s[3]), h2max(s[5], s[7])), h2max(s[9], s[11]));
  uint32_t mx = h2max(h2max(__byte_perm(x0, x1, 0x5410), __byte_perm(x0, x1, 0x7632)), t);
  mx = h2max(mx, shfl_x(mx, 1));
  mx = h2max(mx, shfl_x(mx, 2));
#pragma unroll
  for (int j = 0; j < 6; j++) { s[2 * j] = h2sub(s[2 * j], lo2(mx)); s[2 * j + 1] = h2sub(s[2 * j + 1], hi2(mx)); }
  t = h2sub(t, mx);
}
template <int J>
__device__ __forceinline__ Quad exp_sum(uint32_t (&s)[16], uint32_t& t) {
#pragma unroll
  for (int j = J; j < 12; j++) s[j] = h2ex2(s[j]);
  t = h2ex2(t);
  Quad q;
  q.v[0] = h2add(t, fold_add(h2add(h2add(h2add(s[0], s[2]), h2add(s[4], s[6])), h2add(s[8], s[10])),
                             h2add(h2add(h2add(s[1], s[3]), h2add(s[5], s[7])), h2add(s[9], s[11]))));
#pragma unroll
  for (int i = 1; i < 4; i++) q.v[i] = shfl_x(q.v[0], i);
  return q;
}
__device__ __forceinline__ Quad soft_exp(uint32_t (&s)[16], uint32_t& t) {
  const uint32_t am = h2max(h2max(h2max(amax3(s[0], s[1], s[2]), amax3(s[3], s[4], s[5])), amax3(s[6], s[7], s[8])), h2max(amax3(s[9], s[10], s[11]), t));
  uint32_t rare, sp[4];
#pragma unroll
  for (int j = 0; j < 4; j++) sp[j] = fresh(h2ex2(s[j]));
  asm("{\n.reg .pred p, q;\n.reg .b32 t;\nmov.b32 t, 0x49004900;\nsetp.le.f16x2 p|q, %1, t;\nand.pred p, p, q;\nselp.b32 %0, 0, 1, p;\n}" : "=r"(rare) : "r"(am));
  if (__any_sync(0xffffffffu, rare)) {
    sub_max(s, t);
#pragma unroll
    for (int j = 0; j < 4; j++) sp[j] = h2ex2(s[j]);
  }
#pragma unroll
  for (int j = 0; j < 4; j++) s[j] = sp[j];
  return exp_sum<4>(s, t);
}
__device__ __forceinline__ void soft_norm(uint32_t (&s)[16], uint32_t& t, const Quad& q, const Frame& F, float2 e, uint32_t tid) {
  const float2 d = unpack_h2(h2add(h2add(q.v[0], q.v[1]), h2add(q.v[2], q.v[3])));
  const uint32_t cb = pack_h2(rcp_fast(d.x * e.x), rcp_fast(d.y * e.y)) & (sel(tid & 28, 0u, 0xffffu) | fresh(F.light ? 0u : 0xffffffffu));
#pragma unroll
  for (int j = 0; j < 6; j++) { s[2 * j] = h2mul(s[2 * j], lo2(cb)); s[2 * j + 1] = h2mul(s[2 * j + 1], hi2(cb)); }
  t = fresh(h2mul(t, cb));
  pin<12>(s);
}
__device__ __forceinline__ void soft_tail(uint32_t (&s)[16], uint32_t t) {
  s[12] = t & 0xffffu; s[13] = t >> 16;
  asm volatile("mov.b32 %0, 0;\nmov.b32 %1, 0;" : "=r"(s[14]), "=r"(s[15]));
}
template <int H>
__device__ __forceinline__ uint8_t* row_ptr(const Frame& F, uint8_t* o) {
  const uint32_t oo = fresh(F.oo);
  if (H) asm volatile("mad.wide.u32 %0, %1, 64, %0;" : "+l"(o) : "r"(oo >> 20));
  else { o += oo & 0xfffffu; asm volatile("" : "+l"(o)); }
  return o;
}
template <int H>
__device__ __forceinline__ void affine(uint32_t* r, const uint32_t (&v)[24], const Frame& F) {
  const uint32_t e = H ? F.e1 : F.e0;
#pragma unroll
  for (int j = 0; j < 12; j++) r[j] = h2fma(v[2 * j + H], lo2(e), hi2(e));
  pin<12>(r);
}
template <int H, bool kFence = false>
__device__ __forceinline__ void finish(uint32_t* r, const Frame& F, uint8_t*& o, uint32_t off, uint32_t a, uint32_t m, uint32_t& fz) {
  o = row_ptr<H>(F, o);
#pragma unroll
  for (int j = 0; j < 12; j += 2) { const float2 f = unpack_h2(r[j]), g = unpack_h2(r[j + 1]); r[j] = pack_bf2(f.x, g.x); r[j + 1] = pack_bf2(f.y, g.y); }
  pin<12>(r);
  if (kFence) sfence(fz);
  stg3(o, r, off | (fresh(a) & m));
}
__device__ __forceinline__ uint32_t surplus(uint32_t ring, uint32_t i, uint32_t nfull) { return i + 4 == nfull ? lds32(ring + kExtra) >> 2 : 0; }

__device__ __forceinline__ void release(uint32_t ring, uint32_t slot, uint32_t i, uint32_t nfull, uint32_t w, const CUtensorMap* tm, uint32_t lane) {
  uint32_t old = 0;
  asm volatile("{\n.reg .pred p;\nsetp.eq.u32 p, %2, 0;\n@p atom.relaxed.cta.shared::cta.inc.u32 %0, [%1], 1;\n}" : "+r"(old) : "r"(slot + kRel), "r"(lane) : "memory");
  if (old) {
    sts32(slot + kWide, 0);
    if (i + 4 < nfull) tma_load_win(slot, tm, w + 4 * gridDim.x);
    else if (const uint32_t wn = surplus(ring, i, nfull)) tma_load_win(slot, tm, fresh(wn));
    else mbar_arrive(slot + kFull);
  }
  __syncwarp();
}
__device__ __forceinline__ uint32_t window_offset(uint32_t w) { return (((w * 57457u) >> 22) * (7 * kW - 7 * kNWX) + w * 7) * 192u; }

__device__ __forceinline__ void round_wide(uint32_t ring, uint64_t d0, uint32_t frame, uint32_t nfull, uint32_t i, uint32_t w, int sg, int wp, uint32_t lane,
                                           const CUtensorMap* tm, uint8_t* __restrict__ out) {
  const uint32_t slot = ring + (i & 3) * kSlot;
  uint32_t x[24];
#pragma unroll
  for (int j = 0; j < 24; j++) x[j] = 0;
#pragma unroll 1
  for (uint32_t t = 2 * sg; t < 2 * sg + 2; t++) {
    Frame F;
    uint32_t v[24], s[16];
    load_frame<false>(v, frame_init(F, ring, t, wp, lane), slot, lane);
    load_stats(F, i & 3, lane);
    const uint64_t dp = d0 + (uint32_t)((kWBytes + (i & 3) * kSlot + t * kPlane) / 16);
    gemm<2, kOffAs, 6144>(x, v, d0);
    const uint32_t cs = dup_h2(PAR(ring, cS_s));
    const float kb = PAR(ring, kb), ik = rcp_fast(PAR(ring, kappa));
    wg_wait(); pin<24>(x);
    gemm<0, 0, kChunk>(s, x, dp);
    wg_wait(); pin<14>(s);
    uint32_t u = key48(s, lane);
    sub_max(s, u);
#pragma unroll
    for (int j = 0; j < 12; j++) s[j] = h2mul(s[j], cs);
    u = h2mul(u, cs);
    const float2 z0 = stat_f32(F.e0), z1 = stat_f32(F.e1);
    const float e0 = fmaxf(z0.x, kb), e1 = fmaxf(z1.x, kb);
    const uint32_t aw = pack_h2(__fdividef(z0.x, e0), __fdividef(z1.x, e1));
#pragma unroll
    for (int j = 0; j < 12; j++) { v[2 * j] = h2mul(v[2 * j], lo2(aw)); v[2 * j + 1] = h2mul(v[2 * j + 1], hi2(aw)); }
    soft_norm(s, u, exp_sum<0>(s, u), F, make_float2(e0 * ik, e1 * ik), lane);
    soft_tail(s, u);
    gemm_u<0>(x, s, dp);
    wg_wait(); pin<24>(x);
    gemm<1, kOffWs, 6144>(v, x, d0);
    if ((t & 1) && wp == 0) release(ring, slot, i, nfull, w, tm, lane);
    wg_wait(); pin<24>(v);
    uint8_t* o = out + (size_t)(window_offset(w) + t * frame);
#pragma unroll
    for (int h = 0; h < 2; h++) {
      const float e = h ? e1 : e0, m = h ? z1.y : z0.y;
      uint32_t r[12];
#pragma unroll
      for (int j = 0; j < 12; j += 2) {
        const float2 f = unpack_h2(v[2 * j + h]), g = unpack_h2(v[2 * j + 2 + h]);
        r[j] = pack_bf2(fmaf(f.x, e, m), fmaf(g.x, e, m)); r[j + 1] = pack_bf2(fmaf(f.y, e, m), fmaf(g.y, e, m));
      }
      o = h ? row_ptr<1>(F, o) : row_ptr<0>(F, o);
      stg3(o, r, F.light ? (h ? 1 : lane & 28) : 0);
    }
  }
}

__device__ __forceinline__ uint32_t rounds(uint32_t ring, uint64_t d0, uint64_t d1, uint32_t frame, uint32_t nfull, uint32_t i, uint32_t i1, uint32_t w,
                                           int sg, int wp, int lane, const CUtensorMap* tm, uint8_t* __restrict__ out) {
  Frame A, B;
  uint32_t tid = lane + (frame_init(A, ring, 2 * sg, wp, lane) << 4) + (frame_init(B, ring, 2 * sg + 1, wp, lane) << 16);
  uint32_t va[24], vb[24], x[24], sa[16], sc[16], r0[12], r1[12], ta, tb;
  Quad rs;
  uint32_t& fz = A.oo;
#pragma unroll
  for (int j = 0; j < 24; j++) { vb[j] = 0; x[j] = 0; }
  out += sg * 2 * frame;
  asm volatile("" : "+l"(out));
  uint8_t *ob = out, *o;
  const uint64_t dr = d0 + (uint32_t)(kWBytes / 16 + sg * (2 * kPlane / 16));
  uint32_t slot = ring + (i & 3) * kSlot, first = 1;
  load_frame<false>(va, (tid >> 4) & 0xfff0u, slot, tid);
  do {
    const uint32_t ia = i & 3;
    tid = fresh(tid);
    gemm<2, kOffAs, 6144>(x, va, d0);
    sfence(fz);
    affine<0>(r0, vb, B); affine<1>(r1, vb, B);
    load_frame<true>(vb, (tid >> 16) & 0xfff0u, slot, fz);
    uint64_t dp = dr + ia * (kSlot / 16);
    asm volatile("" : "+l"(dp));
    o = ob + frame;
    asm volatile("" : "+l"(o));
    finish<0, true>(r0, B, o, first, tid, B.light ? 28 : 0, fz);
    sfence(fz);
    wg_wait(); pin<24>(x);
    gemm<0, 0, kChunk>(sa, x, dp);
    if (!B.light) finish<1>(r1, B, o, first, 0, 0, fz);
    else if (sg == 0) {
      if ((tid & 31) == 0) {
        if (i + 4 < nfull) tma_prefetch_win(tm, w + 4 * gridDim.x);
        else if (const uint32_t wn = surplus(ring, i, nfull)) tma_prefetch_win(tm, fresh(wn));
      }
      __syncwarp();
    }
    ob = out + (size_t)window_offset(w);
    asm volatile("" : "+l"(ob));
    wg_wait(); pin<14>(sa);
    gemm<2, kOffAs, 6144>(x, vb, d1);
    ta = key48(sa, tid);
    rs = soft_exp(sa, ta);
    load_stats(A, ia, tid);
    sfence(fz);
    wg_wait(); pin<24>(x);
    gemm<0, kPlane, kChunk>(sc, x, dp);
    sfence(fz);
    soft_norm(sa, ta, rs, A, make_float2(low_f(A.e0), low_f(A.e1)), tid);
    sfence(fz);
    wg_wait(); pin<14>(sc);
    tb = key48(sc, tid);
    sfence(fz);
    soft_tail(sa, ta);
    gemm_u<0>(x, sa, dp);
    rs = soft_exp(sc, tb);
    load_stats(B, ia, tid);
    sfence(fz);
    wg_wait(); pin<24>(x);
    gemm<1, kOffWs, 6144>(va, x, d0);
    sfence(fz);
    soft_norm(sc, tb, rs, B, make_float2(low_f(B.e0), low_f(B.e1)), tid);
    soft_tail(sc, tb);
    sfence(fz);
    wg_wait(); pin<24>(va);
    gemm_u<kPlane>(x, sc, dp);
    sfence(fz);
    const uint32_t sn = ring + ((i + 1) & 3) * kSlot;
    const bool slow = mbar_pending_or<kWide - kDone>(sn + kDone, (i + 1) >> 2);
    affine<0>(r0, va, A);
    o = ob;
    finish<0>(r0, A, o, 0, tid, A.light ? 28 : 0, fz);
    sfence(fz);
    wg_wait(); pin<24>(x);
    gemm<1, kOffWs, 6144>(vb, x, d1);
    affine<1>(r1, va, A);
    if (slow || A.light) {
      if (A.light) release(ring, slot, i, nfull, w, tm, tid & 31);
      if (slow) {
        if (i + 1 < i1) mbar_wait(sn + kDone, (i + 1) >> 2);
        if (__any_sync(0xffffffffu, lds32(sn + kWide))) i1 = 0;
      }
    }
    const uint32_t la = (tid >> 4) & 0xfff0u;
    if (!A.light) { load_block(va, la, sn); finish<1>(r1, A, o, 0, la, 0, fz); }
    else load_light(va, 2 * sg, sn, tid);
    wg_wait(); pin<24>(vb);
    launder<24>(vb);
    launder<24>(va);
    slot = sn; w += gridDim.x; first = 0;
  } while (++i < i1);
  o = ob + frame;
  affine<0>(r0, vb, B); finish<0>(r0, B, o, 0, tid, B.light ? 28 : 0, tid);
  affine<1>(r1, vb, B); finish<1>(r1, B, o, B.light, 0, 0, tid);
  return i;
}

__device__ __forceinline__ void run_S(uint32_t ring, uint64_t d0, uint64_t d1, uint32_t frame, uint32_t nfull, uint32_t i, uint32_t i1, uint32_t w0,
                                      int sg, int wp, const CUtensorMap* tm, uint8_t* __restrict__ out) {
  do {
    const uint32_t lane = fresh(threadIdx.x) & 31;
    const uint32_t slot = ring + (i & 3) * kSlot, w = w0 + i * gridDim.x;
    mbar_wait(slot + kDone, i >> 2);
    if (__any_sync(0xffffffffu, (lds32(slot + kWide) != 0) | (PAR(ring, cS_s) != 1.f) | (PAR(ring, kappa) != 1.f))) {
      round_wide(ring, d1, frame, nfull, i, w, sg, wp, lane, tm, out);
      i++;
    } else {
      i = rounds(ring, d0, d1, frame, nfull, i, i1, w, sg, wp, lane, tm, out);
    }
  } while (i < i1);
}

struct Maps { CUtensorMap load, prefetch; };
__global__ void __launch_bounds__(512, 1) swin_main(const __grid_constant__ Maps tms, uint8_t* __restrict__ out, const uint64_t d0,
                                                    const uint64_t d1, const uint32_t frame) {
  extern __shared__ __align__(1024) uint8_t smem[];
  const CUtensorMap& tm = tms.load;
  const uint32_t sb = smem_u32(smem), ring = sb + kWBytes;
  const int tid = threadIdx.x;
  const int wg = __shfl_sync(0xffffffffu, tid >> 7, 0);
  const int wp = __shfl_sync(0xffffffffu, (tid >> 5) & 3, 0);
  const int lane = tid & 31;
  const uint32_t b = blockIdx.x, nb = gridDim.x;
  const uint32_t nfull = kNWIN / nb, nrem = kNWIN - nfull * nb;
  if (tid == 0) {
    if (sb != 1024 || nfull > 700 || nfull < 12) __trap();
#pragma unroll
    for (int i = 0; i < 4; i++) {
      mbar_init(ring + i * kSlot + kFull, 1);
      mbar_init(ring + i * kSlot + kDone, 49);
      sts32(ring + i * kSlot + kRel, 0); sts32(ring + i * kSlot + kFlag, 0); sts32(ring + i * kSlot + kWide, 0);
    }
    asm volatile("fence.mbarrier_init.release.cluster;" ::: "memory");
    for (int i = 0; i < 2; i++) tma_load_win(ring + i * kSlot, &tm, b + i * nb);
  }
  __syncwarp();
  if (wg == 1 || wg == 2)
    asm volatile("st.shared.v4.b32 [%0], {%1,%1,%1,%1};" ::"r"(ring + ((tid - 128) >> 6) * kSlot + kXBytes + (tid & 63) * 16), "r"(0) : "memory");
  __syncthreads();
  asm volatile("griddepcontrol.wait;" ::: "memory");
#pragma unroll
  for (int q = 0; q < kWBytes / 16 / 512; q++)
    asm volatile("cp.async.cg.shared.global [%0], [%1], 16;" ::"r"(sb + (tid + q * 512) * 16), "l"(g_wimg + tid + q * 512) : "memory");
  if (wg == 0 && wp < 3) {
    static_assert(kWBytes / 16 == 9 * 512 + 96, "weight copy split");
    const int e = tid + 9 * 512;
    asm volatile("cp.async.cg.shared.global [%0], [%1], 16;" ::"r"(sb + e * 16), "l"(g_wimg + e) : "memory");
  }
  if (wg == 0 && wp == 3)
    asm volatile("cp.async.ca.shared.global [%0], [%1], 4;" ::"r"(ring + kPar + lane * 4), "l"(reinterpret_cast<const float*>(&g_par) + lane) : "memory");
  asm volatile("cp.async.wait_all;\nfence.proxy.async.shared::cta;" ::: "memory");
  __syncthreads();
  const float kb = PAR(ring, kb);
  TPar P;
  P.kt = PAR(ring, kt);
  P.sgmin = fmaxf(0.0045f, kb * 0.011f);
  P.outmax = fmaf(kb, -627.2f, 60000.f);
  const bool scaled = __any_sync(0xffffffffu, PAR(ring, cS_t) != 1.f);
  const uint32_t pdir = __ballot_sync(0xffffffffu, scaled || !(P.kt <= 256.f));
  if (tid == 128) for (int i = 2; i < 4; i++) tma_load_win(ring + i * kSlot, &tm, b + i * nb);
  __syncwarp();
  const bool isT = wg < 2;
  run_T(ring, d0, d1, nfull, nrem, !isT, wg, wp, lane, P, scaled, pdir);
  const uint32_t ex = isT ? __shfl_sync(0xffffffffu, lds32(ring + kExtra), 0) : 3;
  if ((ex >> (wg & 1)) & 1) run_S(ring, d0, d1, frame, nfull, isT ? nfull : 0, nfull + isT, isT ? (ex >> 2) - nfull * nb : b, wg & 1, wp, &tm, out);
}

__device__ __forceinline__ int ch_pos(int ch) { return 32 * (ch >> 5) + 16 * ((ch >> 2) & 1) + 8 * (ch & 1) + 2 * ((ch >> 3) & 3) + ((ch >> 1) & 1); }
__device__ __forceinline__ float pow2_ceil(float v) {
  return __uint_as_float((__float_as_uint(v) + 0x7fffffu) & 0x7f800000u);
}

constexpr int kPrepSplit = 12;
constexpr int kPrepThreads = 384;
__global__ void __launch_bounds__(kPrepThreads) swin_prep(const __nv_bfloat16* __restrict__ wqkv_t, const __nv_bfloat16* __restrict__ wo_t,
                                                          const __nv_bfloat16* __restrict__ wqkv_s, const __nv_bfloat16* __restrict__ wo_s) {
  asm volatile("griddepcontrol.launch_dependents;");
  __shared__ __align__(16) uint32_t raw[2][96][52];
  __shared__ __align__(16) uint32_t mu[3][52];
  __shared__ float nrm[12], nrm2[6], csum[6][9];
  const int mat = blockIdx.x / kPrepSplit, blk = blockIdx.x % kPrepSplit;
  const int tid = threadIdx.x, lane = tid & 31, warp = tid >> 5, g = lane >> 2, c = lane & 3;
  const __nv_bfloat16* wqkv = mat < 2 ? wqkv_t : wqkv_s;
  const __nv_bfloat16* wo = mat < 2 ? wo_t : wo_s;
  const bool isA = (mat & 1) == 0;
  {
    uint4 v[3], u[3];
#pragma unroll
    for (int q = 0; q < 3; q++) {
      const int e = tid + q * kPrepThreads, i = e / 12, c8 = (e % 12) * 8;
      v[q] = __ldg(reinterpret_cast<const uint4*>(wqkv + i * 288 + (isA ? 0 : 192) + c8));
      u[q] = __ldg(reinterpret_cast<const uint4*>(isA ? wqkv + i * 288 + 96 + c8 : wo + i * 96 + c8));
    }
#pragma unroll
    for (int q = 0; q < 3; q++) {
      const int e = tid + q * kPrepThreads, i = e / 12, c4 = (e % 12) * 4;
      *reinterpret_cast<uint4*>(&raw[0][i][c4]) = v[q];
      *reinterpret_cast<uint4*>(&raw[1][i][c4]) = u[q];
    }
  }
  __syncthreads();
  {
    const int m = warp / 6, cp = (warp % 6) * 8 + g;
    float s0 = 0.f, s1 = 0.f, q0 = 0.f, q1 = 0.f;
#pragma unroll
    for (int i = 0; i < 24; i++) {
      const uint32_t w = raw[m][4 * i + c][cp];
      const float lo = __uint_as_float(w << 16), hi = __uint_as_float(w & 0xffff0000u);
      s0 += lo; s1 += hi; q0 = fmaf(lo, lo, q0); q1 = fmaf(hi, hi, q1);
    }
    s0 = quad_sum(s0) * (1.f / 96.f); s1 = quad_sum(s1) * (1.f / 96.f); q0 = quad_sum(q0); q1 = quad_sum(q1);
    if (mat == 1 && m == 1) {
      float r0 = 0.f, r1 = 0.f;
#pragma unroll
      for (int i = 0; i < 12; i++) {
        const uint32_t w0 = raw[1][2 * cp][4 * i + c], w1 = raw[1][2 * cp + 1][4 * i + c];
        r0 += __uint_as_float(w0 << 16) + __uint_as_float(w0 & 0xffff0000u);
        r1 += __uint_as_float(w1 << 16) + __uint_as_float(w1 & 0xffff0000u);
      }
      r0 = quad_sum(r0) * (1.f / 96.f); r1 = quad_sum(r1) * (1.f / 96.f);
      s0 = r0; s1 = r1;
    }
    if (m == 1 && c == 0) {
      const uint32_t hi = mat == 3 ? 0u : pack_bf2(s0, s1);
      mu[0][cp] = hi;
      mu[1][cp] = mat == 3 ? 0u : pack_bf2(s0 - __uint_as_float(hi << 16), s1 - __uint_as_float(hi & 0xffff0000u));
      mu[2][cp] = 0u;
    }
    if (m == 0 || isA) {
      q0 = fmaxf(fmaf(-96.f * s0, s0, q0), 0.f) + q0 * 1e-6f;
      q1 = fmaxf(fmaf(-96.f * s1, s1, q1), 0.f) + q1 * 1e-6f;
    }
    const bool usemax = m == 1 && mat == 3;
    float t = usemax ? fmaxf(q0, q1) : q0 + q1;
#pragma unroll
    for (int o = 4; o < 32; o <<= 1) { const float z = __shfl_xor_sync(0xffffffffu, t, o); t = usemax ? fmaxf(t, z) : t + z; }
    if (lane == 0) nrm[warp] = t;
  }
  __syncthreads();
  if (warp >= 6) return;
  float d[4] = {0.f, 0.f, 0.f, 0.f}, e[4] = {0.f, 0.f, 0.f, 0.f}, v0, v1;
  {
    const uint32_t arow = smem_u32(&raw[0][16 * warp + (lane & 15)][(lane >> 4) * 4]);
    const uint32_t brow = isA ? smem_u32(&raw[1][blk * 8 + (lane & 7)][(lane >> 3) * 4]) : smem_u32(&raw[1][lane][blk * 4]);
    const uint32_t mrow = smem_u32(&mu[min(lane & 7, 2)][(lane >> 3) * 4]);
#pragma unroll
    for (int k2 = 0; k2 < 3; k2++) {
      uint32_t b[4], m[4];
      if (isA) ldsm4(b, brow + k2 * 64);
      else asm volatile("ldmatrix.sync.aligned.m8n8.x4.trans.shared.b16 {%0,%1,%2,%3}, [%4];"
                        : "=r"(b[0]), "=r"(b[1]), "=r"(b[2]), "=r"(b[3]) : "r"(brow + k2 * (32 * 208)) : "memory");
      ldsm4(m, mrow + k2 * 64);
#pragma unroll
      for (int hf = 0; hf < 2; hf++) {
        uint32_t a[4];
        ldsm4(a, arow + (2 * k2 + hf) * 32);
        asm volatile("mma.sync.aligned.m16n8k16.row.col.f32.bf16.bf16.f32 {%0,%1,%2,%3},{%4,%5,%6,%7},{%8,%9},{%0,%1,%2,%3};"
                     : "+f"(d[0]), "+f"(d[1]), "+f"(d[2]), "+f"(d[3])
                     : "r"(a[0]), "r"(a[1]), "r"(a[2]), "r"(a[3]), "r"(b[2 * hf]), "r"(b[2 * hf + 1]));
        asm volatile("mma.sync.aligned.m16n8k16.row.col.f32.bf16.bf16.f32 {%0,%1,%2,%3},{%4,%5,%6,%7},{%8,%9},{%0,%1,%2,%3};"
                     : "+f"(e[0]), "+f"(e[1]), "+f"(e[2]), "+f"(e[3])
                     : "r"(a[0]), "r"(a[1]), "r"(a[2]), "r"(a[3]), "r"(m[2 * hf]), "r"(m[2 * hf + 1]));
      }
    }
    v0 = __shfl_sync(0xffffffffu, e[0] + e[1], lane & ~3); v1 = __shfl_sync(0xffffffffu, e[2] + e[3], lane & ~3);
    d[0] -= v0; d[1] -= v0; d[2] -= v1; d[3] -= v1;
    float t0 = d[0] + d[2], t1 = d[1] + d[3], t2 = v0 + v1;
#pragma unroll
    for (int o = 4; o < 32; o <<= 1) {
      t0 += __shfl_xor_sync(0xffffffffu, t0, o); t1 += __shfl_xor_sync(0xffffffffu, t1, o); t2 += __shfl_xor_sync(0xffffffffu, t2, o);
    }
    if (g == 0) { csum[warp][2 * c] = t0; csum[warp][2 * c + 1] = t1; csum[warp][8] = t2; }
  }
  const float nl = nrm[0] + nrm[1] + nrm[2] + nrm[3] + nrm[4] + nrm[5];
  const float nr = mat == 3 ? fmaxf(fmaxf(fmaxf(nrm[6], nrm[7]), fmaxf(nrm[8], nrm[9])), fmaxf(nrm[10], nrm[11]))
                            : nrm[6] + nrm[7] + nrm[8] + nrm[9] + nrm[10] + nrm[11];
  const float bound = __fsqrt_rn(nl) * __fsqrt_rn(nr) * 1.01f;
  const float f = isA ? 0.14724448f : 1.f;
  float sc = pow2_ceil(fmaxf(bound * (isA ? 0.14724448f / 160.f : mat == 1 ? 1.f / 16.f : 1.f / 64.f), 1e-30f));
  if (isA) sc = fminf(fmaxf(sc, 1.f), 32768.f);
  const float kb = sc;
  if (mat == 3 && sc <= 1.f && sc >= 1.f / 1024.f) sc = 1.f;
  const float mul = f * __uint_as_float(0x7f000000u - __float_as_uint(sc));
  if (blk == 0 && tid < 8) reinterpret_cast<float*>(&g_par)[8 * mat + tid] = tid == 0 ? sc : tid == 1 ? kb : 0.f;
  asm volatile("bar.sync 1, 192;" ::: "memory");
  float mean[2];
#pragma unroll
  for (int b = 0; b < 2; b++)
    mean[b] = (csum[0][2 * c + b] + csum[1][2 * c + b] + csum[2][2 * c + b] + csum[3][2 * c + b] + csum[4][2 * c + b] + csum[5][2 * c + b]) *
              (1.f / 96.f);
  const uint32_t img = mat == 0 ? 0 : mat == 1 ? kOffWt : mat == 2 ? kOffAs : kOffWs;
  const float vmean = (csum[0][8] + csum[1][8] + csum[2][8] + csum[3][8] + csum[4][8] + csum[5][8]) * (1.f / 96.f);
  float q2 = 0.f;
#pragma unroll
  for (int q = 0; q < 4; q++) q2 = fmaf(d[q] - mean[q & 1], d[q] - mean[q & 1], q2);
#pragma unroll
  for (int o = 16; o; o >>= 1) q2 += __shfl_xor_sync(0xffffffffu, q2, o);
  if (lane == 0) nrm2[warp] = q2;
  asm volatile("bar.sync 1, 192;" ::: "memory");
  const float rms = __fsqrt_rn((nrm2[0] + nrm2[1] + nrm2[2] + nrm2[3] + nrm2[4] + nrm2[5]) * (1.f / 768.f)) * mul;
  const float big = 12582912.f * pow2_ceil(fmaxf(rms * (1.f / 256.f), 1e-30f));
  const float off = mat == 2 ? 1.5f * pow2_ceil(fmaxf(rms * 3.f, 1e-4f)) : 0.f;
  __half (*stage)[8][96] = reinterpret_cast<__half (*)[8][96]>(&raw[0][0][0]);
#pragma unroll
  for (int q = 0; q < 4; q++) {
    const int kp = ch_pos(16 * warp + g + 8 * (q >> 1));
    const float o = __fadd_rn(__fadd_rn((d[q] - mean[q & 1]) * mul, big), -big);
    stage[0][2 * c + (q & 1)][kp] = __float2half_rn(o + off);
    stage[1][2 * c + (q & 1)][kp] = __float2half_rn((q & 1) ? ((q >> 1 ? v1 : v0) - vmean) * mul : 1.f / 96.f);
  }
  asm volatile("bar.sync 1, 192;" ::: "memory");
  const int ext = tid >= 96, n = (tid >> 2) & 7, ch = (tid - 96 * ext) >> 5;
  if (!ext || (mat == 1 && blk == 0)) {
    uint32_t a = (ext ? 0 : img) + ch * (mat < 2 ? kAtChunk : 6144) + (ext ? 96 + n : ch_pos(blk * 8 + n)) * 64 + c * 16;
    a ^= ((a >> 7) & 3) << 4;
    g_wimg[a >> 4] = *reinterpret_cast<const uint4*>(&stage[ext][n][32 * ch + 8 * c]);
  }
}

typedef CUresult (*EncodeFn)(CUtensorMap*, CUtensorMapDataType, cuuint32_t, void*, const cuuint64_t*, const cuuint64_t*,
                             const cuuint32_t*, const cuuint32_t*, CUtensorMapInterleave, CUtensorMapSwizzle,
                             CUtensorMapL2promotion, CUtensorMapFloatOOBfill);

}

extern "C" void kernel_launch(void* const* d_in, const int* in_sizes, int n_in, void* d_out, int out_size) {
  (void)in_sizes; (void)n_in; (void)out_size;
  static EncodeFn enc = nullptr;
  static int nsm = 0;
  if (!enc) {
    void* fn = nullptr;
    cudaDriverEntryPointQueryResult qr;
    cudaGetDriverEntryPoint("cuTensorMapEncodeTiled", &fn, cudaEnableDefault, &qr);
    enc = reinterpret_cast<EncodeFn>(fn);
    int dev = 0;
    cudaGetDevice(&dev);
    cudaDeviceGetAttribute(&nsm, cudaDevAttrMultiProcessorCount, dev);
    cudaFuncSetAttribute(swin_main, cudaFuncAttributeMaxDynamicSharedMemorySize, kSmemBytes);
  }
  Maps tms;
  CUtensorMap& tm = tms.load;
  const cuuint64_t dims[5] = {32, kW, kH, kT, 3};
  const cuuint64_t strides[4] = {192, 192ull * kW, 192ull * kW * kH, 64};
  const cuuint32_t box[5] = {32, 7, 7, 4, 3};
  const cuuint32_t es[5] = {1, 1, 1, 1, 1};
  enc(&tm, CU_TENSOR_MAP_DATA_TYPE_BFLOAT16, 5, d_in[0], dims, strides, box, es, CU_TENSOR_MAP_INTERLEAVE_NONE,
      CU_TENSOR_MAP_SWIZZLE_64B, CU_TENSOR_MAP_L2_PROMOTION_L2_128B, CU_TENSOR_MAP_FLOAT_OOB_FILL_NONE);

  const cuuint64_t dims2[3] = {24ull * kW, kH, kT};
  const cuuint64_t strides2[2] = {192ull * kW, 192ull * kW * kH};
  const cuuint32_t box2[3] = {168, 7, 4};
  enc(&tms.prefetch, CU_TENSOR_MAP_DATA_TYPE_UINT64, 3, d_in[0], dims2, strides2, box2, es, CU_TENSOR_MAP_INTERLEAVE_NONE,
      CU_TENSOR_MAP_SWIZZLE_NONE, CU_TENSOR_MAP_L2_PROMOTION_L2_128B, CU_TENSOR_MAP_FLOAT_OOB_FILL_NONE);

  cudaStream_t st = cudaStreamPerThread;
  swin_prep<<<4 * kPrepSplit, kPrepThreads, 0, st>>>(
      static_cast<const __nv_bfloat16*>(d_in[1]), static_cast<const __nv_bfloat16*>(d_in[2]),
      static_cast<const __nv_bfloat16*>(d_in[3]), static_cast<const __nv_bfloat16*>(d_in[4]));

  cudaLaunchConfig_t cfg = {};
  cfg.gridDim = dim3(nsm);
  cfg.blockDim = dim3(512);
  cfg.dynamicSmemBytes = kSmemBytes;
  cfg.stream = st;
  cudaLaunchAttribute at[1];
  at[0].id = cudaLaunchAttributeProgrammaticStreamSerialization;
  at[0].val.programmaticStreamSerializationAllowed = 1;
  cfg.attrs = at;
  cfg.numAttrs = 1;
  cudaLaunchKernelEx(&cfg, swin_main, tms, static_cast<uint8_t*>(d_out), mk_desc(1024), mk_desc(1024), (uint32_t)(kH * kW * 192));
}
```

```cpp
#include <cuda_runtime.h>
#include <cuda.h>
#include <cuda_bf16.h>
#include <cuda_fp16.h>
#include <stddef.h>
#include <stdint.h>

namespace {

constexpr int kH = 511, kW = 511, kT = 4;
constexpr int kNWX = 73, kNWIN = 73 * 73;
constexpr int kChunk = 12544;
constexpr int kPlane = 3136;
constexpr int kXBytes = 37632;
constexpr int kZero = kXBytes + 896, kFull = kXBytes + 1024, kDone = kFull + 8, kRel = kFull + 16, kFlag = kFull + 20, kExtra = kFull + 24,
              kWide = kFull + 28;
constexpr int kPar = kFull + 128;
constexpr int kSlot = 38912;
constexpr int kWMat = 18432;
constexpr int kAtChunk = 200 * 64;
constexpr int kOffWt = 104 * 64;
constexpr int kOffAs = 3 * kAtChunk, kOffWs = kOffAs + kWMat;
constexpr int kWBytes = kOffWs + kWMat;
constexpr int kSmemBytes = kWBytes + 4 * kSlot;

struct Params {
  float cS_t, pad0[7];
  float kt, pad1[7];
  float cS_s, pad2[7];
  float kappa;
  float kb;
  uint32_t ticket, pad3[5];
};

__device__ __align__(128) uint4 g_wimg[kWBytes / 16];
__device__ __align__(128) Params g_par;

__device__ __forceinline__ uint32_t smem_u32(const void* p) { return (uint32_t)__cvta_generic_to_shared(p); }
__device__ __forceinline__ void mbar_init(uint32_t a, int c) { asm volatile("mbarrier.init.shared::cta.b64 [%0], %1;" ::"r"(a), "r"(c)); }
__device__ __forceinline__ void mbar_expect(uint32_t a, int bytes) {
  asm volatile("mbarrier.arrive.expect_tx.shared::cta.b64 _, [%0], %1;" ::"r"(a), "r"(bytes) : "memory");
}
__device__ __forceinline__ void mbar_arrive(uint32_t a, uint32_t off = 0) {
  asm volatile("{\n.reg .pred p;\nsetp.eq.u32 p, %1, 0;\n@p mbarrier.arrive.shared::cta.b64 _, [%0];\n}" ::"r"(a), "r"(off) : "memory");
}
__device__ __forceinline__ void mbar_wait(uint32_t a, uint32_t par) {
  asm volatile(
      "{\n.reg .pred p;\n.reg .u32 n;\n"
      "mbarrier.try_wait.parity.shared::cta.b64 p, [%0], %1;\n"
      "@p bra.uni WDONE;\n"
      "mov.u32 n, 0;\n"
      "WLOOP:\n"
      "mbarrier.try_wait.parity.shared::cta.b64 p, [%0], %1;\n"
      "@p bra.uni WDONE;\n"
      "add.u32 n, n, 1;\n"
      "setp.lt.u32 p, n, 0x100000;\n"
      "@p bra.uni WLOOP;\n"
      "trap;\n"
      "WDONE:\n}" ::"r"(a), "r"(par & 1) : "memory");
}
template <int OFF>
__device__ __forceinline__ bool mbar_pending_or(uint32_t a, uint32_t par) {
  uint32_t r;
  asm volatile("{\n.reg .pred p;\n.reg .b32 t;\nmbarrier.test_wait.parity.shared::cta.b64 p, [%1], %2;\nld.shared.b32 t, [%1+%3];\n"
               "setp.ne.or.u32 p, t, 0, !p;\nvote.sync.any.pred p, p, 0xffffffff;\nselp.b32 %0, 1, 0, p;\n}"
               : "=r"(r) : "r"(a), "r"(par & 1), "n"(OFF) : "memory");
  return r;
}
__device__ __forceinline__ uint32_t lds32(uint32_t a) {
  uint32_t v; asm volatile("ld.shared.b32 %0, [%1];" : "=r"(v) : "r"(a) : "memory"); return v;
}
__device__ __forceinline__ void sts32(uint32_t a, uint32_t v) { asm volatile("st.shared.b32 [%0], %1;" ::"r"(a), "r"(v) : "memory"); }
__device__ __forceinline__ void tma_load_win(uint32_t slot, const CUtensorMap* m, uint32_t w) {
  const uint32_t wy = (w * 57457u) >> 22, wx = w - wy * kNWX;
  mbar_expect(slot + kFull, kXBytes);
  asm volatile(
      "cp.async.bulk.tensor.5d.shared::cluster.global.mbarrier::complete_tx::bytes [%0], [%1, {%3,%4,%5,%3,%3}], [%2];" ::"r"(slot),
      "l"(m), "r"(slot + kFull), "r"(0), "r"(wx * 7), "r"(wy * 7)
      : "memory");
}
__device__ __forceinline__ void tma_prefetch_win(const CUtensorMap* m, uint32_t w) {
  const uint32_t wy = (w * 57457u) >> 22, wx = w - wy * kNWX;
  asm volatile("cp.async.bulk.prefetch.tensor.3d.L2.global [%0, {%1,%2,%3}];" ::"l"(m + 1), "r"(wx * 168), "r"(wy * 7), "r"(0) : "memory");
}
__device__ __forceinline__ void wg_fence() { asm volatile("wgmma.fence.sync.aligned;" ::: "memory"); }
__device__ __forceinline__ void wg_commit() { asm volatile("wgmma.commit_group.sync.aligned;" ::: "memory"); }
__device__ __forceinline__ void wg_wait() { asm volatile("wgmma.wait_group.sync.aligned 0;" ::: "memory"); }
template <int N>
__device__ __forceinline__ void pin(uint32_t* d) {
#pragma unroll
  for (int i = 0; i < N; i++) asm volatile("" : "+r"(d[i])::"memory");
}
__device__ __forceinline__ uint32_t fresh(uint32_t v) { asm volatile("" : "+r"(v)); return v; }
__device__ __forceinline__ float fresh(float v) { asm volatile("" : "+f"(v)); return v; }
template <int N>
__device__ __forceinline__ void launder(uint32_t* q) {
#pragma unroll
  for (int j = 0; j < N; j++) { uint32_t t; asm volatile("mov.b32 %0, %1;" : "=r"(t) : "r"(q[j])); q[j] = t; }
}
__device__ __forceinline__ void sfence(uint32_t& v) {
  asm volatile("{\n.reg .pred p;\nsetp.eq.u32 p, %1, 0x7fffffff;\n@p mov.u32 %0, %%clock;\n}" : "+r"(v) : "r"(gridDim.x) : "memory");
}
constexpr uint64_t mk_desc(uint32_t addr) { return ((uint64_t)0x80000020u << 32) | (addr >> 4) | (1u << 16); }

#define R4(d, i) "+r"(d[i]), "+r"(d[i + 1]), "+r"(d[i + 2]), "+r"(d[i + 3])
#define O4(d, i) "=r"(d[i]), "=r"(d[i + 1]), "=r"(d[i + 2]), "=r"(d[i + 3])
#define D26 "{%0,%1,%2,%3,%4,%5,%6,%7,%8,%9,%10,%11,%12,%13,%14,%15,%16,%17,%18,%19,%20,%21,%22,%23,%24,%25},"
#define D24 "{%0,%1,%2,%3,%4,%5,%6,%7,%8,%9,%10,%11,%12,%13,%14,%15,%16,%17,%18,%19,%20,%21,%22,%23},"
#define D14 "{%0,%1,%2,%3,%4,%5,%6,%7,%8,%9,%10,%11,%12,%13},"

template <int SC, int TB>
__device__ __forceinline__ void wgmma(uint32_t (&d)[24], const uint32_t* a, uint64_t db) {
  if (SC == 2)
    asm volatile("{\n.reg .pred p;\nsetp.eq.u32 p, %30, 0x7fffffff;\n"
                 "wgmma.mma_async.sync.aligned.m64n96k16.f16.f16.f16 " D24 "{%24,%25,%26,%27}, %28, p, 1, 1, %29;\n}"
                 : R4(d, 0), R4(d, 4), R4(d, 8), R4(d, 12), R4(d, 16), R4(d, 20)
                 : "r"(a[0]), "r"(a[1]), "r"(a[2]), "r"(a[3]), "l"(db), "n"(TB), "r"(gridDim.x));
  else if (SC)
    asm volatile("wgmma.mma_async.sync.aligned.m64n96k16.f16.f16.f16 " D24 "{%24,%25,%26,%27}, %28, 1, 1, 1, %29;"
                 : R4(d, 0), R4(d, 4), R4(d, 8), R4(d, 12), R4(d, 16), R4(d, 20)
                 : "r"(a[0]), "r"(a[1]), "r"(a[2]), "r"(a[3]), "l"(db), "n"(TB));
  else
    asm volatile("wgmma.mma_async.sync.aligned.m64n96k16.f16.f16.f16 " D24 "{%24,%25,%26,%27}, %28, 0, 1, 1, %29;"
                 : O4(d, 0), O4(d, 4), O4(d, 8), O4(d, 12), O4(d, 16), O4(d, 20)
                 : "r"(a[0]), "r"(a[1]), "r"(a[2]), "r"(a[3]), "l"(db), "n"(TB));
}
template <int SC, int TB>
__device__ __forceinline__ void wgmma(uint32_t (&d)[26], const uint32_t* a, uint64_t db) {
  if (SC)
    asm volatile("wgmma.mma_async.sync.aligned.m64n104k16.f16.f16.f16 " D26 "{%26,%27,%28,%29}, %30, 1, 1, 1, 0;"
                 : R4(d, 0), R4(d, 4), R4(d, 8), R4(d, 12), R4(d, 16), R4(d, 20), "+r"(d[24]), "+r"(d[25])
                 : "r"(a[0]), "r"(a[1]), "r"(a[2]), "r"(a[3]), "l"(db));
  else
    asm volatile("wgmma.mma_async.sync.aligned.m64n104k16.f16.f16.f16 " D26 "{%26,%27,%28,%29}, %30, 0, 1, 1, 0;"
                 : O4(d, 0), O4(d, 4), O4(d, 8), O4(d, 12), O4(d, 16), O4(d, 20), "=r"(d[24]), "=r"(d[25])
                 : "r"(a[0]), "r"(a[1]), "r"(a[2]), "r"(a[3]), "l"(db));
}
template <int SC, int TB>
__device__ __forceinline__ void wgmma(uint32_t (&d)[16], const uint32_t* a, uint64_t db) {
  if (SC)
    asm volatile("wgmma.mma_async.sync.aligned.m64n56k16.f16.f16.f16 " D14 "{%14,%15,%16,%17}, %18, 1, 1, 1, 0;"
                 : R4(d, 0), R4(d, 4), R4(d, 8), "+r"(d[12]), "+r"(d[13])
                 : "r"(a[0]), "r"(a[1]), "r"(a[2]), "r"(a[3]), "l"(db));
  else
    asm volatile("wgmma.mma_async.sync.aligned.m64n56k16.f16.f16.f16 " D14 "{%14,%15,%16,%17}, %18, 0, 1, 1, 0;"
                 : O4(d, 0), O4(d, 4), O4(d, 8), "=r"(d[12]), "=r"(d[13])
                 : "r"(a[0]), "r"(a[1]), "r"(a[2]), "r"(a[3]), "l"(db));
}
template <int SC, int OFF, int CH, int ND>
__device__ __forceinline__ void gemm(uint32_t (&d)[ND], const uint32_t* a, uint64_t db) {
  asm volatile("" : "+l"(db));
  wg_fence();
  wgmma<SC, 0>(d, a, db + OFF / 16);
#pragma unroll
  for (int k = 1; k < 6; k++) wgmma<1, 0>(d, a + 4 * k, db + (OFF + (k >> 1) * CH + (k & 1) * 32) / 16);
  wg_commit();
}
__device__ __forceinline__ void lds128(uint32_t* r, uint32_t a) {
  asm volatile("ld.shared.v4.b32 {%0,%1,%2,%3}, [%4];" : "=r"(r[0]), "=r"(r[1]), "=r"(r[2]), "=r"(r[3]) : "r"(a) : "memory");
}
__device__ __forceinline__ void ldsm4(uint32_t* r, uint32_t a) {
  asm volatile("ldmatrix.sync.aligned.m8n8.x4.shared.b16 {%0,%1,%2,%3}, [%4];"
               : "=r"(r[0]), "=r"(r[1]), "=r"(r[2]), "=r"(r[3]) : "r"(a) : "memory");
}
__device__ __forceinline__ void stsm4(uint32_t a, const uint32_t* r) {
  asm volatile("stmatrix.sync.aligned.m8n8.x4.shared.b16 [%0], {%1,%2,%3,%4};" ::"r"(a), "r"(r[0]), "r"(r[1]), "r"(r[2]), "r"(r[3])
               : "memory");
}
__device__ __forceinline__ void stg3(uint8_t* p, const uint32_t* r, uint32_t off) {
  asm volatile("{\n.reg .pred p;\nsetp.eq.u32 p, %13, 0;\n@p st.global.v4.b32 [%0], {%1,%2,%3,%4};\n"
               "@p st.global.v4.b32 [%0+64], {%5,%6,%7,%8};\n@p st.global.v4.b32 [%0+128], {%9,%10,%11,%12};\n}" ::"l"(p),
               "r"(r[0]), "r"(r[1]), "r"(r[2]), "r"(r[3]), "r"(r[4]), "r"(r[5]), "r"(r[6]), "r"(r[7]), "r"(r[8]), "r"(r[9]), "r"(r[10]), "r"(r[11]),
               "r"(off) : "memory");
}
__device__ __forceinline__ uint32_t pack_h2(float lo, float hi) {
  uint32_t r; asm("cvt.rn.f16x2.f32 %0, %1, %2;" : "=r"(r) : "f"(hi), "f"(lo)); return r;
}
__device__ __forceinline__ uint32_t pack_h2_sat(float lo, float hi) {
  uint32_t r; asm("cvt.rn.satfinite.f16x2.f32 %0, %1, %2;" : "=r"(r) : "f"(hi), "f"(lo)); return r;
}
__device__ __forceinline__ uint32_t pack_bf2(float lo, float hi) {
  uint32_t r; asm("cvt.rn.bf16x2.f32 %0, %1, %2;" : "=r"(r) : "f"(hi), "f"(lo)); return r;
}
__device__ __forceinline__ __half2 as_h2(uint32_t v) { return *reinterpret_cast<__half2*>(&v); }
__device__ __forceinline__ uint32_t as_u(__half2 v) { return *reinterpret_cast<uint32_t*>(&v); }
__device__ __forceinline__ float2 unpack_h2(uint32_t v) { return __half22float2(as_h2(v)); }
__device__ __forceinline__ float low_f(uint32_t v) { return __low2float(as_h2(v)); }
__device__ __forceinline__ uint32_t h2ex2(uint32_t v) { uint32_t r; asm("ex2.approx.f16x2 %0, %1;" : "=r"(r) : "r"(v)); return r; }
__device__ __forceinline__ uint32_t h2max(uint32_t a, uint32_t b) { return as_u(__hmax2(as_h2(a), as_h2(b))); }
__device__ __forceinline__ uint32_t h2add(uint32_t a, uint32_t b) { return as_u(__hadd2(as_h2(a), as_h2(b))); }
__device__ __forceinline__ uint32_t h2sub(uint32_t a, uint32_t b) { return as_u(__hsub2(as_h2(a), as_h2(b))); }
__device__ __forceinline__ uint32_t h2mul(uint32_t a, uint32_t b) { return as_u(__hmul2(as_h2(a), as_h2(b))); }
__device__ __forceinline__ uint32_t h2neg(uint32_t a) { return as_u(__hneg2(as_h2(a))); }
__device__ __forceinline__ uint32_t h2fma(uint32_t a, uint32_t b, uint32_t c) { return as_u(__hfma2(as_h2(a), as_h2(b), as_h2(c))); }
__device__ __forceinline__ uint32_t lo2(uint32_t v) { return as_u(__low2half2(as_h2(v))); }
__device__ __forceinline__ uint32_t hi2(uint32_t v) { return as_u(__high2half2(as_h2(v))); }
__device__ __forceinline__ uint32_t fold_add(uint32_t a, uint32_t b) { return h2add(__byte_perm(a, b, 0x5410), __byte_perm(a, b, 0x7632)); }
__device__ __forceinline__ uint32_t sel(uint32_t p, uint32_t a, uint32_t b) {
  uint32_t r; asm("{\n.reg .pred p;\nsetp.ne.u32 p, %3, 0;\nselp.b32 %0, %1, %2, p;\n}" : "=r"(r) : "r"(a), "r"(b), "r"(p)); return r;
}
__device__ __forceinline__ float sel4(uint32_t c, float a0, float a1, float a2, float a3) {
  return __uint_as_float(sel(c & 2, sel(c & 1, __float_as_uint(a3), __float_as_uint(a2)), sel(c & 1, __float_as_uint(a1), __float_as_uint(a0))));
}
__device__ __forceinline__ float rcp_fast(float v) { float r; asm("rcp.approx.ftz.f32 %0, %1;" : "=f"(r) : "f"(v)); return r; }
__device__ __forceinline__ float rsq_fast(float v) { float r; asm("rsqrt.approx.ftz.f32 %0, %1;" : "=f"(r) : "f"(v)); return r; }
__device__ __forceinline__ uint32_t shfl_x(uint32_t v, int m) { return __shfl_xor_sync(0xffffffffu, v, m); }
__device__ __forceinline__ uint32_t shfl_q(uint32_t v, int i) { return __shfl_sync(0xffffffffu, v, i, 4); }
__device__ __forceinline__ float quad_sum(float v) {
  v += __shfl_xor_sync(0xffffffffu, v, 1);
  return v + __shfl_xor_sync(0xffffffffu, v, 2);
}
#define PAR(ring, f) __uint_as_float(lds32((ring) + kPar + offsetof(Params, f)))
__device__ __forceinline__ uint32_t dup_h2(float v) { return pack_h2(v, v); }

constexpr float kEps96 = 1e-5f * 96.f * 96.f;
__device__ __forceinline__ float2 stat_f32(uint32_t e) {
  const float2 h = unpack_h2(e);
  return make_float2(__uint_as_float(sel(e & 0x8000u, (e << 16) & 0x7fff0000u, __float_as_uint(h.x))),
                     __uint_as_float(sel(e & 0x8000u, e & 0xffff0000u, __float_as_uint(h.y))));
}

struct Tile {
  uint32_t ring, a;
  uint32_t next;
  uint32_t n;
  int live;
  uint32_t stat, wrap;
  uint32_t flag;
  uint32_t gate;
};
struct TPar { float kt, sgmin, outmax; };

__device__ __forceinline__ uint32_t swz(uint32_t r, int t) { return fresh(r ^ (((r >> 3) + 8 * t) & 0x30)); }
__device__ __forceinline__ void load_rows(uint32_t* x0, uint32_t* x1, uint32_t ring, uint32_t r, int t) {
  const uint32_t a0 = swz(r, t), a1 = swz(r, t + 1), u0 = ring + t * kPlane, u1 = u0 + kPlane;
  lds128(x0, a0 + u0); lds128(x1, a1 + u1);
  lds128(x0 + 4, fresh(a0 ^ 32) + (u0 + kChunk)); lds128(x1 + 4, fresh(a1 ^ 32) + (u1 + kChunk));
  lds128(x0 + 8, a0 + (u0 + 2 * kChunk)); lds128(x1 + 8, a1 + (u1 + 2 * kChunk));
}
__device__ __forceinline__ void to_half(uint32_t (&z)[24], const uint32_t* x, int o0, int o1) {
#pragma unroll
  for (int j = 0; j < 24; j += 2) {
    const int o = j < 12 ? 2 * j : 2 * j - 23;
    if (o < o0 || o >= o1) continue;
    uint32_t t;
    asm("cvt.rz.f16x2.f32 %0, %1, %2;" : "=r"(t) : "f"(__uint_as_float(x[j + 1])), "f"(__uint_as_float(x[j])));
    z[o] = fresh(pack_h2(__uint_as_float(x[j] << 16), __uint_as_float(x[j + 1] << 16)));
    z[o + 2] = fresh(t & 0xfff8fff8u);
  }
}
__device__ __forceinline__ void load_general(uint32_t (&z)[24], uint32_t ring, uint32_t r, int t, float& ie0, float& ie1, float& m0, float& m1) {
  float acc[48];
  uint32_t x0[12], x1[12];
  load_rows(x0, x1, ring, r, t);
#pragma unroll
  for (int j = 0; j < 12; j++) {
    acc[4 * j] = __uint_as_float(x0[j] << 16); acc[4 * j + 1] = __uint_as_float(x0[j] & 0xffff0000u);
    acc[4 * j + 2] = __uint_as_float(x1[j] << 16); acc[4 * j + 3] = __uint_as_float(x1[j] & 0xffff0000u);
  }
  float s[4], q[4];
#pragma unroll
  for (int e = 0; e < 4; e++) { s[e] = acc[e]; q[e] = acc[e] * acc[e]; }
#pragma unroll
  for (int j = 4; j < 48; j++) { s[j & 3] += acc[j]; q[j & 3] = fmaf(acc[j], acc[j], q[j & 3]); }
  const float s0 = quad_sum(s[0] + s[1]), s1 = quad_sum(s[2] + s[3]), q0 = quad_sum(q[0] + q[1]), q1 = quad_sum(q[2] + q[3]);
  const float u0 = rsq_fast(fmaxf(fmaf(-s0, s0, fmaf(q0, 96.f, kEps96)), kEps96));
  const float u1 = rsq_fast(fmaxf(fmaf(-s1, s1, fmaf(q1, 96.f, kEps96)), kEps96));
  const float n0 = -s0 * u0, n1 = -s1 * u1;
  ie0 = 96.f * u0; ie1 = 96.f * u1;
  m0 = s0 * (1.f / 96.f); m1 = s1 * (1.f / 96.f);
#pragma unroll
  for (int j = 0; j < 12; j++) {
    const int o = 8 * (j >> 1) + (j & 1);
    z[2 * j] = pack_h2(fmaf(acc[o], ie0, n0), fmaf(acc[o + 4], ie0, n0));
    z[2 * j + 1] = pack_h2(fmaf(acc[o + 2], ie1, n1), fmaf(acc[o + 6], ie1, n1));
  }
}
template <int M>
__device__ __forceinline__ uint32_t sum2(const uint32_t* z) {
  uint32_t q0, q1;
#pragma unroll
  for (int j = 0; j < 12; j++) {
    const uint32_t u = M == 1 ? h2mul(z[2 * j], 0x1c001c00u) : z[2 * j], v = M == 1 ? h2mul(z[2 * j + 1], 0x1c001c00u) : z[2 * j + 1];
    const uint32_t a = M == 2 ? 0x21552155u : u, b = M == 2 ? 0x21552155u : v;
    q0 = j ? h2fma(u, a, q0) : h2mul(u, a); q1 = j ? h2fma(v, b, q1) : h2mul(v, b);
  }
  return fold_add(q0, q1);
}
template <int M>
__device__ __forceinline__ uint32_t row_sum(const uint32_t* z0, const uint32_t* z1, uint32_t c) {
  const uint32_t a = sum2<M>(z0), b = sum2<M>(z1);
  uint32_t t = h2add(sel(c & 2, b, a), shfl_x(sel(c & 2, a, b), 2));
  t = h2add(t, shfl_x(t, 1));
  return sel(c & 1, t >> 16, t);
}
__device__ __forceinline__ void scores2(const uint32_t* q, const uint32_t* z0, const uint32_t* z1, uint32_t* f) {
  uint32_t d[8];
#pragma unroll
  for (int j = 0; j < 12; j++) {
    const uint32_t kk[4] = {z0[2 * j], z0[2 * j + 1], z1[2 * j], z1[2 * j + 1]};
#pragma unroll
    for (int e = 0; e < 4; e++) {
      d[e] = j ? h2fma(q[2 * j], kk[e], d[e]) : h2mul(q[2 * j], kk[e]);
      d[4 + e] = j ? h2fma(q[2 * j + 1], kk[e], d[4 + e]) : h2mul(q[2 * j + 1], kk[e]);
    }
  }
#pragma unroll
  for (int e = 0; e < 4; e++) f[e] = fold_add(d[2 * e], d[2 * e + 1]);
}
struct Xch { uint32_t keep[2], got[2]; };
__device__ __forceinline__ Xch pair_send(const uint32_t* a, const uint32_t* b, uint32_t c, int m) {
  Xch x;
#pragma unroll
  for (int e = 0; e < 2; e++) { x.keep[e] = fresh(sel(c & m, b[e], a[e])); x.got[e] = shfl_x(sel(c & m, a[e], b[e]), m); }
  return x;
}
__device__ __forceinline__ void pair_recv(uint32_t* k, const Xch& x) { k[0] = h2add(x.keep[0], x.got[0]); k[1] = h2add(x.keep[1], x.got[1]); }
__device__ __forceinline__ void mix2(uint32_t* y, const uint32_t* v, uint32_t c0, uint32_t c1) {
#pragma unroll
  for (int j = 0; j < 12; j++) {
    y[2 * j] = h2fma(v[2 * j + 1], hi2(c0), h2fma(v[2 * j], lo2(c0), y[2 * j]));
    y[2 * j + 1] = h2fma(v[2 * j + 1], hi2(c1), h2fma(v[2 * j], lo2(c1), y[2 * j + 1]));
  }
  pin<24>(y);
}
__device__ __forceinline__ void norm_store(uint32_t* y, uint32_t r0, uint32_t r1, uint32_t r, int t) {
#pragma unroll
  for (int j = 0; j < 12; j++) { y[2 * j] = h2fma(y[2 * j], lo2(r0), hi2(r0)); y[2 * j + 1] = h2fma(y[2 * j + 1], lo2(r1), hi2(r1)); }
  const uint32_t ma = swz(r, t), mb = fresh(ma ^ 32), u = t * kPlane;
  stsm4(ma + u, y); stsm4(mb + u, y + 4);
  stsm4(mb + (u + kChunk), y + 8); stsm4(ma + (u + kChunk), y + 12);
  stsm4(ma + (u + 2 * kChunk), y + 16); stsm4(mb + (u + 2 * kChunk), y + 20);
}

template <bool kAlways>
__device__ __forceinline__ void gate_open(uint32_t id) {
  if (kAlways) asm volatile("barrier.cta.arrive.aligned %0, 256;" ::"r"(id) : "memory");
  else asm volatile("{\n.reg .pred p;\nsetp.ne.u32 p, %0, 0;\n@p barrier.cta.arrive.aligned %0, 256;\n}" ::"r"(id) : "memory");
}

struct TState { uint32_t z0[24], z1[24], mu, bad; float ie, mm, mz, mq, qq; };
template <bool kDirect>
__device__ __forceinline__ void temporal(TState& S, uint64_t da, const Tile& T, const TPar& P, bool scaled, uint32_t lane, uint32_t& lst) {
  uint32_t (&z0)[24] = S.z0, (&z1)[24] = S.z1;
  const uint32_t c = lane;
  const uint32_t a0 = T.a + lane * 16 + (lane >= 4 * T.n ? T.next : 0);
  uint32_t q0[26], q1[24], v0[24], w1[26], nn = 0, ng = 0, ca0 = 0, ca1 = 0;
  uint32_t* const v1 = w1 + 2;
  float ie = 1.f, mm = 0.f, mq = 0.f;
  bool tiny = false;
  if (kDirect) {
    uint32_t x[48];
    load_rows(x, x + 12, T.ring, a0, 0);
    to_half(z0, x, 0, 16);
    sfence(lst);
    load_rows(x + 24, x + 36, T.ring, a0, 2);
    to_half(z0, x, 16, 24);
    gemm<0, 0, kAtChunk>(q0, z0, da);
    sfence(lst);
    to_half(z1, x + 24, 0, 24);
    const uint32_t n0 = sum2<0>(z0), n1 = sum2<0>(z1);
    nn = fresh(sel(c & 2, n1, n0)); ng = shfl_x(sel(c & 2, n0, n1), 2);
    pin<24>(z1); sfence(lst);
  } else {
    float e[4], m[4];
    load_general(z0, T.ring, a0, 0, e[0], e[1], m[0], m[1]);
    pin<24>(z0); sfence(lst);
    load_general(z1, T.ring, a0, 2, e[2], e[3], m[2], m[3]);
    ie = sel4(c, e[0], e[1], e[2], e[3]);
    mm = sel4(c, m[0], m[1], m[2], m[3]);
    mq = fmaf(-12e-5f * ie, ie, 12.f);
    tiny = __any_sync(0xffffffffu, ie * P.kt > 400.f);
    if (tiny) {
      float u = 0.f;
#pragma unroll
      for (int r = 0; r < 4; r++) {
        float t = 0.f;
#pragma unroll
        for (int j = 0; j < 12; j++) { const float2 f = unpack_h2((r & 2 ? z1 : z0)[2 * j + (r & 1)]); t = fmaf(f.x, f.x, fmaf(f.y, f.y, t)); }
        u = fmaxf(u, quad_sum(t));
      }
      const float t = fminf(ie, 9.8f * rsq_fast(fmaxf(u, 2e-7f)) * rcp_fast(fresh(P.kt)));
      const uint32_t a = pack_h2(__fdividef(t, ie), 0.f);
      ca0 = __byte_perm(shfl_q(a, 0), shfl_q(a, 1), 0x5410); ca1 = __byte_perm(shfl_q(a, 2), shfl_q(a, 3), 0x5410);
      mq *= low_f(a) * low_f(a);
      ie = t;
    }
    gemm<0, 0, kAtChunk>(q0, z0, da);
  }
  uint32_t f[4], k0[2], k1[2], sk[2];
  wg_wait(); pin<26>(q0);
  gemm<0, 0, kAtChunk>(q1, z1, da);
  gate_open<kDirect>(T.gate);
  if (kDirect) { nn = h2add(nn, ng); ng = shfl_x(nn, 1); }
  sfence(lst);
  scores2(q0, z0, z1, f);
  const uint32_t nu0 = fresh(__byte_perm(q0[24], q0[25], 0x7632)), m01 = fresh(sel(c & 1, q0[25], q0[24]));
  Xch xc = pair_send(f, f + 2, c, 1);
  sfence(lst);
  wg_wait(); pin<24>(q1);
  gemm<0, kOffWt - 512, kAtChunk>(w1, z1, da);
  sfence(lst);
  pair_recv(k0, xc);
  float e2 = 0.f, lim = 0.f;
  if (kDirect) {
    nn = h2add(nn, ng);
    e2 = fresh(fmaf(low_f(sel(c & 1, nn >> 16, nn)), 1.f / 96.f, 1e-5f));
    lim = fresh(e2 <= 4.f ? fmaxf(0.5f * e2, 4e-4f) : __uint_as_float(0x7fffffffu));
  }
  scores2(q1, z0, z1, f);
  xc = pair_send(f, f + 2, c, 1);
  pin<2>(k0); sfence(lst);
  wg_wait(); pin<26>(w1);
  float mz = 0.f, d2 = 0.f;
  if (kDirect) {
    mz = low_f(sel(c & 2, sel(c & 1, w1[1], w1[0]), m01));
    d2 = fmaf(-mz, mz, e2);
    asm volatile("{\n.reg .pred p;\nsetp.lt.s32 p, %3, %4;\nsetp.ltu.and.f32 p, %1, %2, p;\n@p st.volatile.shared.f32 [%0], %2;\n}" ::"r"(T.flag), "f"(d2),
                 "f"(lim), "r"(lane), "r"(T.live) : "memory");
  }
  gemm<0, kOffWt, kAtChunk>(v0, z0, da);
  sfence(lst);
  if (kDirect) mq = fresh(fmaf(e2, 108.f, -96.f * d2));
  uint32_t cw[8], mu;
  {
    uint32_t rc = 0, r0 = 0, r1 = 0;
    if (kDirect) {
      const float r = rsq_fast(d2);
      rc = pack_h2(r, r);
      r0 = __byte_perm(shfl_q(rc, 0), shfl_q(rc, 1), 0x5410); r1 = __byte_perm(shfl_q(rc, 2), shfl_q(rc, 3), 0x5410);
    }
    pair_recv(k1, xc);
    pair_recv(sk, pair_send(k0, k1, c, 2));
    if (kDirect) { sk[0] = h2mul(sk[0], r0); sk[1] = h2mul(sk[1], r1); }
    uint32_t mx = h2max(sk[0], sk[1]);
    mx = h2max(lo2(mx), hi2(mx));
    if (kDirect) {
      const uint32_t nm = h2mul(h2neg(mx), rc);
      sk[0] = h2fma(sk[0], rc, nm); sk[1] = h2fma(sk[1], rc, nm);
    } else {
      sk[0] = h2sub(sk[0], mx); sk[1] = h2sub(sk[1], mx);
      if (scaled) {
        const uint32_t cs = dup_h2(PAR(T.ring, cS_t));
        sk[0] = h2mul(sk[0], cs); sk[1] = h2mul(sk[1], cs);
      }
    }
    sk[0] = h2ex2(sk[0]); sk[1] = h2ex2(sk[1]);
    const uint32_t sm = h2add(sk[0], sk[1]);
    const float iv = (kDirect ? P.kt : P.kt * ie) * rcp_fast(low_f(h2add(lo2(sm), hi2(sm))));
    const uint32_t inv = pack_h2(iv, iv);
    if (kDirect) { sk[0] = h2mul(sk[0], r0); sk[1] = h2mul(sk[1], r1); }
    sk[0] = h2mul(sk[0], inv); sk[1] = h2mul(sk[1], inv);
#pragma unroll
    for (int i = 0; i < 4; i++) { cw[2 * i] = shfl_q(sk[0], i); cw[2 * i + 1] = shfl_q(sk[1], i); }
    mu = h2fma(sk[1], __byte_perm(w1[0], w1[1], 0x7632), h2mul(sk[0], nu0));
    mu = h2add(lo2(mu), hi2(mu));
  }
  uint32_t bad = 0;
  if (kDirect) {
    mix2(z1, v1, cw[5], cw[7]);
    sfence(lst);
    wg_wait(); pin<24>(v0);
    mix2(z1, v0, cw[4], cw[6]);
    sfence(lst);
    bad = lds32(T.flag);
  } else {
    wg_wait(); pin<24>(v0);
    if (tiny) {
#pragma unroll
      for (int j = 0; j < 12; j++) {
        z0[2 * j] = h2mul(z0[2 * j], lo2(ca0)); z0[2 * j + 1] = h2mul(z0[2 * j + 1], hi2(ca0));
        z1[2 * j] = h2mul(z1[2 * j], lo2(ca1)); z1[2 * j + 1] = h2mul(z1[2 * j + 1], hi2(ca1));
      }
    }
    mix2(z1, v1, cw[5], cw[7]);
    mix2(z1, v0, cw[4], cw[6]);
  }
  mix2(z0, v1, cw[1], cw[3]);
  mix2(z0, v0, cw[0], cw[2]);
  S.qq = low_f(row_sum<0>(z0, z1, c));
  S.mu = mu; S.bad = bad; S.ie = ie; S.mm = mm; S.mz = mz; S.mq = mq;
}
__device__ __forceinline__ bool irregular(const TState& S, const Tile& T, uint32_t lane) {
  return __any_sync(0xffffffffu, (!((S.qq < 65000.f) & (S.qq >= S.mq)) & ((int)lane < T.live)) | (S.bad != 0));
}
__device__ __forceinline__ void resum(TState& S, uint32_t lane) {
  uint32_t m = dup_h2(S.mz);
  S.mz = 0.f;
#pragma unroll 1
  for (int k = 0; k < 2; k++) {
    const uint32_t m0 = shfl_q(m, 0), m1 = shfl_q(m, 1), m2 = shfl_q(m, 2), m3 = shfl_q(m, 3);
#pragma unroll
    for (int j = 0; j < 24; j++) { S.z0[j] = h2sub(S.z0[j], j & 1 ? m1 : m0); S.z1[j] = h2sub(S.z1[j], j & 1 ? m3 : m2); }
    S.mu = h2add(S.mu, m);
    m = lo2(row_sum<2>(S.z0, S.z1, lane));
  }
  const float q1 = low_f(row_sum<0>(S.z0, S.z1, lane)), q2 = low_f(row_sum<1>(S.z0, S.z1, lane)) * 65536.f;
  S.qq = q1 < 65000.f ? q1 : q2;
}
template <bool kDirect>
__device__ __forceinline__ void temporal_out(TState& S, const Tile& T, uint32_t slot, const TPar& P, uint32_t lane, uint32_t lst) {
  uint32_t (&z0)[24] = S.z0, (&z1)[24] = S.z1;
  const uint32_t mu = S.mu;
  const float ie = S.ie, mz = S.mz, qq = S.qq;
  float mm = S.mm;
  const float rf = kDirect ? rsq_fast(fmaf(-mz, mz, fmaf(qq, 1.f / 96.f, 1e-5f))) : rsq_fast(fmaf(qq, 1.f / 96.f, 1e-5f * ie * ie));
  const uint32_t rn = pack_h2_sat(rf, -mz * rf);
  uint32_t rr[4];
#pragma unroll
  for (int i = 0; i < 4; i++) rr[i] = shfl_q(rn, i);
  lane = fresh(lane);
  const uint32_t ma = fresh(T.ring + T.a) + lst + ((lane & 7) >= T.n ? T.next : 0);
  norm_store(z0, rr[0], rr[1], ma, 0);
  const float2 rm = unpack_h2(rn);
  const float sg = rcp_fast(kDirect ? rm.x : rm.x * ie);
  mm = kDirect ? fmaf(-rm.y, sg, low_f(mu)) : fmaf(low_f(mu) * rm.x, sg, mm);
  const uint32_t bars = slot + (lane >= 4 * T.n ? T.next + kPlane : 0);
  const bool ok = (sg >= P.sgmin) & (fmaf(sg, 9.8f, fabsf(mm)) < P.outmax);
  asm volatile("{\n.reg .pred p;\nsetp.lt.s32 p, %2, %3;\n@p st.shared.b32 [%0], %1;\n}" ::"r"(
                   T.stat + fresh((lane & 3) * (kSlot + 31) + lane + (lane >= 4 * T.n ? T.wrap : 0))),
               "r"(sel(ok, pack_h2(sg, mm), pack_bf2(sg, mm) | 0x8000u)), "r"(lane), "r"(T.live) : "memory");
  asm volatile("{\n.reg .pred p;\nsetp.eq.u32 p, %1, 0;\n@p st.shared.b32 [%0], %0;\n}" ::"r"(bars + kWide), "r"((uint32_t)ok) : "memory");
  norm_store(z1, rr[2], rr[3], ma, 2);
}

__device__ __forceinline__ void run_T(uint32_t ring, uint64_t d0, uint64_t d1, uint32_t nfull, uint32_t nrem, bool helper, int wg, int wp, uint32_t lane,
                                      const TPar& P, bool scaled, uint32_t pdir) {
  uint32_t lst = (lane & 7) * 64 + (lane & 8) * (kPlane / 8) + (lane & 16);
  uint32_t p0 = 32 * (wg & 1) + (helper ? 0 : 64) + 8 * wp;
  uint32_t npx = 49 * nfull, pstop = npx - 6 * 49 + 8 * wp;
  if (helper) pstop = 0;
  uint32_t pgap = 0;
  sfence(lane);
  Tile T;
  T.ring = ring;
  T.flag = ring + wg * kSlot + kFlag;
  T.gate = wg == 3 ? 6 : 5 + wg;
  while (true) {
    const uint32_t iw = (p0 * 21400u) >> 20, ow = p0 - 49 * iw;
    const uint32_t slot = ring + (iw & 3) * kSlot, dn = (iw & 3) == 3 ? -3 * kSlot : kSlot;
    asm volatile("{\n.reg .pred p;\nsetp.eq.u32 p, %1, 0;\n@p barrier.cta.sync.aligned %0, 256;\n}" ::"r"(6 - (wg & 1)), "r"((uint32_t)helper) : "memory");
    mbar_wait(slot + kFull, iw >> 2);
    if (ow > 41) mbar_wait(slot + dn + kFull, (iw + 1) >> 2);
    T.a = (iw & 3) * kSlot + ow * 64; T.next = dn - kPlane; T.n = 49 - ow;
    T.live = 4 * (npx - p0);
    T.stat = ring + kXBytes + (p0 - 196 * (iw >> 2)) * 4; T.wrap = (iw & 3) == 3 ? -784 : 0;
    lane = fresh(lane);
    {
      TState S;
      Tile G = T;
      if (p0 >= pdir) {
        temporal<true>(S, d0, T, P, false, lane, lst);
        if (!irregular(S, T, lane)) {
          temporal_out<true>(S, T, slot, P, lane, lst);
          goto stored;
        }
        if (!__any_sync(0xffffffffu, S.bad != 0)) {
          launder<24>(S.z0); launder<24>(S.z1);
          goto centre;
        }
        asm volatile("barrier.cta.sync.aligned %0, 128;" ::"r"(wg + 1) : "memory");
        asm volatile("st.shared.b32 [%0], %1;\nfence.acq_rel.cta;" ::"r"(T.flag), "r"(0) : "memory");
        G.gate = 0;
        pgap = p0 == pdir ? 4 * pgap + 64 : 0;
        pdir = p0 + 64 + pgap;
      }
      temporal<false>(S, d1, G, P, scaled, lane, lst);
      if (irregular(S, T, lane)) {
      centre:
        resum(S, lane);
      }
      temporal_out<false>(S, T, slot, P, lane, lst);
    }
  stored:
    const uint32_t pn = __shfl_sync(0xffffffffu, p0 + 64, 0);
    bool last = false;
    if (pn >= pstop) {
      if (helper) last = true;
      else if (pstop < npx - 4 * 49) {
        if (((wg & 1) | wp | lane) == 0) {
          const uint32_t nb = gridDim.x, nwh = min(max((int)(2 * nrem - nb), (int)(nrem / 2)), nrem);
          const uint32_t r = atomicAdd(&g_par.ticket, 1u), j = r - nwh;
          sts32(ring + kExtra, r < nwh ? (nfull * nb + r) * 4 + 3 : j < 2 * (nrem - nwh) ? (nfull * nb + nwh + (j >> 1)) * 4 + 1 + (j & 1) : 0);
        }
        __syncwarp();
        pstop = npx - 2 * 49 + 8 * wp;
      } else if (pstop < npx) {
        if (__shfl_sync(0xffffffffu, lds32(ring + kExtra), 0)) npx += 49;
        pstop = npx + 8 * wp;
      } else last = true;
    }
    asm volatile("fence.proxy.async.shared::cta;" ::: "memory");
    __syncwarp();
    mbar_arrive(slot + kDone + (fresh(lane) >= 4 * T.n ? dn : 0), lane & 3);
    __syncwarp();
    if (last) break;
    p0 = pn;
  }
}

struct Frame {
  bool light;
  uint32_t sta;
  uint32_t oo;
  uint32_t e0, e1;
};
__device__ __forceinline__ uint32_t frame_init(Frame& F, uint32_t ring, uint32_t t, int wp, int lane) {
  wp = (wp + t) & 3;
  F.light = wp == 3;
  F.sta = ring + t * (kSlot + 32) + kXBytes + 64 * wp;
  const uint32_t r = 16 * wp + (lane >> 2);
  F.oo = ((r / 7) * (kW - 7) + r) * 192u + (lane & 3) * 16 + (((((r + 8) / 7 - r / 7) * (kW - 7) + 8) * 3u) << 20);
  F.e0 = F.e1 = 0;
  const uint32_t am = t * kPlane + wp * 1024 + ((lane * 65) & 0x3d0);
  return F.light && (lane & 15) ? kZero : am ^ ((am >> 3) & 0x30);
}
template <bool F>
__device__ __forceinline__ void load_frame(uint32_t (&v)[24], uint32_t ma, uint32_t slot, uint32_t& tid) {
  const uint32_t st = ma < kXBytes ? kChunk : 0, mb = ma ^ 32;
  uint32_t a[6] = {ma, mb, mb + st, ma + st, ma + 2 * st, mb + 2 * st};
  pin<6>(a);
  if (F) sfence(tid);
#pragma unroll
  for (int k = 0; k < 6; k++) ldsm4(v + 4 * k, slot + a[k]);
}
__device__ __forceinline__ void load_block(uint32_t (&v)[24], uint32_t ma, uint32_t slot) {
  const uint32_t mb = fresh(ma ^ 32);
  ldsm4(v, ma + slot); ldsm4(v + 4, mb + slot);
  ldsm4(v + 8, mb + (slot + kChunk)); ldsm4(v + 12, ma + (slot + kChunk));
  ldsm4(v + 16, ma + (slot + 2 * kChunk)); ldsm4(v + 20, mb + (slot + 2 * kChunk));
}
__device__ __forceinline__ void load_light(uint32_t (&v)[24], uint32_t t, uint32_t slot, uint32_t tid) {
  const uint32_t r = t * kPlane + 48 * 64, a0 = ((tid & 3) << 2) | ((r >> 3) & 0x30), u = slot + r, off = tid & 28;
  uint32_t a[4] = {a0, a0 ^ 16, a0 ^ 32, a0 ^ 48};
  pin<4>(a);
#pragma unroll
  for (int j = 0; j < 12; j++) {
    asm volatile("mov.b32 %0, 0;" : "=r"(v[2 * j + 1]));
    asm volatile("{\n.reg .pred p;\nsetp.eq.u32 p, %2, 0;\nmov.b32 %0, 0;\n@p ld.shared.b32 %0, [%1];\n}"
                 : "=r"(v[2 * j]) : "r"(a[(j & 3) ^ (j & 4 ? 2 : 0)] + (u + (j >> 2) * kChunk)), "r"(off) : "memory");
  }
}
__device__ __forceinline__ void load_stats(Frame& F, uint32_t ia, uint32_t tid) {
  const uint32_t a = fresh(tid & 0x1c), u = F.sta + ia * 196;
  F.e0 = lds32(a + u);
  F.e1 = lds32(a + (u + 32));
}
template <int OFF>
__device__ __forceinline__ void gemm_u(uint32_t (&u)[24], const uint32_t* s, uint64_t db) {
  constexpr uint32_t kMN = (((kChunk >> 4) - 1) << 16) + OFF / 16;
  asm volatile("" : "+l"(db));
  wg_fence();
  wgmma<2, 1>(u, s, db + kMN); wgmma<1, 1>(u, s + 4, db + kMN + 64); wgmma<1, 1>(u, s + 8, db + kMN + 128); wgmma<1, 1>(u, s + 12, db + kMN + 192);
  wg_commit();
}
__device__ __forceinline__ uint32_t key48(uint32_t (&s)[16], uint32_t tid) {
  return fresh(sel(tid & 3, 0xfc00fc00u, __byte_perm(s[12], s[13], 0x5410)));
}
__device__ __forceinline__ uint32_t amax3(uint32_t a, uint32_t b, uint32_t c) {
  return as_u(__hmax2(__hmax2(__habs2(as_h2(a)), __habs2(as_h2(b))), __habs2(as_h2(c))));
}
struct Quad { uint32_t v[4]; };
__device__ __forceinline__ void sub_max(uint32_t (&s)[16], uint32_t& t) {
  const uint32_t x0 = h2max(h2max(h2max(s[0], s[2]), h2max(s[4], s[6])), h2max(s[8], s[10]));
  const uint32_t x1 = h2max(h2max(h2max(s[1], s[3]), h2max(s[5], s[7])), h2max(s[9], s[11]));
  uint32_t mx = h2max(h2max(__byte_perm(x0, x1, 0x5410), __byte_perm(x0, x1, 0x7632)), t);
  mx = h2max(mx, shfl_x(mx, 1));
  mx = h2max(mx, shfl_x(mx, 2));
#pragma unroll
  for (int j = 0; j < 6; j++) { s[2 * j] = h2sub(s[2 * j], lo2(mx)); s[2 * j + 1] = h2sub(s[2 * j + 1], hi2(mx)); }
  t = h2sub(t, mx);
}
template <int J>
__device__ __forceinline__ Quad exp_sum(uint32_t (&s)[16], uint32_t& t) {
#pragma unroll
  for (int j = J; j < 12; j++) s[j] = h2ex2(s[j]);
  t = h2ex2(t);
  Quad q;
  q.v[0] = h2add(t, fold_add(h2add(h2add(h2add(s[0], s[2]), h2add(s[4], s[6])), h2add(s[8], s[10])),
                             h2add(h2add(h2add(s[1], s[3]), h2add(s[5], s[7])), h2add(s[9], s[11]))));
#pragma unroll
  for (int i = 1; i < 4; i++) q.v[i] = shfl_x(q.v[0], i);
  return q;
}
__device__ __forceinline__ Quad soft_exp(uint32_t (&s)[16], uint32_t& t) {
  const uint32_t am = h2max(h2max(h2max(amax3(s[0], s[1], s[2]), amax3(s[3], s[4], s[5])), amax3(s[6], s[7], s[8])), h2max(amax3(s[9], s[10], s[11]), t));
  uint32_t rare, sp[4];
#pragma unroll
  for (int j = 0; j < 4; j++) sp[j] = fresh(h2ex2(s[j]));
  asm("{\n.reg .pred p, q;\n.reg .b32 t;\nmov.b32 t, 0x49004900;\nsetp.le.f16x2 p|q, %1, t;\nand.pred p, p, q;\nselp.b32 %0, 0, 1, p;\n}" : "=r"(rare) : "r"(am));
  if (__any_sync(0xffffffffu, rare)) {
    sub_max(s, t);
#pragma unroll
    for (int j = 0; j < 4; j++) sp[j] = h2ex2(s[j]);
  }
#pragma unroll
  for (int j = 0; j < 4; j++) s[j] = sp[j];
  return exp_sum<4>(s, t);
}
__device__ __forceinline__ void soft_norm(uint32_t (&s)[16], uint32_t& t, const Quad& q, const Frame& F, float2 e, uint32_t tid) {
  const float2 d = unpack_h2(h2add(h2add(q.v[0], q.v[1]), h2add(q.v[2], q.v[3])));
  const uint32_t cb = pack_h2(rcp_fast(d.x * e.x), rcp_fast(d.y * e.y)) & (sel(tid & 28, 0u, 0xffffu) | fresh(F.light ? 0u : 0xffffffffu));
#pragma unroll
  for (int j = 0; j < 6; j++) { s[2 * j] = h2mul(s[2 * j], lo2(cb)); s[2 * j + 1] = h2mul(s[2 * j + 1], hi2(cb)); }
  t = fresh(h2mul(t, cb));
  pin<12>(s);
}
__device__ __forceinline__ void soft_tail(uint32_t (&s)[16], uint32_t t) {
  s[12] = t & 0xffffu; s[13] = t >> 16;
  asm volatile("mov.b32 %0, 0;\nmov.b32 %1, 0;" : "=r"(s[14]), "=r"(s[15]));
}
template <int H>
__device__ __forceinline__ uint8_t* row_ptr(const Frame& F, uint8_t* o) {
  const uint32_t oo = fresh(F.oo);
  if (H) asm volatile("mad.wide.u32 %0, %1, 64, %0;" : "+l"(o) : "r"(oo >> 20));
  else { o += oo & 0xfffffu; asm volatile("" : "+l"(o)); }
  return o;
}
template <int H>
__device__ __forceinline__ void affine(uint32_t* r, const uint32_t (&v)[24], const Frame& F) {
  const uint32_t e = H ? F.e1 : F.e0;
#pragma unroll
  for (int j = 0; j < 12; j++) r[j] = h2fma(v[2 * j + H], lo2(e), hi2(e));
  pin<12>(r);
}
template <int H, bool kFence = false>
__device__ __forceinline__ void finish(uint32_t* r, const Frame& F, uint8_t*& o, uint32_t off, uint32_t a, uint32_t m, uint32_t& fz) {
  o = row_ptr<H>(F, o);
#pragma unroll
  for (int j = 0; j < 12; j += 2) { const float2 f = unpack_h2(r[j]), g = unpack_h2(r[j + 1]); r[j] = pack_bf2(f.x, g.x); r[j + 1] = pack_bf2(f.y, g.y); }
  pin<12>(r);
  if (kFence) sfence(fz);
  stg3(o, r, off | (fresh(a) & m));
}
__device__ __forceinline__ uint32_t surplus(uint32_t ring, uint32_t i, uint32_t nfull) { return i + 4 == nfull ? lds32(ring + kExtra) >> 2 : 0; }

__device__ __forceinline__ void release(uint32_t ring, uint32_t slot, uint32_t i, uint32_t nfull, uint32_t w, const CUtensorMap* tm, uint32_t lane) {
  uint32_t old = 0;
  asm volatile("{\n.reg .pred p;\nsetp.eq.u32 p, %2, 0;\n@p atom.relaxed.cta.shared::cta.inc.u32 %0, [%1], 1;\n}" : "+r"(old) : "r"(slot + kRel), "r"(lane) : "memory");
  if (old) {
    sts32(slot + kWide, 0);
    if (i + 4 < nfull) tma_load_win(slot, tm, w + 4 * gridDim.x);
    else if (const uint32_t wn = surplus(ring, i, nfull)) tma_load_win(slot, tm, fresh(wn));
    else mbar_arrive(slot + kFull);
  }
  __syncwarp();
}
__device__ __forceinline__ uint32_t window_offset(uint32_t w) { return (((w * 57457u) >> 22) * (7 * kW - 7 * kNWX) + w * 7) * 192u; }

__device__ __forceinline__ void round_wide(uint32_t ring, uint64_t d0, uint32_t frame, uint32_t nfull, uint32_t i, uint32_t w, int sg, int wp, uint32_t lane,
                                           const CUtensorMap* tm, uint8_t* __restrict__ out) {
  const uint32_t slot = ring + (i & 3) * kSlot;
  uint32_t x[24];
#pragma unroll
  for (int j = 0; j < 24; j++) x[j] = 0;
#pragma unroll 1
  for (uint32_t t = 2 * sg; t < 2 * sg + 2; t++) {
    Frame F;
    uint32_t v[24], s[16];
    load_frame<false>(v, frame_init(F, ring, t, wp, lane), slot, lane);
    load_stats(F, i & 3, lane);
    const uint64_t dp = d0 + (uint32_t)((kWBytes + (i & 3) * kSlot + t * kPlane) / 16);
    gemm<2, kOffAs, 6144>(x, v, d0);
    const uint32_t cs = dup_h2(PAR(ring, cS_s));
    const float kb = PAR(ring, kb), ik = rcp_fast(PAR(ring, kappa));
    wg_wait(); pin<24>(x);
    gemm<0, 0, kChunk>(s, x, dp);
    wg_wait(); pin<14>(s);
    uint32_t u = key48(s, lane);
    sub_max(s, u);
#pragma unroll
    for (int j = 0; j < 12; j++) s[j] = h2mul(s[j], cs);
    u = h2mul(u, cs);
    const float2 z0 = stat_f32(F.e0), z1 = stat_f32(F.e1);
    const float e0 = fmaxf(z0.x, kb), e1 = fmaxf(z1.x, kb);
    const uint32_t aw = pack_h2(__fdividef(z0.x, e0), __fdividef(z1.x, e1));
#pragma unroll
    for (int j = 0; j < 12; j++) { v[2 * j] = h2mul(v[2 * j], lo2(aw)); v[2 * j + 1] = h2mul(v[2 * j + 1], hi2(aw)); }
    soft_norm(s, u, exp_sum<0>(s, u), F, make_float2(e0 * ik, e1 * ik), lane);
    soft_tail(s, u);
    gemm_u<0>(x, s, dp);
    wg_wait(); pin<24>(x);
    gemm<1, kOffWs, 6144>(v, x, d0);
    if ((t & 1) && wp == 0) release(ring, slot, i, nfull, w, tm, lane);
    wg_wait(); pin<24>(v);
    uint8_t* o = out + (size_t)(window_offset(w) + t * frame);
#pragma unroll
    for (int h = 0; h < 2; h++) {
      const float e = h ? e1 : e0, m = h ? z1.y : z0.y;
      uint32_t r[12];
#pragma unroll
      for (int j = 0; j < 12; j += 2) {
        const float2 f = unpack_h2(v[2 * j + h]), g = unpack_h2(v[2 * j + 2 + h]);
        r[j] = pack_bf2(fmaf(f.x, e, m), fmaf(g.x, e, m)); r[j + 1] = pack_bf2(fmaf(f.y, e, m), fmaf(g.y, e, m));
      }
      o = h ? row_ptr<1>(F, o) : row_ptr<0>(F, o);
      stg3(o, r, F.light ? (h ? 1 : lane & 28) : 0);
    }
  }
}

__device__ __forceinline__ uint32_t rounds(uint32_t ring, uint64_t d0, uint64_t d1, uint32_t frame, uint32_t nfull, uint32_t i, uint32_t i1, uint32_t w,
                                           int sg, int wp, int lane, const CUtensorMap* tm, uint8_t* __restrict__ out) {
  Frame A, B;
  uint32_t tid = lane + (frame_init(A, ring, 2 * sg, wp, lane) << 4) + (frame_init(B, ring, 2 * sg + 1, wp, lane) << 16);
  uint32_t va[24], vb[24], x[24], sa[16], sc[16], r0[12], r1[12], ta, tb;
  Quad rs;
  uint32_t& fz = A.oo;
#pragma unroll
  for (int j = 0; j < 24; j++) { vb[j] = 0; x[j] = 0; }
  out += sg * 2 * frame;
  asm volatile("" : "+l"(out));
  uint8_t *ob = out, *o;
  const uint64_t dr = d0 + (uint32_t)(kWBytes / 16 + sg * (2 * kPlane / 16));
  uint32_t slot = ring + (i & 3) * kSlot, first = 1;
  load_frame<false>(va, (tid >> 4) & 0xfff0u, slot, tid);
  do {
    const uint32_t ia = i & 3;
    tid = fresh(tid);
    gemm<2, kOffAs, 6144>(x, va, d0);
    sfence(fz);
    affine<0>(r0, vb, B); affine<1>(r1, vb, B);
    load_frame<true>(vb, (tid >> 16) & 0xfff0u, slot, fz);
    uint64_t dp = dr + ia * (kSlot / 16);
    asm volatile("" : "+l"(dp));
    o = ob + frame;
    asm volatile("" : "+l"(o));
    finish<0, true>(r0, B, o, first, tid, B.light ? 28 : 0, fz);
    sfence(fz);
    wg_wait(); pin<24>(x);
    gemm<0, 0, kChunk>(sa, x, dp);
    if (!B.light) finish<1>(r1, B, o, first, 0, 0, fz);
    else if (sg == 0) {
      if ((tid & 31) == 0) {
        if (i + 4 < nfull) tma_prefetch_win(tm, w + 4 * gridDim.x);
        else if (const uint32_t wn = surplus(ring, i, nfull)) tma_prefetch_win(tm, fresh(wn));
      }
      __syncwarp();
    }
    ob = out + (size_t)window_offset(w);
    asm volatile("" : "+l"(ob));
    wg_wait(); pin<14>(sa);
    gemm<2, kOffAs, 6144>(x, vb, d1);
    ta = key48(sa, tid);
    rs = soft_exp(sa, ta);
    load_stats(A, ia, tid);
    sfence(fz);
    wg_wait(); pin<24>(x);
    gemm<0, kPlane, kChunk>(sc, x, dp);
    sfence(fz);
    soft_norm(sa, ta, rs, A, make_float2(low_f(A.e0), low_f(A.e1)), tid);
    sfence(fz);
    wg_wait(); pin<14>(sc);
    tb = key48(sc, tid);
    sfence(fz);
    soft_tail(sa, ta);
    gemm_u<0>(x, sa, dp);
    rs = soft_exp(sc, tb);
    load_stats(B, ia, tid);
    sfence(fz);
    wg_wait(); pin<24>(x);
    gemm<1, kOffWs, 6144>(va, x, d0);
    sfence(fz);
    soft_norm(sc, tb, rs, B, make_float2(low_f(B.e0), low_f(B.e1)), tid);
    soft_tail(sc, tb);
    sfence(fz);
    wg_wait(); pin<24>(va);
    gemm_u<kPlane>(x, sc, dp);
    sfence(fz);
    const uint32_t sn = ring + ((i + 1) & 3) * kSlot;
    const bool slow = mbar_pending_or<kWide - kDone>(sn + kDone, (i + 1) >> 2);
    affine<0>(r0, va, A);
    o = ob;
    finish<0>(r0, A, o, 0, tid, A.light ? 28 : 0, fz);
    sfence(fz);
    wg_wait(); pin<24>(x);
    gemm<1, kOffWs, 6144>(vb, x, d1);
    affine<1>(r1, va, A);
    if (slow || A.light) {
      if (A.light) release(ring, slot, i, nfull, w, tm, tid & 31);
      if (slow) {
        if (i + 1 < i1) mbar_wait(sn + kDone, (i + 1) >> 2);
        if (__any_sync(0xffffffffu, lds32(sn + kWide))) i1 = 0;
      }
    }
    const uint32_t la = (tid >> 4) & 0xfff0u;
    if (!A.light) { load_block(va, la, sn); finish<1>(r1, A, o, 0, la, 0, fz); }
    else load_light(va, 2 * sg, sn, tid);
    wg_wait(); pin<24>(vb);
    launder<24>(vb);
    launder<24>(va);
    slot = sn; w += gridDim.x; first = 0;
  } while (++i < i1);
  o = ob + frame;
  affine<0>(r0, vb, B); finish<0>(r0, B, o, 0, tid, B.light ? 28 : 0, tid);
  affine<1>(r1, vb, B); finish<1>(r1, B, o, B.light, 0, 0, tid);
  return i;
}

__device__ __forceinline__ void run_S(uint32_t ring, uint64_t d0, uint64_t d1, uint32_t frame, uint32_t nfull, uint32_t i, uint32_t i1, uint32_t w0,
                                      int sg, int wp, const CUtensorMap* tm, uint8_t* __restrict__ out) {
  do {
    const uint32_t lane = fresh(threadIdx.x) & 31;
    const uint32_t slot = ring + (i & 3) * kSlot, w = w0 + i * gridDim.x;
    mbar_wait(slot + kDone, i >> 2);
    if (__any_sync(0xffffffffu, (lds32(slot + kWide) != 0) | (PAR(ring, cS_s) != 1.f) | (PAR(ring, kappa) != 1.f))) {
      round_wide(ring, d1, frame, nfull, i, w, sg, wp, lane, tm, out);
      i++;
    } else {
      i = rounds(ring, d0, d1, frame, nfull, i, i1, w, sg, wp, lane, tm, out);
    }
  } while (i < i1);
}

struct Maps { CUtensorMap load, prefetch; };
__global__ void __launch_bounds__(512, 1) swin_main(const __grid_constant__ Maps tms, uint8_t* __restrict__ out, const uint64_t d0,
                                                    const uint64_t d1, const uint32_t frame) {
  extern __shared__ __align__(1024) uint8_t smem[];
  const CUtensorMap& tm = tms.load;
  const uint32_t sb = smem_u32(smem), ring = sb + kWBytes;
  const int tid = threadIdx.x;
  const int wg = __shfl_sync(0xffffffffu, tid >> 7, 0);
  const int wp = __shfl_sync(0xffffffffu, (tid >> 5) & 3, 0);
  const int lane = tid & 31;
  const uint32_t b = blockIdx.x, nb = gridDim.x;
  const uint32_t nfull = kNWIN / nb, nrem = kNWIN - nfull * nb;
  if (tid == 0) {
    if (sb != 1024 || nfull > 700 || nfull < 12) __trap();
#pragma unroll
    for (int i = 0; i < 4; i++) {
      mbar_init(ring + i * kSlot + kFull, 1);
      mbar_init(ring + i * kSlot + kDone, 49);
      sts32(ring + i * kSlot + kRel, 0); sts32(ring + i * kSlot + kFlag, 0); sts32(ring + i * kSlot + kWide, 0);
    }
    asm volatile("fence.mbarrier_init.release.cluster;" ::: "memory");
    for (int i = 0; i < 2; i++) tma_load_win(ring + i * kSlot, &tm, b + i * nb);
  }
  __syncwarp();
  if (wg == 1 || wg == 2)
    asm volatile("st.shared.v4.b32 [%0], {%1,%1,%1,%1};" ::"r"(ring + ((tid - 128) >> 6) * kSlot + kXBytes + (tid & 63) * 16), "r"(0) : "memory");
  __syncthreads();
  asm volatile("griddepcontrol.wait;" ::: "memory");
#pragma unroll
  for (int q = 0; q < kWBytes / 16 / 512; q++)
    asm volatile("cp.async.cg.shared.global [%0], [%1], 16;" ::"r"(sb + (tid + q * 512) * 16), "l"(g_wimg + tid + q * 512) : "memory");
  if (wg == 0 && wp < 3) {
    static_assert(kWBytes / 16 == 9 * 512 + 96, "weight copy split");
    const int e = tid + 9 * 512;
    asm volatile("cp.async.cg.shared.global [%0], [%1], 16;" ::"r"(sb + e * 16), "l"(g_wimg + e) : "memory");
  }
  if (wg == 0 && wp == 3)
    asm volatile("cp.async.ca.shared.global [%0], [%1], 4;" ::"r"(ring + kPar + lane * 4), "l"(reinterpret_cast<const float*>(&g_par) + lane) : "memory");
  asm volatile("cp.async.wait_all;\nfence.proxy.async.shared::cta;" ::: "memory");
  __syncthreads();
  const float kb = PAR(ring, kb);
  TPar P;
  P.kt = PAR(ring, kt);
  P.sgmin = fmaxf(0.0045f, kb * 0.011f);
  P.outmax = fmaf(kb, -627.2f, 60000.f);
  const bool scaled = __any_sync(0xffffffffu, PAR(ring, cS_t) != 1.f);
  const uint32_t pdir = __ballot_sync(0xffffffffu, scaled || !(P.kt <= 256.f));
  if (tid == 128) for (int i = 2; i < 4; i++) tma_load_win(ring + i * kSlot, &tm, b + i * nb);
  __syncwarp();
  const bool isT = wg < 2;
  run_T(ring, d0, d1, nfull, nrem, !isT, wg, wp, lane, P, scaled, pdir);
  const uint32_t ex = isT ? __shfl_sync(0xffffffffu, lds32(ring + kExtra), 0) : 3;
  if ((ex >> (wg & 1)) & 1) run_S(ring, d0, d1, frame, nfull, isT ? nfull : 0, nfull + isT, isT ? (ex >> 2) - nfull * nb : b, wg & 1, wp, &tm, out);
}

__device__ __forceinline__ int ch_pos(int ch) { return 32 * (ch >> 5) + 16 * ((ch >> 2) & 1) + 8 * (ch & 1) + 2 * ((ch >> 3) & 3) + ((ch >> 1) & 1); }
__device__ __forceinline__ float pow2_ceil(float v) {
  return __uint_as_float((__float_as_uint(v) + 0x7fffffu) & 0x7f800000u);
}

constexpr int kPrepSplit = 12;
constexpr int kPrepThreads = 384;
__global__ void __launch_bounds__(kPrepThreads) swin_prep(const __nv_bfloat16* __restrict__ wqkv_t, const __nv_bfloat16* __restrict__ wo_t,
                                                          const __nv_bfloat16* __restrict__ wqkv_s, const __nv_bfloat16* __restrict__ wo_s) {
  asm volatile("griddepcontrol.launch_dependents;");
  __shared__ __align__(16) uint32_t raw[2][96][52];
  __shared__ __align__(16) uint32_t mu[3][52];
  __shared__ float nrm[12], nrm2[6], csum[6][9];
  const int mat = blockIdx.x / kPrepSplit, blk = blockIdx.x % kPrepSplit;
  const int tid = threadIdx.x, lane = tid & 31, warp = tid >> 5, g = lane >> 2, c = lane & 3;
  const __nv_bfloat16* wqkv = mat < 2 ? wqkv_t : wqkv_s;
  const __nv_bfloat16* wo = mat < 2 ? wo_t : wo_s;
  const bool isA = (mat & 1) == 0;
  {
    uint4 v[3], u[3];
#pragma unroll
    for (int q = 0; q < 3; q++) {
      const int e = tid + q * kPrepThreads, i = e / 12, c8 = (e % 12) * 8;
      v[q] = __ldg(reinterpret_cast<const uint4*>(wqkv + i * 288 + (isA ? 0 : 192) + c8));
      u[q] = __ldg(reinterpret_cast<const uint4*>(isA ? wqkv + i * 288 + 96 + c8 : wo + i * 96 + c8));
    }
#pragma unroll
    for (int q = 0; q < 3; q++) {
      const int e = tid + q * kPrepThreads, i = e / 12, c4 = (e % 12) * 4;
      *reinterpret_cast<uint4*>(&raw[0][i][c4]) = v[q];
      *reinterpret_cast<uint4*>(&raw[1][i][c4]) = u[q];
    }
  }
  __syncthreads();
  {
    const int m = warp / 6, cp = (warp % 6) * 8 + g;
    float s0 = 0.f, s1 = 0.f, q0 = 0.f, q1 = 0.f;
#pragma unroll
    for (int i = 0; i < 24; i++) {
      const uint32_t w = raw[m][4 * i + c][cp];
      const float lo = __uint_as_float(w << 16), hi = __uint_as_float(w & 0xffff0000u);
      s0 += lo; s1 += hi; q0 = fmaf(lo, lo, q0); q1 = fmaf(hi, hi, q1);
    }
    s0 = quad_sum(s0) * (1.f / 96.f); s1 = quad_sum(s1) * (1.f / 96.f); q0 = quad_sum(q0); q1 = quad_sum(q1);
    if (mat == 1 && m == 1) {
      float r0 = 0.f, r1 = 0.f;
#pragma unroll
      for (int i = 0; i < 12; i++) {
        const uint32_t w0 = raw[1][2 * cp][4 * i + c], w1 = raw[1][2 * cp + 1][4 * i + c];
        r0 += __uint_as_float(w0 << 16) + __uint_as_float(w0 & 0xffff0000u);
        r1 += __uint_as_float(w1 << 16) + __uint_as_float(w1 & 0xffff0000u);
      }
      r0 = quad_sum(r0) * (1.f / 96.f); r1 = quad_sum(r1) * (1.f / 96.f);
      s0 = r0; s1 = r1;
    }
    if (m == 1 && c == 0) {
      const uint32_t hi = mat == 3 ? 0u : pack_bf2(s0, s1);
      mu[0][cp] = hi;
      mu[1][cp] = mat == 3 ? 0u : pack_bf2(s0 - __uint_as_float(hi << 16), s1 - __uint_as_float(hi & 0xffff0000u));
      mu[2][cp] = 0u;
    }
    if (m == 0 || isA) {
      q0 = fmaxf(fmaf(-96.f * s0, s0, q0), 0.f) + q0 * 1e-6f;
      q1 = fmaxf(fmaf(-96.f * s1, s1, q1), 0.f) + q1 * 1e-6f;
    }
    const bool usemax = m == 1 && mat == 3;
    float t = usemax ? fmaxf(q0, q1) : q0 + q1;
#pragma unroll
    for (int o = 4; o < 32; o <<= 1) { const float z = __shfl_xor_sync(0xffffffffu, t, o); t = usemax ? fmaxf(t, z) : t + z; }
    if (lane == 0) nrm[warp] = t;
  }
  __syncthreads();
  if (warp >= 6) return;
  float d[4] = {0.f, 0.f, 0.f, 0.f}, e[4] = {0.f, 0.f, 0.f, 0.f}, v0, v1;
  {
    const uint32_t arow = smem_u32(&raw[0][16 * warp + (lane & 15)][(lane >> 4) * 4]);
    const uint32_t brow = isA ? smem_u32(&raw[1][blk * 8 + (lane & 7)][(lane >> 3) * 4]) : smem_u32(&raw[1][lane][blk * 4]);
    const uint32_t mrow = smem_u32(&mu[min(lane & 7, 2)][(lane >> 3) * 4]);
#pragma unroll
    for (int k2 = 0; k2 < 3; k2++) {
      uint32_t b[4], m[4];
      if (isA) ldsm4(b, brow + k2 * 64);
      else asm volatile("ldmatrix.sync.aligned.m8n8.x4.trans.shared.b16 {%0,%1,%2,%3}, [%4];"
                        : "=r"(b[0]), "=r"(b[1]), "=r"(b[2]), "=r"(b[3]) : "r"(brow + k2 * (32 * 208)) : "memory");
      ldsm4(m, mrow + k2 * 64);
#pragma unroll
      for (int hf = 0; hf < 2; hf++) {
        uint32_t a[4];
        ldsm4(a, arow + (2 * k2 + hf) * 32);
        asm volatile("mma.sync.aligned.m16n8k16.row.col.f32.bf16.bf16.f32 {%0,%1,%2,%3},{%4,%5,%6,%7},{%8,%9},{%0,%1,%2,%3};"
                     : "+f"(d[0]), "+f"(d[1]), "+f"(d[2]), "+f"(d[3])
                     : "r"(a[0]), "r"(a[1]), "r"(a[2]), "r"(a[3]), "r"(b[2 * hf]), "r"(b[2 * hf + 1]));
        asm volatile("mma.sync.aligned.m16n8k16.row.col.f32.bf16.bf16.f32 {%0,%1,%2,%3},{%4,%5,%6,%7},{%8,%9},{%0,%1,%2,%3};"
                     : "+f"(e[0]), "+f"(e[1]), "+f"(e[2]), "+f"(e[3])
                     : "r"(a[0]), "r"(a[1]), "r"(a[2]), "r"(a[3]), "r"(m[2 * hf]), "r"(m[2 * hf + 1]));
      }
    }
    v0 = __shfl_sync(0xffffffffu, e[0] + e[1], lane & ~3); v1 = __shfl_sync(0xffffffffu, e[2] + e[3], lane & ~3);
    d[0] -= v0; d[1] -= v0; d[2] -= v1; d[3] -= v1;
    float t0 = d[0] + d[2], t1 = d[1] + d[3], t2 = v0 + v1;
#pragma unroll
    for (int o = 4; o < 32; o <<= 1) {
      t0 += __shfl_xor_sync(0xffffffffu, t0, o); t1 += __shfl_xor_sync(0xffffffffu, t1, o); t2 += __shfl_xor_sync(0xffffffffu, t2, o);
    }
    if (g == 0) { csum[warp][2 * c] = t0; csum[warp][2 * c + 1] = t1; csum[warp][8] = t2; }
  }
  const float nl = nrm[0] + nrm[1] + nrm[2] + nrm[3] + nrm[4] + nrm[5];
  const float nr = mat == 3 ? fmaxf(fmaxf(fmaxf(nrm[6], nrm[7]), fmaxf(nrm[8], nrm[9])), fmaxf(nrm[10], nrm[11]))
                            : nrm[6] + nrm[7] + nrm[8] + nrm[9] + nrm[10] + nrm[11];
  const float bound = __fsqrt_rn(nl) * __fsqrt_rn(nr) * 1.01f;
  const float f = isA ? 0.14724448f : 1.f;
  float sc = pow2_ceil(fmaxf(bound * (isA ? 0.14724448f / 160.f : mat == 1 ? 1.f / 16.f : 1.f / 64.f), 1e-30f));
  if (isA) sc = fminf(fmaxf(sc, 1.f), 32768.f);
  const float kb = sc;
  if (mat == 3 && sc <= 1.f && sc >= 1.f / 1024.f) sc = 1.f;
  const float mul = f * __uint_as_float(0x7f000000u - __float_as_uint(sc));
  if (blk == 0 && tid < 8) reinterpret_cast<float*>(&g_par)[8 * mat + tid] = tid == 0 ? sc : tid == 1 ? kb : 0.f;
  asm volatile("bar.sync 1, 192;" ::: "memory");
  float mean[2];
#pragma unroll
  for (int b = 0; b < 2; b++)
    mean[b] = (csum[0][2 * c + b] + csum[1][2 * c + b] + csum[2][2 * c + b] + csum[3][2 * c + b] + csum[4][2 * c + b] + csum[5][2 * c + b]) *
              (1.f / 96.f);
  const uint32_t img = mat == 0 ? 0 : mat == 1 ? kOffWt : mat == 2 ? kOffAs : kOffWs;
  const float vmean = (csum[0][8] + csum[1][8] + csum[2][8] + csum[3][8] + csum[4][8] + csum[5][8]) * (1.f / 96.f);
  float off = 0.f;
  if (mat == 2) {
    float q2 = 0.f;
#pragma unroll
    for (int q = 0; q < 4; q++) q2 = fmaf(d[q] - mean[q & 1], d[q] - mean[q & 1], q2);
#pragma unroll
    for (int o = 16; o; o >>= 1) q2 += __shfl_xor_sync(0xffffffffu, q2, o);
    if (lane == 0) nrm2[warp] = q2;
    asm volatile("bar.sync 1, 192;" ::: "memory");
    q2 = nrm2[0] + nrm2[1] + nrm2[2] + nrm2[3] + nrm2[4] + nrm2[5];
    off = 1.5f * pow2_ceil(fmaxf(__fsqrt_rn(q2 * (1.f / 768.f)) * mul * 3.f, 1e-4f));
  }
  __half (*stage)[8][96] = reinterpret_cast<__half (*)[8][96]>(&raw[0][0][0]);
#pragma unroll
  for (int q = 0; q < 4; q++) {
    const int kp = ch_pos(16 * warp + g + 8 * (q >> 1));
    const float o = (d[q] - mean[q & 1]) * mul;
    stage[0][2 * c + (q & 1)][kp] = __float2half_rn(mat == 2 ? o + off : __uint_as_float((__float_as_uint(o) + 0x8000u) & 0xffff0000u));
    stage[1][2 * c + (q & 1)][kp] = __float2half_rn((q & 1) ? ((q >> 1 ? v1 : v0) - vmean) * mul : 1.f / 96.f);
  }
  asm volatile("bar.sync 1, 192;" ::: "memory");
  const int ext = tid >= 96, n = (tid >> 2) & 7, ch = (tid - 96 * ext) >> 5;
  if (!ext || (mat == 1 && blk == 0)) {
    uint32_t a = (ext ? 0 : img) + ch * (mat < 2 ? kAtChunk : 6144) + (ext ? 96 + n : ch_pos(blk * 8 + n)) * 64 + c * 16;
    a ^= ((a >> 7) & 3) << 4;
    g_wimg[a >> 4] = *reinterpret_cast<const uint4*>(&stage[ext][n][32 * ch + 8 * c]);
  }
}

typedef CUresult (*EncodeFn)(CUtensorMap*, CUtensorMapDataType, cuuint32_t, void*, const cuuint64_t*, const cuuint64_t*,
                             const cuuint32_t*, const cuuint32_t*, CUtensorMapInterleave, CUtensorMapSwizzle,
                             CUtensorMapL2promotion, CUtensorMapFloatOOBfill);

}

extern "C" void kernel_launch(void* const* d_in, const int* in_sizes, int n_in, void* d_out, int out_size) {
  (void)in_sizes; (void)n_in; (void)out_size;
  static EncodeFn enc = nullptr;
  static int nsm = 0;
  if (!enc) {
    void* fn = nullptr;
    cudaDriverEntryPointQueryResult qr;
    cudaGetDriverEntryPoint("cuTensorMapEncodeTiled", &fn, cudaEnableDefault, &qr);
    enc = reinterpret_cast<EncodeFn>(fn);
    int dev = 0;
    cudaGetDevice(&dev);
    cudaDeviceGetAttribute(&nsm, cudaDevAttrMultiProcessorCount, dev);
    cudaFuncSetAttribute(swin_main, cudaFuncAttributeMaxDynamicSharedMemorySize, kSmemBytes);
  }
  Maps tms;
  CUtensorMap& tm = tms.load;
  const cuuint64_t dims[5] = {32, kW, kH, kT, 3};
  const cuuint64_t strides[4] = {192, 192ull * kW, 192ull * kW * kH, 64};
  const cuuint32_t box[5] = {32, 7, 7, 4, 3};
  const cuuint32_t es[5] = {1, 1, 1, 1, 1};
  enc(&tm, CU_TENSOR_MAP_DATA_TYPE_BFLOAT16, 5, d_in[0], dims, strides, box, es, CU_TENSOR_MAP_INTERLEAVE_NONE,
      CU_TENSOR_MAP_SWIZZLE_64B, CU_TENSOR_MAP_L2_PROMOTION_L2_128B, CU_TENSOR_MAP_FLOAT_OOB_FILL_NONE);

  const cuuint64_t dims2[3] = {24ull * kW, kH, kT};
  const cuuint64_t strides2[2] = {192ull * kW, 192ull * kW * kH};
  const cuuint32_t box2[3] = {168, 7, 4};
  enc(&tms.prefetch, CU_TENSOR_MAP_DATA_TYPE_UINT64, 3, d_in[0], dims2, strides2, box2, es, CU_TENSOR_MAP_INTERLEAVE_NONE,
      CU_TENSOR_MAP_SWIZZLE_NONE, CU_TENSOR_MAP_L2_PROMOTION_L2_128B, CU_TENSOR_MAP_FLOAT_OOB_FILL_NONE);

  cudaStream_t st = cudaStreamPerThread;
  swin_prep<<<4 * kPrepSplit, kPrepThreads, 0, st>>>(
      static_cast<const __nv_bfloat16*>(d_in[1]), static_cast<const __nv_bfloat16*>(d_in[2]),
      static_cast<const __nv_bfloat16*>(d_in[3]), static_cast<const __nv_bfloat16*>(d_in[4]));

  cudaLaunchConfig_t cfg = {};
  cfg.gridDim = dim3(nsm);
  cfg.blockDim = dim3(512);
  cfg.dynamicSmemBytes = kSmemBytes;
  cfg.stream = st;
  cudaLaunchAttribute at[1];
  at[0].id = cudaLaunchAttributeProgrammaticStreamSerialization;
  at[0].val.programmaticStreamSerializationAllowed = 1;
  cfg.attrs = at;
  cfg.numAttrs = 1;
  cudaLaunchKernelEx(&cfg, swin_main, tms, static_cast<uint8_t*>(d_out), mk_desc(1024), mk_desc(1024), (uint32_t)(kH * kW * 192));
}
```

```cpp
#include <cuda_runtime.h>
#include <cuda.h>
#include <cuda_bf16.h>
#include <cuda_fp16.h>
#include <stddef.h>
#include <stdint.h>

namespace {

constexpr int kH = 511, kW = 511, kT = 4;
constexpr int kNWX = 73, kNWIN = 73 * 73;
constexpr int kChunk = 12544;
constexpr int kPlane = 3136;
constexpr int kXBytes = 37632;
constexpr int kZero = kXBytes + 896, kFull = kXBytes + 1024, kDone = kFull + 8, kRel = kFull + 16, kFlag = kFull + 20, kExtra = kFull + 24,
              kWide = kFull + 28;
constexpr int kPar = kFull + 128;
constexpr int kSlot = 38912;
constexpr int kWMat = 18432;
constexpr int kAtChunk = 200 * 64;
constexpr int kOffWt = 104 * 64;
constexpr int kOffAs = 3 * kAtChunk, kOffWs = kOffAs + kWMat;
constexpr int kWBytes = kOffWs + kWMat;
constexpr int kSmemBytes = kWBytes + 4 * kSlot;

struct Params {
  float cS_t, ka, pad0[6];
  float kt, pad1[7];
  float cS_s, pad2[7];
  float kappa;
  float kb;
  uint32_t ticket, pad3[5];
};

__device__ __align__(128) uint4 g_wimg[kWBytes / 16];
__device__ __align__(128) Params g_par;

__device__ __forceinline__ uint32_t smem_u32(const void* p) { return (uint32_t)__cvta_generic_to_shared(p); }
__device__ __forceinline__ void mbar_init(uint32_t a, int c) { asm volatile("mbarrier.init.shared::cta.b64 [%0], %1;" ::"r"(a), "r"(c)); }
__device__ __forceinline__ void mbar_expect(uint32_t a, int bytes) {
  asm volatile("mbarrier.arrive.expect_tx.shared::cta.b64 _, [%0], %1;" ::"r"(a), "r"(bytes) : "memory");
}
__device__ __forceinline__ void mbar_arrive(uint32_t a, uint32_t off = 0) {
  asm volatile("{\n.reg .pred p;\nsetp.eq.u32 p, %1, 0;\n@p mbarrier.arrive.shared::cta.b64 _, [%0];\n}" ::"r"(a), "r"(off) : "memory");
}
__device__ __forceinline__ void mbar_wait(uint32_t a, uint32_t par) {
  asm volatile(
      "{\n.reg .pred p;\n.reg .u32 n;\n"
      "mbarrier.try_wait.parity.shared::cta.b64 p, [%0], %1;\n"
      "@p bra.uni WDONE;\n"
      "mov.u32 n, 0;\n"
      "WLOOP:\n"
      "mbarrier.try_wait.parity.shared::cta.b64 p, [%0], %1;\n"
      "@p bra.uni WDONE;\n"
      "add.u32 n, n, 1;\n"
      "setp.lt.u32 p, n, 0x100000;\n"
      "@p bra.uni WLOOP;\n"
      "trap;\n"
      "WDONE:\n}" ::"r"(a), "r"(par & 1) : "memory");
}
template <int OFF>
__device__ __forceinline__ bool mbar_pending_or(uint32_t a, uint32_t par) {
  uint32_t r;
  asm volatile("{\n.reg .pred p;\n.reg .b32 t;\nmbarrier.test_wait.parity.shared::cta.b64 p, [%1], %2;\nld.shared.b32 t, [%1+%3];\n"
               "setp.ne.or.u32 p, t, 0, !p;\nvote.sync.any.pred p, p, 0xffffffff;\nselp.b32 %0, 1, 0, p;\n}"
               : "=r"(r) : "r"(a), "r"(par & 1), "n"(OFF) : "memory");
  return r;
}
__device__ __forceinline__ uint32_t lds32(uint32_t a) {
  uint32_t v; asm volatile("ld.shared.b32 %0, [%1];" : "=r"(v) : "r"(a) : "memory"); return v;
}
__device__ __forceinline__ void sts32(uint32_t a, uint32_t v) { asm volatile("st.shared.b32 [%0], %1;" ::"r"(a), "r"(v) : "memory"); }
__device__ __forceinline__ void tma_load_win(uint32_t slot, const CUtensorMap* m, uint32_t w) {
  const uint32_t wy = (w * 57457u) >> 22, wx = w - wy * kNWX;
  mbar_expect(slot + kFull, kXBytes);
  asm volatile(
      "cp.async.bulk.tensor.5d.shared::cluster.global.mbarrier::complete_tx::bytes [%0], [%1, {%3,%4,%5,%3,%3}], [%2];" ::"r"(slot),
      "l"(m), "r"(slot + kFull), "r"(0), "r"(wx * 7), "r"(wy * 7)
      : "memory");
}
__device__ __forceinline__ void tma_prefetch_win(const CUtensorMap* m, uint32_t w) {
  const uint32_t wy = (w * 57457u) >> 22, wx = w - wy * kNWX;
  asm volatile("cp.async.bulk.prefetch.tensor.3d.L2.global [%0, {%1,%2,%3}];" ::"l"(m + 1), "r"(wx * 168), "r"(wy * 7), "r"(0) : "memory");
}
__device__ __forceinline__ void wg_fence() { asm volatile("wgmma.fence.sync.aligned;" ::: "memory"); }
__device__ __forceinline__ void wg_commit() { asm volatile("wgmma.commit_group.sync.aligned;" ::: "memory"); }
__device__ __forceinline__ void wg_wait() { asm volatile("wgmma.wait_group.sync.aligned 0;" ::: "memory"); }
template <int N>
__device__ __forceinline__ void pin(uint32_t* d) {
#pragma unroll
  for (int i = 0; i < N; i++) asm volatile("" : "+r"(d[i])::"memory");
}
__device__ __forceinline__ uint32_t fresh(uint32_t v) { asm volatile("" : "+r"(v)); return v; }
__device__ __forceinline__ float fresh(float v) { asm volatile("" : "+f"(v)); return v; }
template <int N>
__device__ __forceinline__ void launder(uint32_t* q) {
#pragma unroll
  for (int j = 0; j < N; j++) { uint32_t t; asm volatile("mov.b32 %0, %1;" : "=r"(t) : "r"(q[j])); q[j] = t; }
}
__device__ __forceinline__ void sfence(uint32_t& v) {
  asm volatile("{\n.reg .pred p;\nsetp.eq.u32 p, %1, 0x7fffffff;\n@p mov.u32 %0, %%clock;\n}" : "+r"(v) : "r"(gridDim.x) : "memory");
}
constexpr uint64_t mk_desc(uint32_t addr) { return ((uint64_t)0x80000020u << 32) | (addr >> 4) | (1u << 16); }

#define R4(d, i) "+r"(d[i]), "+r"(d[i + 1]), "+r"(d[i + 2]), "+r"(d[i + 3])
#define O4(d, i) "=r"(d[i]), "=r"(d[i + 1]), "=r"(d[i + 2]), "=r"(d[i + 3])
#define D26 "{%0,%1,%2,%3,%4,%5,%6,%7,%8,%9,%10,%11,%12,%13,%14,%15,%16,%17,%18,%19,%20,%21,%22,%23,%24,%25},"
#define D24 "{%0,%1,%2,%3,%4,%5,%6,%7,%8,%9,%10,%11,%12,%13,%14,%15,%16,%17,%18,%19,%20,%21,%22,%23},"
#define D14 "{%0,%1,%2,%3,%4,%5,%6,%7,%8,%9,%10,%11,%12,%13},"

template <int SC, int TB>
__device__ __forceinline__ void wgmma(uint32_t (&d)[24], const uint32_t* a, uint64_t db) {
  if (SC == 2)
    asm volatile("{\n.reg .pred p;\nsetp.eq.u32 p, %30, 0x7fffffff;\n"
                 "wgmma.mma_async.sync.aligned.m64n96k16.f16.f16.f16 " D24 "{%24,%25,%26,%27}, %28, p, 1, 1, %29;\n}"
                 : R4(d, 0), R4(d, 4), R4(d, 8), R4(d, 12), R4(d, 16), R4(d, 20)
                 : "r"(a[0]), "r"(a[1]), "r"(a[2]), "r"(a[3]), "l"(db), "n"(TB), "r"(gridDim.x));
  else if (SC)
    asm volatile("wgmma.mma_async.sync.aligned.m64n96k16.f16.f16.f16 " D24 "{%24,%25,%26,%27}, %28, 1, 1, 1, %29;"
                 : R4(d, 0), R4(d, 4), R4(d, 8), R4(d, 12), R4(d, 16), R4(d, 20)
                 : "r"(a[0]), "r"(a[1]), "r"(a[2]), "r"(a[3]), "l"(db), "n"(TB));
  else
    asm volatile("wgmma.mma_async.sync.aligned.m64n96k16.f16.f16.f16 " D24 "{%24,%25,%26,%27}, %28, 0, 1, 1, %29;"
                 : O4(d, 0), O4(d, 4), O4(d, 8), O4(d, 12), O4(d, 16), O4(d, 20)
                 : "r"(a[0]), "r"(a[1]), "r"(a[2]), "r"(a[3]), "l"(db), "n"(TB));
}
template <int SC, int TB>
__device__ __forceinline__ void wgmma(uint32_t (&d)[26], const uint32_t* a, uint64_t db) {
  if (SC)
    asm volatile("wgmma.mma_async.sync.aligned.m64n104k16.f16.f16.f16 " D26 "{%26,%27,%28,%29}, %30, 1, 1, 1, 0;"
                 : R4(d, 0), R4(d, 4), R4(d, 8), R4(d, 12), R4(d, 16), R4(d, 20), "+r"(d[24]), "+r"(d[25])
                 : "r"(a[0]), "r"(a[1]), "r"(a[2]), "r"(a[3]), "l"(db));
  else
    asm volatile("wgmma.mma_async.sync.aligned.m64n104k16.f16.f16.f16 " D26 "{%26,%27,%28,%29}, %30, 0, 1, 1, 0;"
                 : O4(d, 0), O4(d, 4), O4(d, 8), O4(d, 12), O4(d, 16), O4(d, 20), "=r"(d[24]), "=r"(d[25])
                 : "r"(a[0]), "r"(a[1]), "r"(a[2]), "r"(a[3]), "l"(db));
}
template <int SC, int TB>
__device__ __forceinline__ void wgmma(uint32_t (&d)[16], const uint32_t* a, uint64_t db) {
  if (SC)
    asm volatile("wgmma.mma_async.sync.aligned.m64n56k16.f16.f16.f16 " D14 "{%14,%15,%16,%17}, %18, 1, 1, 1, 0;"
                 : R4(d, 0), R4(d, 4), R4(d, 8), "+r"(d[12]), "+r"(d[13])
                 : "r"(a[0]), "r"(a[1]), "r"(a[2]), "r"(a[3]), "l"(db));
  else
    asm volatile("wgmma.mma_async.sync.aligned.m64n56k16.f16.f16.f16 " D14 "{%14,%15,%16,%17}, %18, 0, 1, 1, 0;"
                 : O4(d, 0), O4(d, 4), O4(d, 8), "=r"(d[12]), "=r"(d[13])
                 : "r"(a[0]), "r"(a[1]), "r"(a[2]), "r"(a[3]), "l"(db));
}
template <int SC, int OFF, int CH, int ND>
__device__ __forceinline__ void gemm(uint32_t (&d)[ND], const uint32_t* a, uint64_t db) {
  asm volatile("" : "+l"(db));
  wg_fence();
  wgmma<SC, 0>(d, a, db + OFF / 16);
#pragma unroll
  for (int k = 1; k < 6; k++) wgmma<1, 0>(d, a + 4 * k, db + (OFF + (k >> 1) * CH + (k & 1) * 32) / 16);
  wg_commit();
}
__device__ __forceinline__ void lds128(uint32_t* r, uint32_t a) {
  asm volatile("ld.shared.v4.b32 {%0,%1,%2,%3}, [%4];" : "=r"(r[0]), "=r"(r[1]), "=r"(r[2]), "=r"(r[3]) : "r"(a) : "memory");
}
__device__ __forceinline__ void ldsm4(uint32_t* r, uint32_t a) {
  asm volatile("ldmatrix.sync.aligned.m8n8.x4.shared.b16 {%0,%1,%2,%3}, [%4];"
               : "=r"(r[0]), "=r"(r[1]), "=r"(r[2]), "=r"(r[3]) : "r"(a) : "memory");
}
__device__ __forceinline__ void stsm4(uint32_t a, const uint32_t* r) {
  asm volatile("stmatrix.sync.aligned.m8n8.x4.shared.b16 [%0], {%1,%2,%3,%4};" ::"r"(a), "r"(r[0]), "r"(r[1]), "r"(r[2]), "r"(r[3])
               : "memory");
}
__device__ __forceinline__ void stg3(uint8_t* p, const uint32_t* r, uint32_t off) {
  asm volatile("{\n.reg .pred p;\nsetp.eq.u32 p, %13, 0;\n@p st.global.v4.b32 [%0], {%1,%2,%3,%4};\n"
               "@p st.global.v4.b32 [%0+64], {%5,%6,%7,%8};\n@p st.global.v4.b32 [%0+128], {%9,%10,%11,%12};\n}" ::"l"(p),
               "r"(r[0]), "r"(r[1]), "r"(r[2]), "r"(r[3]), "r"(r[4]), "r"(r[5]), "r"(r[6]), "r"(r[7]), "r"(r[8]), "r"(r[9]), "r"(r[10]), "r"(r[11]),
               "r"(off) : "memory");
}
__device__ __forceinline__ uint32_t pack_h2(float lo, float hi) {
  uint32_t r; asm("cvt.rn.f16x2.f32 %0, %1, %2;" : "=r"(r) : "f"(hi), "f"(lo)); return r;
}
__device__ __forceinline__ uint32_t pack_h2_sat(float lo, float hi) {
  uint32_t r; asm("cvt.rn.satfinite.f16x2.f32 %0, %1, %2;" : "=r"(r) : "f"(hi), "f"(lo)); return r;
}
__device__ __forceinline__ uint32_t pack_bf2(float lo, float hi) {
  uint32_t r; asm("cvt.rn.bf16x2.f32 %0, %1, %2;" : "=r"(r) : "f"(hi), "f"(lo)); return r;
}
__device__ __forceinline__ __half2 as_h2(uint32_t v) { return *reinterpret_cast<__half2*>(&v); }
__device__ __forceinline__ uint32_t as_u(__half2 v) { return *reinterpret_cast<uint32_t*>(&v); }
__device__ __forceinline__ float2 unpack_h2(uint32_t v) { return __half22float2(as_h2(v)); }
__device__ __forceinline__ float low_f(uint32_t v) { return __low2float(as_h2(v)); }
__device__ __forceinline__ uint32_t h2ex2(uint32_t v) { uint32_t r; asm("ex2.approx.f16x2 %0, %1;" : "=r"(r) : "r"(v)); return r; }
__device__ __forceinline__ uint32_t h2max(uint32_t a, uint32_t b) { return as_u(__hmax2(as_h2(a), as_h2(b))); }
__device__ __forceinline__ uint32_t h2add(uint32_t a, uint32_t b) { return as_u(__hadd2(as_h2(a), as_h2(b))); }
__device__ __forceinline__ uint32_t h2sub(uint32_t a, uint32_t b) { return as_u(__hsub2(as_h2(a), as_h2(b))); }
__device__ __forceinline__ uint32_t h2mul(uint32_t a, uint32_t b) { return as_u(__hmul2(as_h2(a), as_h2(b))); }
__device__ __forceinline__ uint32_t h2neg(uint32_t a) { return as_u(__hneg2(as_h2(a))); }
__device__ __forceinline__ uint32_t h2fma(uint32_t a, uint32_t b, uint32_t c) { return as_u(__hfma2(as_h2(a), as_h2(b), as_h2(c))); }
__device__ __forceinline__ uint32_t lo2(uint32_t v) { return as_u(__low2half2(as_h2(v))); }
__device__ __forceinline__ uint32_t hi2(uint32_t v) { return as_u(__high2half2(as_h2(v))); }
__device__ __forceinline__ uint32_t fold_add(uint32_t a, uint32_t b) { return h2add(__byte_perm(a, b, 0x5410), __byte_perm(a, b, 0x7632)); }
__device__ __forceinline__ uint32_t sel(uint32_t p, uint32_t a, uint32_t b) {
  uint32_t r; asm("{\n.reg .pred p;\nsetp.ne.u32 p, %3, 0;\nselp.b32 %0, %1, %2, p;\n}" : "=r"(r) : "r"(a), "r"(b), "r"(p)); return r;
}
__device__ __forceinline__ float sel4(uint32_t c, float a0, float a1, float a2, float a3) {
  return __uint_as_float(sel(c & 2, sel(c & 1, __float_as_uint(a3), __float_as_uint(a2)), sel(c & 1, __float_as_uint(a1), __float_as_uint(a0))));
}
__device__ __forceinline__ float rcp_fast(float v) { float r; asm("rcp.approx.ftz.f32 %0, %1;" : "=f"(r) : "f"(v)); return r; }
__device__ __forceinline__ float rsq_fast(float v) { float r; asm("rsqrt.approx.ftz.f32 %0, %1;" : "=f"(r) : "f"(v)); return r; }
__device__ __forceinline__ uint32_t shfl_x(uint32_t v, int m) { return __shfl_xor_sync(0xffffffffu, v, m); }
__device__ __forceinline__ uint32_t shfl_q(uint32_t v, int i) { return __shfl_sync(0xffffffffu, v, i, 4); }
__device__ __forceinline__ float quad_sum(float v) {
  v += __shfl_xor_sync(0xffffffffu, v, 1);
  return v + __shfl_xor_sync(0xffffffffu, v, 2);
}
#define PAR(ring, f) __uint_as_float(lds32((ring) + kPar + offsetof(Params, f)))
__device__ __forceinline__ uint32_t dup_h2(float v) { return pack_h2(v, v); }

constexpr float kEps96 = 1e-5f * 96.f * 96.f;
__device__ __forceinline__ float2 stat_f32(uint32_t e) {
  const float2 h = unpack_h2(e);
  return make_float2(__uint_as_float(sel(e & 0x8000u, (e << 16) & 0x7fff0000u, __float_as_uint(h.x))),
                     __uint_as_float(sel(e & 0x8000u, e & 0xffff0000u, __float_as_uint(h.y))));
}

struct Tile {
  uint32_t ring, a;
  uint32_t next;
  uint32_t n;
  int live;
  uint32_t stat, wrap;
  uint32_t flag;
  uint32_t gate;
};
struct TPar { float kt, e2max, sgmin, outmax; };

__device__ __forceinline__ uint32_t swz(uint32_t r, int t) { return fresh(r ^ (((r >> 3) + 8 * t) & 0x30)); }
__device__ __forceinline__ void load_rows(uint32_t* x0, uint32_t* x1, uint32_t ring, uint32_t r, int t) {
  const uint32_t a0 = swz(r, t), a1 = swz(r, t + 1), u0 = ring + t * kPlane, u1 = u0 + kPlane;
  lds128(x0, a0 + u0); lds128(x1, a1 + u1);
  lds128(x0 + 4, fresh(a0 ^ 32) + (u0 + kChunk)); lds128(x1 + 4, fresh(a1 ^ 32) + (u1 + kChunk));
  lds128(x0 + 8, a0 + (u0 + 2 * kChunk)); lds128(x1 + 8, a1 + (u1 + 2 * kChunk));
}
__device__ __forceinline__ void to_half(uint32_t (&z)[24], const uint32_t* x, int o0, int o1) {
#pragma unroll
  for (int j = 0; j < 24; j += 2) {
    const int o = j < 12 ? 2 * j : 2 * j - 23;
    if (o < o0 || o >= o1) continue;
    uint32_t t;
    asm("cvt.rz.f16x2.f32 %0, %1, %2;" : "=r"(t) : "f"(__uint_as_float(x[j + 1])), "f"(__uint_as_float(x[j])));
    z[o] = fresh(pack_h2(__uint_as_float(x[j] << 16), __uint_as_float(x[j + 1] << 16)));
    z[o + 2] = fresh(t & 0xfff8fff8u);
  }
}
__device__ __forceinline__ void load_general(uint32_t (&z)[24], uint32_t ring, uint32_t r, int t, float& ie0, float& ie1, float& m0, float& m1) {
  float acc[48];
  uint32_t x0[12], x1[12];
  load_rows(x0, x1, ring, r, t);
#pragma unroll
  for (int j = 0; j < 12; j++) {
    acc[4 * j] = __uint_as_float(x0[j] << 16); acc[4 * j + 1] = __uint_as_float(x0[j] & 0xffff0000u);
    acc[4 * j + 2] = __uint_as_float(x1[j] << 16); acc[4 * j + 3] = __uint_as_float(x1[j] & 0xffff0000u);
  }
  float s[4], q[4];
#pragma unroll
  for (int e = 0; e < 4; e++) { s[e] = acc[e]; q[e] = acc[e] * acc[e]; }
#pragma unroll
  for (int j = 4; j < 48; j++) { s[j & 3] += acc[j]; q[j & 3] = fmaf(acc[j], acc[j], q[j & 3]); }
  const float s0 = quad_sum(s[0] + s[1]), s1 = quad_sum(s[2] + s[3]), q0 = quad_sum(q[0] + q[1]), q1 = quad_sum(q[2] + q[3]);
  const float u0 = rsq_fast(fmaxf(fmaf(-s0, s0, fmaf(q0, 96.f, kEps96)), kEps96));
  const float u1 = rsq_fast(fmaxf(fmaf(-s1, s1, fmaf(q1, 96.f, kEps96)), kEps96));
  const float n0 = -s0 * u0, n1 = -s1 * u1;
  ie0 = 96.f * u0; ie1 = 96.f * u1;
  m0 = s0 * (1.f / 96.f); m1 = s1 * (1.f / 96.f);
#pragma unroll
  for (int j = 0; j < 12; j++) {
    const int o = 8 * (j >> 1) + (j & 1);
    z[2 * j] = pack_h2(fmaf(acc[o], ie0, n0), fmaf(acc[o + 4], ie0, n0));
    z[2 * j + 1] = pack_h2(fmaf(acc[o + 2], ie1, n1), fmaf(acc[o + 6], ie1, n1));
  }
}
template <int M>
__device__ __forceinline__ uint32_t sum2(const uint32_t* z) {
  uint32_t q0, q1;
#pragma unroll
  for (int j = 0; j < 12; j++) {
    const uint32_t u = M == 1 ? h2mul(z[2 * j], 0x1c001c00u) : z[2 * j], v = M == 1 ? h2mul(z[2 * j + 1], 0x1c001c00u) : z[2 * j + 1];
    const uint32_t a = M == 2 ? 0x21552155u : u, b = M == 2 ? 0x21552155u : v;
    q0 = j ? h2fma(u, a, q0) : h2mul(u, a); q1 = j ? h2fma(v, b, q1) : h2mul(v, b);
  }
  return fold_add(q0, q1);
}
template <int M>
__device__ __forceinline__ uint32_t row_sum(const uint32_t* z0, const uint32_t* z1, uint32_t c) {
  const uint32_t a = sum2<M>(z0), b = sum2<M>(z1);
  uint32_t t = h2add(sel(c & 2, b, a), shfl_x(sel(c & 2, a, b), 2));
  t = h2add(t, shfl_x(t, 1));
  return sel(c & 1, t >> 16, t);
}
__device__ __forceinline__ void scores2(const uint32_t* q, const uint32_t* z0, const uint32_t* z1, uint32_t* f) {
  uint32_t d[8];
#pragma unroll
  for (int j = 0; j < 12; j++) {
    const uint32_t kk[4] = {z0[2 * j], z0[2 * j + 1], z1[2 * j], z1[2 * j + 1]};
#pragma unroll
    for (int e = 0; e < 4; e++) {
      d[e] = j ? h2fma(q[2 * j], kk[e], d[e]) : h2mul(q[2 * j], kk[e]);
      d[4 + e] = j ? h2fma(q[2 * j + 1], kk[e], d[4 + e]) : h2mul(q[2 * j + 1], kk[e]);
    }
  }
#pragma unroll
  for (int e = 0; e < 4; e++) f[e] = fold_add(d[2 * e], d[2 * e + 1]);
}
struct Xch { uint32_t keep[2], got[2]; };
__device__ __forceinline__ Xch pair_send(const uint32_t* a, const uint32_t* b, uint32_t c, int m) {
  Xch x;
#pragma unroll
  for (int e = 0; e < 2; e++) { x.keep[e] = fresh(sel(c & m, b[e], a[e])); x.got[e] = shfl_x(sel(c & m, a[e], b[e]), m); }
  return x;
}
__device__ __forceinline__ void pair_recv(uint32_t* k, const Xch& x) { k[0] = h2add(x.keep[0], x.got[0]); k[1] = h2add(x.keep[1], x.got[1]); }
__device__ __forceinline__ void mix2(uint32_t* y, const uint32_t* v, uint32_t c0, uint32_t c1) {
#pragma unroll
  for (int j = 0; j < 12; j++) {
    y[2 * j] = h2fma(v[2 * j + 1], hi2(c0), h2fma(v[2 * j], lo2(c0), y[2 * j]));
    y[2 * j + 1] = h2fma(v[2 * j + 1], hi2(c1), h2fma(v[2 * j], lo2(c1), y[2 * j + 1]));
  }
  pin<24>(y);
}
__device__ __forceinline__ void norm_store(uint32_t* y, uint32_t r0, uint32_t r1, uint32_t r, int t) {
#pragma unroll
  for (int j = 0; j < 12; j++) { y[2 * j] = h2fma(y[2 * j], lo2(r0), hi2(r0)); y[2 * j + 1] = h2fma(y[2 * j + 1], lo2(r1), hi2(r1)); }
  const uint32_t ma = swz(r, t), mb = fresh(ma ^ 32), u = t * kPlane;
  stsm4(ma + u, y); stsm4(mb + u, y + 4);
  stsm4(mb + (u + kChunk), y + 8); stsm4(ma + (u + kChunk), y + 12);
  stsm4(ma + (u + 2 * kChunk), y + 16); stsm4(mb + (u + 2 * kChunk), y + 20);
}

template <bool kAlways>
__device__ __forceinline__ void gate_open(uint32_t id) {
  if (kAlways) asm volatile("barrier.cta.arrive.aligned %0, 256;" ::"r"(id) : "memory");
  else asm volatile("{\n.reg .pred p;\nsetp.ne.u32 p, %0, 0;\n@p barrier.cta.arrive.aligned %0, 256;\n}" ::"r"(id) : "memory");
}

struct TState { uint32_t z0[24], z1[24], mu, bad; float ie, mm, mz, mq, qq; };
template <bool kDirect>
__device__ __forceinline__ void temporal(TState& S, uint64_t da, const Tile& T, const TPar& P, bool scaled, uint32_t lane, uint32_t& lst) {
  uint32_t (&z0)[24] = S.z0, (&z1)[24] = S.z1;
  const uint32_t c = lane;
  const uint32_t a0 = T.a + lane * 16 + (lane >= 4 * T.n ? T.next : 0);
  uint32_t q0[26], q1[24], v0[24], w1[26], nn = 0, ng = 0, ca0 = 0, ca1 = 0;
  uint32_t* const v1 = w1 + 2;
  float ie = 1.f, mm = 0.f, mq = 0.f;
  bool tiny = false;
  if (kDirect) {
    uint32_t x[48];
    load_rows(x, x + 12, T.ring, a0, 0);
    to_half(z0, x, 0, 16);
    sfence(lst);
    load_rows(x + 24, x + 36, T.ring, a0, 2);
    to_half(z0, x, 16, 24);
    gemm<0, 0, kAtChunk>(q0, z0, da);
    sfence(lst);
    to_half(z1, x + 24, 0, 24);
    const uint32_t n0 = sum2<0>(z0), n1 = sum2<0>(z1);
    nn = fresh(sel(c & 2, n1, n0)); ng = shfl_x(sel(c & 2, n0, n1), 2);
    pin<24>(z1); sfence(lst);
  } else {
    float e[4], m[4];
    load_general(z0, T.ring, a0, 0, e[0], e[1], m[0], m[1]);
    pin<24>(z0); sfence(lst);
    load_general(z1, T.ring, a0, 2, e[2], e[3], m[2], m[3]);
    ie = sel4(c, e[0], e[1], e[2], e[3]);
    mm = sel4(c, m[0], m[1], m[2], m[3]);
    mq = fmaf(-12e-5f * ie, ie, 12.f);
    tiny = __any_sync(0xffffffffu, ie * P.kt > 400.f);
    if (tiny) {
      float u = 0.f;
#pragma unroll
      for (int r = 0; r < 4; r++) {
        float t = 0.f;
#pragma unroll
        for (int j = 0; j < 12; j++) { const float2 f = unpack_h2((r & 2 ? z1 : z0)[2 * j + (r & 1)]); t = fmaf(f.x, f.x, fmaf(f.y, f.y, t)); }
        u = fmaxf(u, quad_sum(t));
      }
      const float t = fminf(ie, 9.8f * rsq_fast(fmaxf(u, 2e-7f)) * rcp_fast(fresh(P.kt)));
      const uint32_t a = pack_h2(__fdividef(t, ie), 0.f);
      ca0 = __byte_perm(shfl_q(a, 0), shfl_q(a, 1), 0x5410); ca1 = __byte_perm(shfl_q(a, 2), shfl_q(a, 3), 0x5410);
      mq *= low_f(a) * low_f(a);
      ie = t;
    }
    gemm<0, 0, kAtChunk>(q0, z0, da);
  }
  uint32_t f[4], k0[2], k1[2], sk[2];
  wg_wait(); pin<26>(q0);
  gemm<0, 0, kAtChunk>(q1, z1, da);
  gate_open<kDirect>(T.gate);
  if (kDirect) { nn = h2add(nn, ng); ng = shfl_x(nn, 1); }
  sfence(lst);
  scores2(q0, z0, z1, f);
  const uint32_t nu0 = fresh(__byte_perm(q0[24], q0[25], 0x7632)), m01 = fresh(sel(c & 1, q0[25], q0[24]));
  Xch xc = pair_send(f, f + 2, c, 1);
  sfence(lst);
  wg_wait(); pin<24>(q1);
  gemm<0, kOffWt - 512, kAtChunk>(w1, z1, da);
  sfence(lst);
  pair_recv(k0, xc);
  float e2 = 0.f, lim = 0.f;
  if (kDirect) {
    nn = h2add(nn, ng);
    e2 = fresh(fmaf(low_f(sel(c & 1, nn >> 16, nn)), 1.f / 96.f, 1e-5f));
    lim = fresh(e2 <= P.e2max ? fmaxf(0.5f * e2, 4e-4f) : __uint_as_float(0x7fffffffu));
  }
  scores2(q1, z0, z1, f);
  xc = pair_send(f, f + 2, c, 1);
  pin<2>(k0); sfence(lst);
  wg_wait(); pin<26>(w1);
  float mz = 0.f, d2 = 0.f;
  if (kDirect) {
    mz = low_f(sel(c & 2, sel(c & 1, w1[1], w1[0]), m01));
    d2 = fmaf(-mz, mz, e2);
    asm volatile("{\n.reg .pred p;\nsetp.lt.s32 p, %3, %4;\nsetp.ltu.and.f32 p, %1, %2, p;\n@p st.volatile.shared.f32 [%0], %2;\n}" ::"r"(T.flag), "f"(d2),
                 "f"(lim), "r"(lane), "r"(T.live) : "memory");
  }
  gemm<0, kOffWt, kAtChunk>(v0, z0, da);
  sfence(lst);
  if (kDirect) mq = fresh(fmaf(e2, 108.f, -96.f * d2));
  uint32_t cw[8], mu;
  {
    uint32_t rc = 0, r0 = 0, r1 = 0;
    if (kDirect) {
      const float r = rsq_fast(d2);
      rc = pack_h2(r, r);
      r0 = __byte_perm(shfl_q(rc, 0), shfl_q(rc, 1), 0x5410); r1 = __byte_perm(shfl_q(rc, 2), shfl_q(rc, 3), 0x5410);
    }
    pair_recv(k1, xc);
    pair_recv(sk, pair_send(k0, k1, c, 2));
    if (kDirect) { sk[0] = h2mul(sk[0], r0); sk[1] = h2mul(sk[1], r1); }
    uint32_t mx = h2max(sk[0], sk[1]);
    mx = h2max(lo2(mx), hi2(mx));
    if (kDirect) {
      const uint32_t nm = h2mul(h2neg(mx), rc);
      sk[0] = h2fma(sk[0], rc, nm); sk[1] = h2fma(sk[1], rc, nm);
    } else {
      sk[0] = h2sub(sk[0], mx); sk[1] = h2sub(sk[1], mx);
      if (scaled) {
        const uint32_t cs = dup_h2(PAR(T.ring, cS_t));
        sk[0] = h2mul(sk[0], cs); sk[1] = h2mul(sk[1], cs);
      }
    }
    sk[0] = h2ex2(sk[0]); sk[1] = h2ex2(sk[1]);
    const uint32_t sm = h2add(sk[0], sk[1]);
    const float iv = (kDirect ? P.kt : P.kt * ie) * rcp_fast(low_f(h2add(lo2(sm), hi2(sm))));
    const uint32_t inv = pack_h2(iv, iv);
    if (kDirect) { sk[0] = h2mul(sk[0], r0); sk[1] = h2mul(sk[1], r1); }
    sk[0] = h2mul(sk[0], inv); sk[1] = h2mul(sk[1], inv);
#pragma unroll
    for (int i = 0; i < 4; i++) { cw[2 * i] = shfl_q(sk[0], i); cw[2 * i + 1] = shfl_q(sk[1], i); }
    mu = h2fma(sk[1], __byte_perm(w1[0], w1[1], 0x7632), h2mul(sk[0], nu0));
    mu = h2add(lo2(mu), hi2(mu));
  }
  uint32_t bad = 0;
  if (kDirect) {
    mix2(z1, v1, cw[5], cw[7]);
    sfence(lst);
    wg_wait(); pin<24>(v0);
    mix2(z1, v0, cw[4], cw[6]);
    sfence(lst);
    bad = lds32(T.flag);
  } else {
    wg_wait(); pin<24>(v0);
    if (tiny) {
#pragma unroll
      for (int j = 0; j < 12; j++) {
        z0[2 * j] = h2mul(z0[2 * j], lo2(ca0)); z0[2 * j + 1] = h2mul(z0[2 * j + 1], hi2(ca0));
        z1[2 * j] = h2mul(z1[2 * j], lo2(ca1)); z1[2 * j + 1] = h2mul(z1[2 * j + 1], hi2(ca1));
      }
    }
    mix2(z1, v1, cw[5], cw[7]);
    mix2(z1, v0, cw[4], cw[6]);
  }
  mix2(z0, v1, cw[1], cw[3]);
  mix2(z0, v0, cw[0], cw[2]);
  S.qq = low_f(row_sum<0>(z0, z1, c));
  S.mu = mu; S.bad = bad; S.ie = ie; S.mm = mm; S.mz = mz; S.mq = mq;
}
__device__ __forceinline__ bool irregular(const TState& S, const Tile& T, uint32_t lane) {
  return __any_sync(0xffffffffu, (!((S.qq < 65000.f) & (S.qq >= S.mq)) & ((int)lane < T.live)) | (S.bad != 0));
}
__device__ __forceinline__ void resum(TState& S, uint32_t lane) {
  uint32_t m = dup_h2(S.mz);
  S.mz = 0.f;
#pragma unroll 1
  for (int k = 0; k < 2; k++) {
    const uint32_t m0 = shfl_q(m, 0), m1 = shfl_q(m, 1), m2 = shfl_q(m, 2), m3 = shfl_q(m, 3);
#pragma unroll
    for (int j = 0; j < 24; j++) { S.z0[j] = h2sub(S.z0[j], j & 1 ? m1 : m0); S.z1[j] = h2sub(S.z1[j], j & 1 ? m3 : m2); }
    S.mu = h2add(S.mu, m);
    m = lo2(row_sum<2>(S.z0, S.z1, lane));
  }
  const float q1 = low_f(row_sum<0>(S.z0, S.z1, lane)), q2 = low_f(row_sum<1>(S.z0, S.z1, lane)) * 65536.f;
  S.qq = q1 < 65000.f ? q1 : q2;
}
template <bool kDirect>
__device__ __forceinline__ void temporal_out(TState& S, const Tile& T, uint32_t slot, const TPar& P, uint32_t lane, uint32_t lst) {
  uint32_t (&z0)[24] = S.z0, (&z1)[24] = S.z1;
  const uint32_t mu = S.mu;
  const float ie = S.ie, mz = S.mz, qq = S.qq;
  float mm = S.mm;
  const float rf = kDirect ? rsq_fast(fmaf(-mz, mz, fmaf(qq, 1.f / 96.f, 1e-5f))) : rsq_fast(fmaf(qq, 1.f / 96.f, 1e-5f * ie * ie));
  const uint32_t rn = pack_h2_sat(rf, -mz * rf);
  uint32_t rr[4];
#pragma unroll
  for (int i = 0; i < 4; i++) rr[i] = shfl_q(rn, i);
  lane = fresh(lane);
  const uint32_t ma = fresh(T.ring + T.a) + lst + ((lane & 7) >= T.n ? T.next : 0);
  norm_store(z0, rr[0], rr[1], ma, 0);
  const float2 rm = unpack_h2(rn);
  const float sg = rcp_fast(kDirect ? rm.x : rm.x * ie);
  mm = kDirect ? fmaf(-rm.y, sg, low_f(mu)) : fmaf(low_f(mu) * rm.x, sg, mm);
  const uint32_t bars = slot + (lane >= 4 * T.n ? T.next + kPlane : 0);
  const bool ok = (sg >= P.sgmin) & (fmaf(sg, 9.8f, fabsf(mm)) < P.outmax);
  asm volatile("{\n.reg .pred p;\nsetp.lt.s32 p, %2, %3;\n@p st.shared.b32 [%0], %1;\n}" ::"r"(
                   T.stat + fresh((lane & 3) * (kSlot + 31) + lane + (lane >= 4 * T.n ? T.wrap : 0))),
               "r"(sel(ok, pack_h2(sg, mm), pack_bf2(sg, mm) | 0x8000u)), "r"(lane), "r"(T.live) : "memory");
  asm volatile("{\n.reg .pred p;\nsetp.eq.u32 p, %1, 0;\n@p st.shared.b32 [%0], %0;\n}" ::"r"(bars + kWide), "r"((uint32_t)ok) : "memory");
  norm_store(z1, rr[2], rr[3], ma, 2);
}

__device__ __forceinline__ void run_T(uint32_t ring, uint64_t d0, uint64_t d1, uint32_t nfull, uint32_t nrem, bool helper, int wg, int wp, uint32_t lane,
                                      const TPar& P, bool scaled, uint32_t pdir) {
  uint32_t lst = (lane & 7) * 64 + (lane & 8) * (kPlane / 8) + (lane & 16);
  uint32_t p0 = 32 * (wg & 1) + (helper ? 0 : 64) + 8 * wp;
  uint32_t npx = 49 * nfull, pstop = npx - 6 * 49 + 8 * wp;
  if (helper) pstop = 0;
  uint32_t pgap = 0;
  sfence(lane);
  Tile T;
  T.ring = ring;
  T.flag = ring + wg * kSlot + kFlag;
  T.gate = wg == 3 ? 6 : 5 + wg;
  while (true) {
    const uint32_t iw = (p0 * 21400u) >> 20, ow = p0 - 49 * iw;
    const uint32_t slot = ring + (iw & 3) * kSlot, dn = (iw & 3) == 3 ? -3 * kSlot : kSlot;
    asm volatile("{\n.reg .pred p;\nsetp.eq.u32 p, %1, 0;\n@p barrier.cta.sync.aligned %0, 256;\n}" ::"r"(6 - (wg & 1)), "r"((uint32_t)helper) : "memory");
    mbar_wait(slot + kFull, iw >> 2);
    if (ow > 41) mbar_wait(slot + dn + kFull, (iw + 1) >> 2);
    T.a = (iw & 3) * kSlot + ow * 64; T.next = dn - kPlane; T.n = 49 - ow;
    T.live = 4 * (npx - p0);
    T.stat = ring + kXBytes + (p0 - 196 * (iw >> 2)) * 4; T.wrap = (iw & 3) == 3 ? -784 : 0;
    lane = fresh(lane);
    {
      TState S;
      Tile G = T;
      if (p0 >= pdir) {
        temporal<true>(S, d0, T, P, false, lane, lst);
        if (!irregular(S, T, lane)) {
          temporal_out<true>(S, T, slot, P, lane, lst);
          goto stored;
        }
        if (!__any_sync(0xffffffffu, S.bad != 0)) {
          launder<24>(S.z0); launder<24>(S.z1);
          goto centre;
        }
        asm volatile("barrier.cta.sync.aligned %0, 128;" ::"r"(wg + 1) : "memory");
        asm volatile("st.shared.b32 [%0], %1;\nfence.acq_rel.cta;" ::"r"(T.flag), "r"(0) : "memory");
        G.gate = 0;
        pgap = p0 == pdir ? 4 * pgap + 64 : 0;
        pdir = p0 + 64 + pgap;
      }
      temporal<false>(S, d1, G, P, scaled, lane, lst);
      if (irregular(S, T, lane)) {
      centre:
        resum(S, lane);
      }
      temporal_out<false>(S, T, slot, P, lane, lst);
    }
  stored:
    const uint32_t pn = __shfl_sync(0xffffffffu, p0 + 64, 0);
    bool last = false;
    if (pn >= pstop) {
      if (helper) last = true;
      else if (pstop < npx - 4 * 49) {
        if (((wg & 1) | wp | lane) == 0) {
          const uint32_t nb = gridDim.x, nwh = min(max((int)(2 * nrem - nb), (int)(nrem / 2)), nrem);
          const uint32_t r = atomicAdd(&g_par.ticket, 1u), j = r - nwh;
          sts32(ring + kExtra, r < nwh ? (nfull * nb + r) * 4 + 3 : j < 2 * (nrem - nwh) ? (nfull * nb + nwh + (j >> 1)) * 4 + 1 + (j & 1) : 0);
        }
        __syncwarp();
        pstop = npx - 2 * 49 + 8 * wp;
      } else if (pstop < npx) {
        if (__shfl_sync(0xffffffffu, lds32(ring + kExtra), 0)) npx += 49;
        pstop = npx + 8 * wp;
      } else last = true;
    }
    asm volatile("fence.proxy.async.shared::cta;" ::: "memory");
    __syncwarp();
    mbar_arrive(slot + kDone + (fresh(lane) >= 4 * T.n ? dn : 0), lane & 3);
    __syncwarp();
    if (last) break;
    p0 = pn;
  }
}

struct Frame {
  bool light;
  uint32_t sta;
  uint32_t oo;
  uint32_t e0, e1;
};
__device__ __forceinline__ uint32_t frame_init(Frame& F, uint32_t ring, uint32_t t, int wp, int lane) {
  wp = (wp + t) & 3;
  F.light = wp == 3;
  F.sta = ring + t * (kSlot + 32) + kXBytes + 64 * wp;
  const uint32_t r = 16 * wp + (lane >> 2);
  F.oo = ((r / 7) * (kW - 7) + r) * 192u + (lane & 3) * 16 + (((((r + 8) / 7 - r / 7) * (kW - 7) + 8) * 3u) << 20);
  F.e0 = F.e1 = 0;
  const uint32_t am = t * kPlane + wp * 1024 + ((lane * 65) & 0x3d0);
  return F.light && (lane & 15) ? kZero : am ^ ((am >> 3) & 0x30);
}
template <bool F>
__device__ __forceinline__ void load_frame(uint32_t (&v)[24], uint32_t ma, uint32_t slot, uint32_t& tid) {
  const uint32_t st = ma < kXBytes ? kChunk : 0, mb = ma ^ 32;
  uint32_t a[6] = {ma, mb, mb + st, ma + st, ma + 2 * st, mb + 2 * st};
  pin<6>(a);
  if (F) sfence(tid);
#pragma unroll
  for (int k = 0; k < 6; k++) ldsm4(v + 4 * k, slot + a[k]);
}
__device__ __forceinline__ void load_block(uint32_t (&v)[24], uint32_t ma, uint32_t slot) {
  const uint32_t mb = fresh(ma ^ 32);
  ldsm4(v, ma + slot); ldsm4(v + 4, mb + slot);
  ldsm4(v + 8, mb + (slot + kChunk)); ldsm4(v + 12, ma + (slot + kChunk));
  ldsm4(v + 16, ma + (slot + 2 * kChunk)); ldsm4(v + 20, mb + (slot + 2 * kChunk));
}
__device__ __forceinline__ void load_light(uint32_t (&v)[24], uint32_t t, uint32_t slot, uint32_t tid) {
  const uint32_t r = t * kPlane + 48 * 64, a0 = ((tid & 3) << 2) | ((r >> 3) & 0x30), u = slot + r, off = tid & 28;
  uint32_t a[4] = {a0, a0 ^ 16, a0 ^ 32, a0 ^ 48};
  pin<4>(a);
#pragma unroll
  for (int j = 0; j < 12; j++) {
    asm volatile("mov.b32 %0, 0;" : "=r"(v[2 * j + 1]));
    asm volatile("{\n.reg .pred p;\nsetp.eq.u32 p, %2, 0;\nmov.b32 %0, 0;\n@p ld.shared.b32 %0, [%1];\n}"
                 : "=r"(v[2 * j]) : "r"(a[(j & 3) ^ (j & 4 ? 2 : 0)] + (u + (j >> 2) * kChunk)), "r"(off) : "memory");
  }
}
__device__ __forceinline__ void load_stats(Frame& F, uint32_t ia, uint32_t tid) {
  const uint32_t a = fresh(tid & 0x1c), u = F.sta + ia * 196;
  F.e0 = lds32(a + u);
  F.e1 = lds32(a + (u + 32));
}
template <int OFF>
__device__ __forceinline__ void gemm_u(uint32_t (&u)[24], const uint32_t* s, uint64_t db) {
  constexpr uint32_t kMN = (((kChunk >> 4) - 1) << 16) + OFF / 16;
  asm volatile("" : "+l"(db));
  wg_fence();
  wgmma<2, 1>(u, s, db + kMN); wgmma<1, 1>(u, s + 4, db + kMN + 64); wgmma<1, 1>(u, s + 8, db + kMN + 128); wgmma<1, 1>(u, s + 12, db + kMN + 192);
  wg_commit();
}
__device__ __forceinline__ uint32_t key48(uint32_t (&s)[16], uint32_t tid) {
  return fresh(sel(tid & 3, 0xfc00fc00u, __byte_perm(s[12], s[13], 0x5410)));
}
__device__ __forceinline__ uint32_t amax3(uint32_t a, uint32_t b, uint32_t c) {
  return as_u(__hmax2(__hmax2(__habs2(as_h2(a)), __habs2(as_h2(b))), __habs2(as_h2(c))));
}
struct Quad { uint32_t v[4]; };
__device__ __forceinline__ void sub_max(uint32_t (&s)[16], uint32_t& t) {
  const uint32_t x0 = h2max(h2max(h2max(s[0], s[2]), h2max(s[4], s[6])), h2max(s[8], s[10]));
  const uint32_t x1 = h2max(h2max(h2max(s[1], s[3]), h2max(s[5], s[7])), h2max(s[9], s[11]));
  uint32_t mx = h2max(h2max(__byte_perm(x0, x1, 0x5410), __byte_perm(x0, x1, 0x7632)), t);
  mx = h2max(mx, shfl_x(mx, 1));
  mx = h2max(mx, shfl_x(mx, 2));
#pragma unroll
  for (int j = 0; j < 6; j++) { s[2 * j] = h2sub(s[2 * j], lo2(mx)); s[2 * j + 1] = h2sub(s[2 * j + 1], hi2(mx)); }
  t = h2sub(t, mx);
}
template <int J>
__device__ __forceinline__ Quad exp_sum(uint32_t (&s)[16], uint32_t& t) {
#pragma unroll
  for (int j = J; j < 12; j++) s[j] = h2ex2(s[j]);
  t = h2ex2(t);
  Quad q;
  q.v[0] = h2add(t, fold_add(h2add(h2add(h2add(s[0], s[2]), h2add(s[4], s[6])), h2add(s[8], s[10])),
                             h2add(h2add(h2add(s[1], s[3]), h2add(s[5], s[7])), h2add(s[9], s[11]))));
#pragma unroll
  for (int i = 1; i < 4; i++) q.v[i] = shfl_x(q.v[0], i);
  return q;
}
__device__ __forceinline__ Quad soft_exp(uint32_t (&s)[16], uint32_t& t) {
  const uint32_t am = h2max(h2max(h2max(amax3(s[0], s[1], s[2]), amax3(s[3], s[4], s[5])), amax3(s[6], s[7], s[8])), h2max(amax3(s[9], s[10], s[11]), t));
  uint32_t rare, sp[4];
#pragma unroll
  for (int j = 0; j < 4; j++) sp[j] = fresh(h2ex2(s[j]));
  asm("{\n.reg .pred p, q;\n.reg .b32 t;\nmov.b32 t, 0x49004900;\nsetp.le.f16x2 p|q, %1, t;\nand.pred p, p, q;\nselp.b32 %0, 0, 1, p;\n}" : "=r"(rare) : "r"(am));
  if (__any_sync(0xffffffffu, rare)) {
    sub_max(s, t);
#pragma unroll
    for (int j = 0; j < 4; j++) sp[j] = h2ex2(s[j]);
  }
#pragma unroll
  for (int j = 0; j < 4; j++) s[j] = sp[j];
  return exp_sum<4>(s, t);
}
__device__ __forceinline__ void soft_norm(uint32_t (&s)[16], uint32_t& t, const Quad& q, const Frame& F, float2 e, uint32_t tid) {
  const float2 d = unpack_h2(h2add(h2add(q.v[0], q.v[1]), h2add(q.v[2], q.v[3])));
  const uint32_t cb = pack_h2(rcp_fast(d.x * e.x), rcp_fast(d.y * e.y)) & (sel(tid & 28, 0u, 0xffffu) | fresh(F.light ? 0u : 0xffffffffu));
#pragma unroll
  for (int j = 0; j < 6; j++) { s[2 * j] = h2mul(s[2 * j], lo2(cb)); s[2 * j + 1] = h2mul(s[2 * j + 1], hi2(cb)); }
  t = fresh(h2mul(t, cb));
  pin<12>(s);
}
__device__ __forceinline__ void soft_tail(uint32_t (&s)[16], uint32_t t) {
  s[12] = t & 0xffffu; s[13] = t >> 16;
  asm volatile("mov.b32 %0, 0;\nmov.b32 %1, 0;" : "=r"(s[14]), "=r"(s[15]));
}
template <int H>
__device__ __forceinline__ uint8_t* row_ptr(const Frame& F, uint8_t* o) {
  const uint32_t oo = fresh(F.oo);
  if (H) asm volatile("mad.wide.u32 %0, %1, 64, %0;" : "+l"(o) : "r"(oo >> 20));
  else { o += oo & 0xfffffu; asm volatile("" : "+l"(o)); }
  return o;
}
template <int H>
__device__ __forceinline__ void affine(uint32_t* r, const uint32_t (&v)[24], const Frame& F) {
  const uint32_t e = H ? F.e1 : F.e0;
#pragma unroll
  for (int j = 0; j < 12; j++) r[j] = h2fma(v[2 * j + H], lo2(e), hi2(e));
  pin<12>(r);
}
template <int H, bool kFence = false>
__device__ __forceinline__ void finish(uint32_t* r, const Frame& F, uint8_t*& o, uint32_t off, uint32_t a, uint32_t m, uint32_t& fz) {
  o = row_ptr<H>(F, o);
#pragma unroll
  for (int j = 0; j < 12; j += 2) { const float2 f = unpack_h2(r[j]), g = unpack_h2(r[j + 1]); r[j] = pack_bf2(f.x, g.x); r[j + 1] = pack_bf2(f.y, g.y); }
  pin<12>(r);
  if (kFence) sfence(fz);
  stg3(o, r, off | (fresh(a) & m));
}
__device__ __forceinline__ uint32_t surplus(uint32_t ring, uint32_t i, uint32_t nfull) { return i + 4 == nfull ? lds32(ring + kExtra) >> 2 : 0; }

__device__ __forceinline__ void release(uint32_t ring, uint32_t slot, uint32_t i, uint32_t nfull, uint32_t w, const CUtensorMap* tm, uint32_t lane) {
  uint32_t old = 0;
  asm volatile("{\n.reg .pred p;\nsetp.eq.u32 p, %2, 0;\n@p atom.relaxed.cta.shared::cta.inc.u32 %0, [%1], 1;\n}" : "+r"(old) : "r"(slot + kRel), "r"(lane) : "memory");
  if (old) {
    sts32(slot + kWide, 0);
    if (i + 4 < nfull) tma_load_win(slot, tm, w + 4 * gridDim.x);
    else if (const uint32_t wn = surplus(ring, i, nfull)) tma_load_win(slot, tm, fresh(wn));
    else mbar_arrive(slot + kFull);
  }
  __syncwarp();
}
__device__ __forceinline__ uint32_t window_offset(uint32_t w) { return (((w * 57457u) >> 22) * (7 * kW - 7 * kNWX) + w * 7) * 192u; }

__device__ __forceinline__ void round_wide(uint32_t ring, uint64_t d0, uint32_t frame, uint32_t nfull, uint32_t i, uint32_t w, int sg, int wp, uint32_t lane,
                                           const CUtensorMap* tm, uint8_t* __restrict__ out) {
  const uint32_t slot = ring + (i & 3) * kSlot;
  uint32_t x[24];
#pragma unroll
  for (int j = 0; j < 24; j++) x[j] = 0;
#pragma unroll 1
  for (uint32_t t = 2 * sg; t < 2 * sg + 2; t++) {
    Frame F;
    uint32_t v[24], s[16];
    load_frame<false>(v, frame_init(F, ring, t, wp, lane), slot, lane);
    load_stats(F, i & 3, lane);
    const uint64_t dp = d0 + (uint32_t)((kWBytes + (i & 3) * kSlot + t * kPlane) / 16);
    gemm<2, kOffAs, 6144>(x, v, d0);
    const uint32_t cs = dup_h2(PAR(ring, cS_s));
    const float kb = PAR(ring, kb), ik = rcp_fast(PAR(ring, kappa));
    wg_wait(); pin<24>(x);
    gemm<0, 0, kChunk>(s, x, dp);
    wg_wait(); pin<14>(s);
    uint32_t u = key48(s, lane);
    sub_max(s, u);
#pragma unroll
    for (int j = 0; j < 12; j++) s[j] = h2mul(s[j], cs);
    u = h2mul(u, cs);
    const float2 z0 = stat_f32(F.e0), z1 = stat_f32(F.e1);
    const float e0 = fmaxf(z0.x, kb), e1 = fmaxf(z1.x, kb);
    const uint32_t aw = pack_h2(__fdividef(z0.x, e0), __fdividef(z1.x, e1));
#pragma unroll
    for (int j = 0; j < 12; j++) { v[2 * j] = h2mul(v[2 * j], lo2(aw)); v[2 * j + 1] = h2mul(v[2 * j + 1], hi2(aw)); }
    soft_norm(s, u, exp_sum<0>(s, u), F, make_float2(e0 * ik, e1 * ik), lane);
    soft_tail(s, u);
    gemm_u<0>(x, s, dp);
    wg_wait(); pin<24>(x);
    gemm<1, kOffWs, 6144>(v, x, d0);
    if ((t & 1) && wp == 0) release(ring, slot, i, nfull, w, tm, lane);
    wg_wait(); pin<24>(v);
    uint8_t* o = out + (size_t)(window_offset(w) + t * frame);
#pragma unroll
    for (int h = 0; h < 2; h++) {
      const float e = h ? e1 : e0, m = h ? z1.y : z0.y;
      uint32_t r[12];
#pragma unroll
      for (int j = 0; j < 12; j += 2) {
        const float2 f = unpack_h2(v[2 * j + h]), g = unpack_h2(v[2 * j + 2 + h]);
        r[j] = pack_bf2(fmaf(f.x, e, m), fmaf(g.x, e, m)); r[j + 1] = pack_bf2(fmaf(f.y, e, m), fmaf(g.y, e, m));
      }
      o = h ? row_ptr<1>(F, o) : row_ptr<0>(F, o);
      stg3(o, r, F.light ? (h ? 1 : lane & 28) : 0);
    }
  }
}

__device__ __forceinline__ uint32_t rounds(uint32_t ring, uint64_t d0, uint64_t d1, uint32_t frame, uint32_t nfull, uint32_t i, uint32_t i1, uint32_t w,
                                           int sg, int wp, int lane, const CUtensorMap* tm, uint8_t* __restrict__ out) {
  Frame A, B;
  uint32_t tid = lane + (frame_init(A, ring, 2 * sg, wp, lane) << 4) + (frame_init(B, ring, 2 * sg + 1, wp, lane) << 16);
  uint32_t va[24], vb[24], x[24], sa[16], sc[16], r0[12], r1[12], ta, tb;
  Quad rs;
  uint32_t& fz = A.oo;
#pragma unroll
  for (int j = 0; j < 24; j++) { vb[j] = 0; x[j] = 0; }
  out += sg * 2 * frame;
  asm volatile("" : "+l"(out));
  uint8_t *ob = out, *o;
  const uint64_t dr = d0 + (uint32_t)(kWBytes / 16 + sg * (2 * kPlane / 16));
  uint32_t slot = ring + (i & 3) * kSlot, first = 1;
  load_frame<false>(va, (tid >> 4) & 0xfff0u, slot, tid);
  do {
    const uint32_t ia = i & 3;
    tid = fresh(tid);
    gemm<2, kOffAs, 6144>(x, va, d0);
    sfence(fz);
    affine<0>(r0, vb, B); affine<1>(r1, vb, B);
    load_frame<true>(vb, (tid >> 16) & 0xfff0u, slot, fz);
    uint64_t dp = dr + ia * (kSlot / 16);
    asm volatile("" : "+l"(dp));
    o = ob + frame;
    asm volatile("" : "+l"(o));
    finish<0, true>(r0, B, o, first, tid, B.light ? 28 : 0, fz);
    sfence(fz);
    wg_wait(); pin<24>(x);
    gemm<0, 0, kChunk>(sa, x, dp);
    if (!B.light) finish<1>(r1, B, o, first, 0, 0, fz);
    else if (sg == 0) {
      if ((tid & 31) == 0) {
        if (i + 4 < nfull) tma_prefetch_win(tm, w + 4 * gridDim.x);
        else if (const uint32_t wn = surplus(ring, i, nfull)) tma_prefetch_win(tm, fresh(wn));
      }
      __syncwarp();
    }
    ob = out + (size_t)window_offset(w);
    asm volatile("" : "+l"(ob));
    wg_wait(); pin<14>(sa);
    gemm<2, kOffAs, 6144>(x, vb, d1);
    ta = key48(sa, tid);
    rs = soft_exp(sa, ta);
    load_stats(A, ia, tid);
    sfence(fz);
    wg_wait(); pin<24>(x);
    gemm<0, kPlane, kChunk>(sc, x, dp);
    sfence(fz);
    soft_norm(sa, ta, rs, A, make_float2(low_f(A.e0), low_f(A.e1)), tid);
    sfence(fz);
    wg_wait(); pin<14>(sc);
    tb = key48(sc, tid);
    sfence(fz);
    soft_tail(sa, ta);
    gemm_u<0>(x, sa, dp);
    rs = soft_exp(sc, tb);
    load_stats(B, ia, tid);
    sfence(fz);
    wg_wait(); pin<24>(x);
    gemm<1, kOffWs, 6144>(va, x, d0);
    sfence(fz);
    soft_norm(sc, tb, rs, B, make_float2(low_f(B.e0), low_f(B.e1)), tid);
    soft_tail(sc, tb);
    sfence(fz);
    wg_wait(); pin<24>(va);
    gemm_u<kPlane>(x, sc, dp);
    sfence(fz);
    const uint32_t sn = ring + ((i + 1) & 3) * kSlot;
    const bool slow = mbar_pending_or<kWide - kDone>(sn + kDone, (i + 1) >> 2);
    affine<0>(r0, va, A);
    o = ob;
    finish<0>(r0, A, o, 0, tid, A.light ? 28 : 0, fz);
    sfence(fz);
    wg_wait(); pin<24>(x);
    gemm<1, kOffWs, 6144>(vb, x, d1);
    affine<1>(r1, va, A);
    if (slow || A.light) {
      if (A.light) release(ring, slot, i, nfull, w, tm, tid & 31);
      if (slow) {
        if (i + 1 < i1) mbar_wait(sn + kDone, (i + 1) >> 2);
        if (__any_sync(0xffffffffu, lds32(sn + kWide))) i1 = 0;
      }
    }
    const uint32_t la = (tid >> 4) & 0xfff0u;
    if (!A.light) { load_block(va, la, sn); finish<1>(r1, A, o, 0, la, 0, fz); }
    else load_light(va, 2 * sg, sn, tid);
    wg_wait(); pin<24>(vb);
    launder<24>(vb);
    launder<24>(va);
    slot = sn; w += gridDim.x; first = 0;
  } while (++i < i1);
  o = ob + frame;
  affine<0>(r0, vb, B); finish<0>(r0, B, o, 0, tid, B.light ? 28 : 0, tid);
  affine<1>(r1, vb, B); finish<1>(r1, B, o, B.light, 0, 0, tid);
  return i;
}

__device__ __forceinline__ void run_S(uint32_t ring, uint64_t d0, uint64_t d1, uint32_t frame, uint32_t nfull, uint32_t i, uint32_t i1, uint32_t w0,
                                      int sg, int wp, const CUtensorMap* tm, uint8_t* __restrict__ out) {
  do {
    const uint32_t lane = fresh(threadIdx.x) & 31;
    const uint32_t slot = ring + (i & 3) * kSlot, w = w0 + i * gridDim.x;
    mbar_wait(slot + kDone, i >> 2);
    if (__any_sync(0xffffffffu, (lds32(slot + kWide) != 0) | (PAR(ring, cS_s) != 1.f) | (PAR(ring, kappa) != 1.f))) {
      round_wide(ring, d1, frame, nfull, i, w, sg, wp, lane, tm, out);
      i++;
    } else {
      i = rounds(ring, d0, d1, frame, nfull, i, i1, w, sg, wp, lane, tm, out);
    }
  } while (i < i1);
}

struct Maps { CUtensorMap load, prefetch; };
__global__ void __launch_bounds__(512, 1) swin_main(const __grid_constant__ Maps tms, uint8_t* __restrict__ out, const uint64_t d0,
                                                    const uint64_t d1, const uint32_t frame) {
  extern __shared__ __align__(1024) uint8_t smem[];
  const CUtensorMap& tm = tms.load;
  const uint32_t sb = smem_u32(smem), ring = sb + kWBytes;
  const int tid = threadIdx.x;
  const int wg = __shfl_sync(0xffffffffu, tid >> 7, 0);
  const int wp = __shfl_sync(0xffffffffu, (tid >> 5) & 3, 0);
  const int lane = tid & 31;
  const uint32_t b = blockIdx.x, nb = gridDim.x;
  const uint32_t nfull = kNWIN / nb, nrem = kNWIN - nfull * nb;
  if (tid == 0) {
    if (sb != 1024 || nfull > 700 || nfull < 12) __trap();
#pragma unroll
    for (int i = 0; i < 4; i++) {
      mbar_init(ring + i * kSlot + kFull, 1);
      mbar_init(ring + i * kSlot + kDone, 49);
      sts32(ring + i * kSlot + kRel, 0); sts32(ring + i * kSlot + kFlag, 0); sts32(ring + i * kSlot + kWide, 0);
    }
    asm volatile("fence.mbarrier_init.release.cluster;" ::: "memory");
    for (int i = 0; i < 2; i++) tma_load_win(ring + i * kSlot, &tm, b + i * nb);
  }
  __syncwarp();
  if (wg == 1 || wg == 2)
    asm volatile("st.shared.v4.b32 [%0], {%1,%1,%1,%1};" ::"r"(ring + ((tid - 128) >> 6) * kSlot + kXBytes + (tid & 63) * 16), "r"(0) : "memory");
  __syncthreads();
  asm volatile("griddepcontrol.wait;" ::: "memory");
#pragma unroll
  for (int q = 0; q < kWBytes / 16 / 512; q++)
    asm volatile("cp.async.cg.shared.global [%0], [%1], 16;" ::"r"(sb + (tid + q * 512) * 16), "l"(g_wimg + tid + q * 512) : "memory");
  if (wg == 0 && wp < 3) {
    static_assert(kWBytes / 16 == 9 * 512 + 96, "weight copy split");
    const int e = tid + 9 * 512;
    asm volatile("cp.async.cg.shared.global [%0], [%1], 16;" ::"r"(sb + e * 16), "l"(g_wimg + e) : "memory");
  }
  if (wg == 0 && wp == 3)
    asm volatile("cp.async.ca.shared.global [%0], [%1], 4;" ::"r"(ring + kPar + lane * 4), "l"(reinterpret_cast<const float*>(&g_par) + lane) : "memory");
  asm volatile("cp.async.wait_all;\nfence.proxy.async.shared::cta;" ::: "memory");
  __syncthreads();
  const float kb = PAR(ring, kb);
  TPar P;
  P.kt = PAR(ring, kt);
  P.e2max = 4.f * rcp_fast(fmaxf(PAR(ring, ka), 1.f / 64.f));
  P.sgmin = fmaxf(0.0045f, kb * 0.011f);
  P.outmax = fmaf(kb, -627.2f, 60000.f);
  const bool scaled = __any_sync(0xffffffffu, PAR(ring, cS_t) != 1.f);
  const uint32_t pdir = __ballot_sync(0xffffffffu, scaled || !(P.kt <= 256.f));
  if (tid == 128) for (int i = 2; i < 4; i++) tma_load_win(ring + i * kSlot, &tm, b + i * nb);
  __syncwarp();
  const bool isT = wg < 2;
  run_T(ring, d0, d1, nfull, nrem, !isT, wg, wp, lane, P, scaled, pdir);
  const uint32_t ex = isT ? __shfl_sync(0xffffffffu, lds32(ring + kExtra), 0) : 3;
  if ((ex >> (wg & 1)) & 1) run_S(ring, d0, d1, frame, nfull, isT ? nfull : 0, nfull + isT, isT ? (ex >> 2) - nfull * nb : b, wg & 1, wp, &tm, out);
}

__device__ __forceinline__ int ch_pos(int ch) { return 32 * (ch >> 5) + 16 * ((ch >> 2) & 1) + 8 * (ch & 1) + 2 * ((ch >> 3) & 3) + ((ch >> 1) & 1); }
__device__ __forceinline__ float pow2_ceil(float v) {
  return __uint_as_float((__float_as_uint(v) + 0x7fffffu) & 0x7f800000u);
}

constexpr int kPrepSplit = 12;
constexpr int kPrepThreads = 384;
__global__ void __launch_bounds__(kPrepThreads) swin_prep(const __nv_bfloat16* __restrict__ wqkv_t, const __nv_bfloat16* __restrict__ wo_t,
                                                          const __nv_bfloat16* __restrict__ wqkv_s, const __nv_bfloat16* __restrict__ wo_s) {
  asm volatile("griddepcontrol.launch_dependents;");
  __shared__ __align__(16) uint32_t raw[2][96][52];
  __shared__ __align__(16) uint32_t mu[3][52];
  __shared__ float nrm[12], nrm2[6], csum[6][9];
  const int mat = blockIdx.x / kPrepSplit, blk = blockIdx.x % kPrepSplit;
  const int tid = threadIdx.x, lane = tid & 31, warp = tid >> 5, g = lane >> 2, c = lane & 3;
  const __nv_bfloat16* wqkv = mat < 2 ? wqkv_t : wqkv_s;
  const __nv_bfloat16* wo = mat < 2 ? wo_t : wo_s;
  const bool isA = (mat & 1) == 0;
  {
    uint4 v[3], u[3];
#pragma unroll
    for (int q = 0; q < 3; q++) {
      const int e = tid + q * kPrepThreads, i = e / 12, c8 = (e % 12) * 8;
      v[q] = __ldg(reinterpret_cast<const uint4*>(wqkv + i * 288 + (isA ? 0 : 192) + c8));
      u[q] = __ldg(reinterpret_cast<const uint4*>(isA ? wqkv + i * 288 + 96 + c8 : wo + i * 96 + c8));
    }
#pragma unroll
    for (int q = 0; q < 3; q++) {
      const int e = tid + q * kPrepThreads, i = e / 12, c4 = (e % 12) * 4;
      *reinterpret_cast<uint4*>(&raw[0][i][c4]) = v[q];
      *reinterpret_cast<uint4*>(&raw[1][i][c4]) = u[q];
    }
  }
  __syncthreads();
  {
    const int m = warp / 6, cp = (warp % 6) * 8 + g;
    float s0 = 0.f, s1 = 0.f, q0 = 0.f, q1 = 0.f;
#pragma unroll
    for (int i = 0; i < 24; i++) {
      const uint32_t w = raw[m][4 * i + c][cp];
      const float lo = __uint_as_float(w << 16), hi = __uint_as_float(w & 0xffff0000u);
      s0 += lo; s1 += hi; q0 = fmaf(lo, lo, q0); q1 = fmaf(hi, hi, q1);
    }
    s0 = quad_sum(s0) * (1.f / 96.f); s1 = quad_sum(s1) * (1.f / 96.f); q0 = quad_sum(q0); q1 = quad_sum(q1);
    if (mat == 1 && m == 1) {
      float r0 = 0.f, r1 = 0.f;
#pragma unroll
      for (int i = 0; i < 12; i++) {
        const uint32_t w0 = raw[1][2 * cp][4 * i + c], w1 = raw[1][2 * cp + 1][4 * i + c];
        r0 += __uint_as_float(w0 << 16) + __uint_as_float(w0 & 0xffff0000u);
        r1 += __uint_as_float(w1 << 16) + __uint_as_float(w1 & 0xffff0000u);
      }
      r0 = quad_sum(r0) * (1.f / 96.f); r1 = quad_sum(r1) * (1.f / 96.f);
      s0 = r0; s1 = r1;
    }
    if (m == 1 && c == 0) {
      const uint32_t hi = mat == 3 ? 0u : pack_bf2(s0, s1);
      mu[0][cp] = hi;
      mu[1][cp] = mat == 3 ? 0u : pack_bf2(s0 - __uint_as_float(hi << 16), s1 - __uint_as_float(hi & 0xffff0000u));
      mu[2][cp] = 0u;
    }
    if (m == 0 || isA) {
      q0 = fmaxf(fmaf(-96.f * s0, s0, q0), 0.f) + q0 * 1e-6f;
      q1 = fmaxf(fmaf(-96.f * s1, s1, q1), 0.f) + q1 * 1e-6f;
    }
    const bool usemax = m == 1 && mat == 3;
    float t = usemax ? fmaxf(q0, q1) : q0 + q1;
#pragma unroll
    for (int o = 4; o < 32; o <<= 1) { const float z = __shfl_xor_sync(0xffffffffu, t, o); t = usemax ? fmaxf(t, z) : t + z; }
    if (lane == 0) nrm[warp] = t;
  }
  __syncthreads();
  if (warp >= 6) return;
  float d[4] = {0.f, 0.f, 0.f, 0.f}, e[4] = {0.f, 0.f, 0.f, 0.f}, v0, v1;
  {
    const uint32_t arow = smem_u32(&raw[0][16 * warp + (lane & 15)][(lane >> 4) * 4]);
    const uint32_t brow = isA ? smem_u32(&raw[1][blk * 8 + (lane & 7)][(lane >> 3) * 4]) : smem_u32(&raw[1][lane][blk * 4]);
    const uint32_t mrow = smem_u32(&mu[min(lane & 7, 2)][(lane >> 3) * 4]);
#pragma unroll
    for (int k2 = 0; k2 < 3; k2++) {
      uint32_t b[4], m[4];
      if (isA) ldsm4(b, brow + k2 * 64);
      else asm volatile("ldmatrix.sync.aligned.m8n8.x4.trans.shared.b16 {%0,%1,%2,%3}, [%4];"
                        : "=r"(b[0]), "=r"(b[1]), "=r"(b[2]), "=r"(b[3]) : "r"(brow + k2 * (32 * 208)) : "memory");
      ldsm4(m, mrow + k2 * 64);
#pragma unroll
      for (int hf = 0; hf < 2; hf++) {
        uint32_t a[4];
        ldsm4(a, arow + (2 * k2 + hf) * 32);
        asm volatile("mma.sync.aligned.m16n8k16.row.col.f32.bf16.bf16.f32 {%0,%1,%2,%3},{%4,%5,%6,%7},{%8,%9},{%0,%1,%2,%3};"
                     : "+f"(d[0]), "+f"(d[1]), "+f"(d[2]), "+f"(d[3])
                     : "r"(a[0]), "r"(a[1]), "r"(a[2]), "r"(a[3]), "r"(b[2 * hf]), "r"(b[2 * hf + 1]));
        asm volatile("mma.sync.aligned.m16n8k16.row.col.f32.bf16.bf16.f32 {%0,%1,%2,%3},{%4,%5,%6,%7},{%8,%9},{%0,%1,%2,%3};"
                     : "+f"(e[0]), "+f"(e[1]), "+f"(e[2]), "+f"(e[3])
                     : "r"(a[0]), "r"(a[1]), "r"(a[2]), "r"(a[3]), "r"(m[2 * hf]), "r"(m[2 * hf + 1]));
      }
    }
    v0 = __shfl_sync(0xffffffffu, e[0] + e[1], lane & ~3); v1 = __shfl_sync(0xffffffffu, e[2] + e[3], lane & ~3);
    d[0] -= v0; d[1] -= v0; d[2] -= v1; d[3] -= v1;
    float t0 = d[0] + d[2], t1 = d[1] + d[3], t2 = v0 + v1;
#pragma unroll
    for (int o = 4; o < 32; o <<= 1) {
      t0 += __shfl_xor_sync(0xffffffffu, t0, o); t1 += __shfl_xor_sync(0xffffffffu, t1, o); t2 += __shfl_xor_sync(0xffffffffu, t2, o);
    }
    if (g == 0) { csum[warp][2 * c] = t0; csum[warp][2 * c + 1] = t1; csum[warp][8] = t2; }
  }
  const float nl = nrm[0] + nrm[1] + nrm[2] + nrm[3] + nrm[4] + nrm[5];
  const float nr = mat == 3 ? fmaxf(fmaxf(fmaxf(nrm[6], nrm[7]), fmaxf(nrm[8], nrm[9])), fmaxf(nrm[10], nrm[11]))
                            : nrm[6] + nrm[7] + nrm[8] + nrm[9] + nrm[10] + nrm[11];
  const float bound = __fsqrt_rn(nl) * __fsqrt_rn(nr) * 1.01f;
  const float f = isA ? 0.14724448f : 1.f;
  float sc = pow2_ceil(fmaxf(bound * (isA ? 0.14724448f / 160.f : mat == 1 ? 1.f / 16.f : 1.f / 64.f), 1e-30f));
  const float kb = sc;
  if (isA) sc = fminf(fmaxf(sc, 1.f), 32768.f);
  if (mat == 3 && sc <= 1.f && sc >= 1.f / 1024.f) sc = 1.f;
  const float mul = f * __uint_as_float(0x7f000000u - __float_as_uint(sc));
  if (blk == 0 && tid < 8) reinterpret_cast<float*>(&g_par)[8 * mat + tid] = tid == 0 ? sc : tid == 1 ? kb : 0.f;
  asm volatile("bar.sync 1, 192;" ::: "memory");
  float mean[2];
#pragma unroll
  for (int b = 0; b < 2; b++)
    mean[b] = (csum[0][2 * c + b] + csum[1][2 * c + b] + csum[2][2 * c + b] + csum[3][2 * c + b] + csum[4][2 * c + b] + csum[5][2 * c + b]) *
              (1.f / 96.f);
  const uint32_t img = mat == 0 ? 0 : mat == 1 ? kOffWt : mat == 2 ? kOffAs : kOffWs;
  const float vmean = (csum[0][8] + csum[1][8] + csum[2][8] + csum[3][8] + csum[4][8] + csum[5][8]) * (1.f / 96.f);
  float off = 0.f;
  if (mat == 2) {
    float q2 = 0.f;
#pragma unroll
    for (int q = 0; q < 4; q++) q2 = fmaf(d[q] - mean[q & 1], d[q] - mean[q & 1], q2);
#pragma unroll
    for (int o = 16; o; o >>= 1) q2 += __shfl_xor_sync(0xffffffffu, q2, o);
    if (lane == 0) nrm2[warp] = q2;
    asm volatile("bar.sync 1, 192;" ::: "memory");
    q2 = nrm2[0] + nrm2[1] + nrm2[2] + nrm2[3] + nrm2[4] + nrm2[5];
    off = 1.5f * pow2_ceil(fmaxf(__fsqrt_rn(q2 * (1.f / 768.f)) * mul * 3.f, 1e-4f));
  }
  __half (*stage)[8][96] = reinterpret_cast<__half (*)[8][96]>(&raw[0][0][0]);
#pragma unroll
  for (int q = 0; q < 4; q++) {
    const int kp = ch_pos(16 * warp + g + 8 * (q >> 1));
    const float o = (d[q] - mean[q & 1]) * mul;
    stage[0][2 * c + (q & 1)][kp] = __float2half_rn(mat == 2 ? o + off : __uint_as_float((__float_as_uint(o) + 0x8000u) & 0xffff0000u));
    stage[1][2 * c + (q & 1)][kp] = __float2half_rn((q & 1) ? ((q >> 1 ? v1 : v0) - vmean) * mul : 1.f / 96.f);
  }
  asm volatile("bar.sync 1, 192;" ::: "memory");
  const int ext = tid >= 96, n = (tid >> 2) & 7, ch = (tid - 96 * ext) >> 5;
  if (!ext || (mat == 1 && blk == 0)) {
    uint32_t a = (ext ? 0 : img) + ch * (mat < 2 ? kAtChunk : 6144) + (ext ? 96 + n : ch_pos(blk * 8 + n)) * 64 + c * 16;
    a ^= ((a >> 7) & 3) << 4;
    g_wimg[a >> 4] = *reinterpret_cast<const uint4*>(&stage[ext][n][32 * ch + 8 * c]);
  }
}

typedef CUresult (*EncodeFn)(CUtensorMap*, CUtensorMapDataType, cuuint32_t, void*, const cuuint64_t*, const cuuint64_t*,
                             const cuuint32_t*, const cuuint32_t*, CUtensorMapInterleave, CUtensorMapSwizzle,
                             CUtensorMapL2promotion, CUtensorMapFloatOOBfill);

}

extern "C" void kernel_launch(void* const* d_in, const int* in_sizes, int n_in, void* d_out, int out_size) {
  (void)in_sizes; (void)n_in; (void)out_size;
  static EncodeFn enc = nullptr;
  static int nsm = 0;
  if (!enc) {
    void* fn = nullptr;
    cudaDriverEntryPointQueryResult qr;
    cudaGetDriverEntryPoint("cuTensorMapEncodeTiled", &fn, cudaEnableDefault, &qr);
    enc = reinterpret_cast<EncodeFn>(fn);
    int dev = 0;
    cudaGetDevice(&dev);
    cudaDeviceGetAttribute(&nsm, cudaDevAttrMultiProcessorCount, dev);
    cudaFuncSetAttribute(swin_main, cudaFuncAttributeMaxDynamicSharedMemorySize, kSmemBytes);
  }
  Maps tms;
  CUtensorMap& tm = tms.load;
  const cuuint64_t dims[5] = {32, kW, kH, kT, 3};
  const cuuint64_t strides[4] = {192, 192ull * kW, 192ull * kW * kH, 64};
  const cuuint32_t box[5] = {32, 7, 7, 4, 3};
  const cuuint32_t es[5] = {1, 1, 1, 1, 1};
  enc(&tm, CU_TENSOR_MAP_DATA_TYPE_BFLOAT16, 5, d_in[0], dims, strides, box, es, CU_TENSOR_MAP_INTERLEAVE_NONE,
      CU_TENSOR_MAP_SWIZZLE_64B, CU_TENSOR_MAP_L2_PROMOTION_L2_128B, CU_TENSOR_MAP_FLOAT_OOB_FILL_NONE);

  const cuuint64_t dims2[3] = {24ull * kW, kH, kT};
  const cuuint64_t strides2[2] = {192ull * kW, 192ull * kW * kH};
  const cuuint32_t box2[3] = {168, 7, 4};
  enc(&tms.prefetch, CU_TENSOR_MAP_DATA_TYPE_UINT64, 3, d_in[0], dims2, strides2, box2, es, CU_TENSOR_MAP_INTERLEAVE_NONE,
      CU_TENSOR_MAP_SWIZZLE_NONE, CU_TENSOR_MAP_L2_PROMOTION_L2_128B, CU_TENSOR_MAP_FLOAT_OOB_FILL_NONE);

  cudaStream_t st = cudaStreamPerThread;
  swin_prep<<<4 * kPrepSplit, kPrepThreads, 0, st>>>(
      static_cast<const __nv_bfloat16*>(d_in[1]), static_cast<const __nv_bfloat16*>(d_in[2]),
      static_cast<const __nv_bfloat16*>(d_in[3]), static_cast<const __nv_bfloat16*>(d_in[4]));

  cudaLaunchConfig_t cfg = {};
  cfg.gridDim = dim3(nsm);
  cfg.blockDim = dim3(512);
  cfg.dynamicSmemBytes = kSmemBytes;
  cfg.stream = st;
  cudaLaunchAttribute at[1];
  at[0].id = cudaLaunchAttributeProgrammaticStreamSerialization;
  at[0].val.programmaticStreamSerializationAllowed = 1;
  cfg.attrs = at;
  cfg.numAttrs = 1;
  cudaLaunchKernelEx(&cfg, swin_main, tms, static_cast<uint8_t*>(d_out), mk_desc(1024), mk_desc(1024), (uint32_t)(kH * kW * 192));
}
```
